```python
import torch

def _softmax(x, axis=-1):
    return torch.softmax(x, dim=axis)
def _gelu(x):
    return torch.nn.functional.gelu(x, approximate="tanh")
def _silu(x):
    return torch.nn.functional.silu(x)
def _sigmoid(x):
    return torch.sigmoid(x)
def _layernorm(x, axis=-1, eps=1e-5):
    m = x.mean(dim=axis, keepdim=True)
    v = x.var(dim=axis, keepdim=True, unbiased=False)
    return (x - m) / torch.sqrt(v + eps)
def _scatter_add(tgt, idx, src, axis=0):
    return tgt.clone().index_add_(axis, idx, src)
def _segment_sum(src, seg, n):
    out = torch.zeros((n,) + src.shape[1:], dtype=src.dtype)
    return out.index_add_(0, seg, src)
def _pad(x, pw):
    flat = tuple(v for pair in reversed(pw) for v in pair)
    return torch.nn.functional.pad(x, flat)

kernel_name = 'gated_mix__compressed_kv_cla__sliding_local_dilated__prompt'

def setup_inputs():

    _w = (lambda a: (lambda t: t.to(torch.bfloat16) if t.is_floating_point() else t)(torch.as_tensor(a)))
    def _A_setup():
        B, H, Sq, Sk, D, M = 1, 32, 2048, 2048, 128, 1024
        Dc = 4 * D
        return {
            "x": _w((lambda *s: torch.randn(*s, dtype=torch.bfloat16) * 0.05)(B, Sq, M)),
            "c_kv": _w((lambda *s: torch.randn(*s, dtype=torch.bfloat16) * 1.6)(B, Sk, Dc)),
            "w_q": _w((lambda *s: torch.randn(*s, dtype=torch.bfloat16) * 6.4)(M, H, D) * (M ** -0.5)),
            "w_uk": _w((lambda *s: torch.randn(*s, dtype=torch.bfloat16) * 6.4)(Dc, H, D) * (Dc ** -0.5)),
            "w_uv": _w((lambda *s: torch.randn(*s, dtype=torch.bfloat16) * 1.6)(Dc, H, D) * (Dc ** -0.5)),
            "w_o": _w((lambda *s: torch.randn(*s, dtype=torch.bfloat16) * 1.6)(H, D, M) * ((H * D) ** -0.5)),
        }
    _A_in = _A_setup()

    def _B_setup():
        B, S, D = 1, 2048, 1024
        return {
            "x": _w((lambda *s: torch.randn(*s, dtype=torch.bfloat16) * 0.05)(B, S, D)),
            "wqkv": _w((lambda *s: torch.randn(*s, dtype=torch.bfloat16) * 0.8)(D, 3 * D)),
            "wo": _w((lambda *s: torch.randn(*s, dtype=torch.bfloat16) * 0.05)(D, D)),
        }
    _B_in = _B_setup()

    return {
        "A_x": _A_in["x"],
        "A_c_kv": _A_in["c_kv"],
        "A_w_q": _A_in["w_q"],
        "A_w_uk": _A_in["w_uk"],
        "A_w_uv": _A_in["w_uv"],
        "A_w_o": _A_in["w_o"],
        "B_x": _B_in["x"],
        "B_wqkv": _B_in["wqkv"],
        "B_wo": _B_in["wo"],
        "gate_w": _w((lambda *s: torch.randn(*s, dtype=torch.bfloat16) * 0.05)(1024) * 16.0),
    }

def reference(A_x, A_c_kv, A_w_q, A_w_uk, A_w_uv, A_w_o, B_x, B_wqkv, B_wo, gate_w):
    def _A_ref(x, c_kv, w_q, w_uk, w_uv, w_o):
        B, Sq, M = x.shape[0], x.shape[1], x.shape[2]
        Sk = c_kv.shape[1]
        H, D = w_q.shape[1], w_q.shape[2]
        q = torch.einsum("bqm,mhd->bhqd", x, w_q)
        k = torch.einsum("bkc,chd->bhkd", c_kv, w_uk)
        v = torch.einsum("bkc,chd->bhkd", c_kv, w_uv)
        scores = torch.einsum("bhqd,bhkd->bhqk", q, k) * (D ** -0.5)
        off = Sk - Sq
        qi = torch.arange(Sq)[:, None]
        kj = torch.arange(Sk)[None, :]
        cmask = kj <= (qi + off)
        scores = torch.where(cmask[None, None], scores, -1e9)
        p = _softmax(scores, axis=-1)
        ctx = torch.einsum("bhqk,bhkd->bhqd", p, v)
        return torch.einsum("bhqd,hdm->bqm", ctx, w_o)

    def _B_ref(x, wqkv, wo):
        B, S, D = x.shape
        H = 32; Dh = D // H
        W, dil = 8, 2
        qkv = (lambda x, *d: x.permute(*d))((x @ wqkv).reshape(B, S, 3, H, Dh), 2, 0, 3, 1, 4)
        q, k, v = qkv[0], qkv[1], qkv[2]
        scale = Dh ** -0.5
        pos = torch.arange(S)
        off = torch.arange(W) * dil
        idx = pos[:, None] - off[None, :]
        mask = idx >= 0
        idx_c = torch.where(mask, idx, 0).reshape(-1)
        kg = k[:, :, idx_c, :].reshape(B, H, S, W, Dh)
        vg = v[:, :, idx_c, :].reshape(B, H, S, W, Dh)
        logits = torch.einsum("bhsd,bhswd->bhsw", q, kg) * scale
        logits = torch.where(mask[None, None, :, :], logits, -1e9)
        attn = _softmax(logits, axis=-1)
        o = torch.einsum("bhsw,bhswd->bhsd", attn, vg)
        return (lambda x, *d: x.permute(*d))(o, 0, 2, 1, 3).reshape(B, S, D) @ wo

    x = A_x
    g = _sigmoid((x * gate_w).sum(-1, keepdims=True))
    a = _A_ref(x, A_c_kv, A_w_q, A_w_uk, A_w_uv, A_w_o)
    b = _B_ref(x, B_wqkv, B_wo)
    return g * a + (1 - g) * b
```

```cpp
#include <cuda_runtime.h>
#include <cuda_bf16.h>
#include <cuda.h>
#include <stdint.h>

#define INL __attribute__((always_inline))

namespace {

constexpr int SEQ = 2048;
constexpr int DM = 1024;
constexpr int DC = 512;
constexpr int QKV_W = 13312;
constexpr int NUM_SMS = 132;
constexpr int GATE_DELAY_SHORT_NS = 1000, GATE_DELAY_LONG_NS = 3000;
constexpr int CLEAR_KS = 30, CLEAR_GAP_NS = 100;
constexpr float Q_SCALE = 0.08838834764831845f * 1.4426950408889634f;
constexpr int SOLO_STAGES = 1;

__device__ __align__(1024) __nv_bfloat16 g_qkv[(size_t)SEQ * QKV_W];
__device__ float g_gate[SEQ];
__device__ uint4 g_halo[16 * 8 * 2 * 5 * 4 * 32];

constexpr int F_Q = 0;
constexpr int F_KV = 1792;
constexpr int F_H = 768;
constexpr int F_CTX = 960;
constexpr int F_GATE = 1600;
constexpr int F_DONE = 1632;
constexpr int F_SPLIT = 1664;
constexpr int F_TICKET = 1696;
constexpr int F_OUT = 1728;
constexpr int GATE_COUNT = NUM_SMS;
__device__ uint32_t g_flags[2304];

#define END_MARK(slot)
#define TRACE_MARK(k, w, i)
#define GTRACE(w)
#define KTRACE(w)
#define PTRACE(i)
#define TRACE_GATE 32
#define TRACE_TID 128

__device__ __forceinline__ uint32_t smem_u32(const void* p) { return (uint32_t)__cvta_generic_to_shared(p); }
__device__ __forceinline__ void mbar_init(uint32_t bar, uint32_t cnt) {
    asm volatile("mbarrier.init.shared::cta.b64 [%0], %1;" ::"r"(bar), "r"(cnt));
}
__device__ __forceinline__ void mbar_arrive(uint32_t bar) {
    asm volatile("mbarrier.arrive.shared::cta.b64 _, [%0];" ::"r"(bar) : "memory");
}
__device__ __forceinline__ bool elect_one() {
    uint32_t r;
    asm volatile("{\n.reg .pred p;\nelect.sync _|p, 0xffffffff;\nselp.b32 %0, 1, 0, p;\n}" : "=r"(r));
    return r != 0;
}
__device__ __forceinline__ uint32_t mapa(uint32_t addr, uint32_t cta) {
    uint32_t r;
    asm("mapa.shared::cluster.u32 %0, %1, %2;" : "=r"(r) : "r"(addr), "r"(cta));
    return r;
}
__device__ __forceinline__ void warp_arrive(uint32_t bar, bool pred = true) {
    asm volatile("{\n.reg .pred p, q;\nsetp.ne.u32 q, %1, 0;\nelect.sync _|p, 0xffffffff;\nand.pred p, p, q;\n"
                 "@p mbarrier.arrive.shared::cta.b64 _, [%0];\n}" ::"r"(bar), "r"((uint32_t)pred) : "memory");
}
__device__ __forceinline__ void warp_arrive2(uint32_t bar0, uint32_t bar1) {
    asm volatile("{\n.reg .pred p;\nelect.sync _|p, 0xffffffff;\n@p mbarrier.arrive.shared::cta.b64 _, [%0];\n"
                 "@p mbarrier.arrive.shared::cta.b64 _, [%1];\n}" ::"r"(bar0), "r"(bar1) : "memory");
}
__device__ __forceinline__ void warp_arrive_pair(uint32_t bar, uint32_t peer_bar, bool pred = true) {
    asm volatile("{\n.reg .pred p, q;\nsetp.ne.u32 q, %2, 0;\nelect.sync _|p, 0xffffffff;\nand.pred p, p, q;\n"
                 "@p mbarrier.arrive.shared::cluster.b64 _, [%1];\n@p mbarrier.arrive.shared::cta.b64 _, [%0];\n}"
                 ::"r"(bar), "r"(peer_bar), "r"((uint32_t)pred) : "memory");
}
__device__ __forceinline__ void mbar_expect_tx(uint32_t bar, uint32_t bytes) {
    asm volatile("mbarrier.arrive.expect_tx.shared::cta.b64 _, [%0], %1;" ::"r"(bar), "r"(bytes) : "memory");
}
constexpr int WAIT_HINT_NS = 20000, WAIT_TRIES = 200000;
__device__ __forceinline__ void mbar_wait(uint32_t bar, uint32_t parity) {
    asm volatile("{\n.reg .pred p;\n.reg .u32 c;\n"
                 "mbarrier.try_wait.parity.shared::cta.b64 p, [%0], %1;\n@p bra DONE;\nmov.u32 c, 0;\n"
                 "SPIN:\nmbarrier.try_wait.parity.shared::cta.b64 p, [%0], %1, %2;\n@p bra DONE;\n"
                 "add.u32 c, c, 1;\nsetp.lt.u32 p, c, %3;\n@p bra SPIN;\ntrap;\nDONE:\n}"
                 ::"r"(bar), "r"(parity), "n"(WAIT_HINT_NS), "n"(WAIT_TRIES) : "memory");
}
__device__ __forceinline__ void mbar_wait_hot(uint32_t bar, uint32_t parity) {
    asm volatile("{\n.reg .pred p, q;\n.reg .u32 c;\n.reg .u64 z;\nmov.u32 c, 0;\nmov.u64 z, 0;\n"
                 "SPIN:\nmbarrier.try_wait.parity.shared::cta.b64 p, [%0], %1;\n"
                 "add.u32 c, c, 1;\nsetp.lt.and.u32 q, c, 4194304, !p;\n@q bra SPIN;\n@!p st.global.u32 [z], c;\n}"
                 ::"r"(bar), "r"(parity) : "memory");
}
constexpr uint64_t POL_STREAM = 0x12F0000000000000ull;
constexpr uint64_t POL_NORMAL = 0x1000000000000000ull;
__device__ __forceinline__ void tma_load_3d(uint32_t dst, const CUtensorMap* map, uint32_t bar, int c0, int c1, int c2, uint64_t pol = POL_NORMAL) {
    asm volatile("cp.async.bulk.tensor.3d.shared::cluster.global.mbarrier::complete_tx::bytes.L2::cache_hint [%0], [%1, {%3, %4, %5}], [%2], %6;"
                 ::"r"(dst), "l"(map), "r"(bar), "r"(c0), "r"(c1), "r"(c2), "l"(pol) : "memory");
}
__device__ __forceinline__ void load_kstep(uint32_t sa, uint32_t sw, uint32_t bar, uint32_t bytes, const CUtensorMap* wmap, int wk, int wblk,
                                           const CUtensorMap* amap, int arow, int kc, uint32_t amode) {
    asm volatile("{\n.reg .pred p, q, r;\n.reg .b32 k;\nelect.sync _|p, 0xffffffff;\nsetp.eq.and.u32 q, %9, 1, p;\nsetp.eq.and.u32 r, %9, 2, p;\nshl.b32 k, %12, 6;\n"
                 "@p mbarrier.arrive.expect_tx.shared::cta.b64 _, [%2], %3;\n"
                 "@p cp.async.bulk.tensor.3d.shared::cluster.global.mbarrier::complete_tx::bytes.multicast::cluster.L2::cache_hint [%1], [%4, {0, k, %5}], [%2], %10, %11;\n"
                 "@q cp.async.bulk.tensor.3d.shared::cluster.global.mbarrier::complete_tx::bytes.L2::cache_hint [%0], [%6, {0, %7, %8}], [%2], %11;\n"
                 "@r cp.async.bulk.tensor.4d.shared::cluster.global.mbarrier::complete_tx::bytes.L2::cache_hint [%0], [%6, {0, %7, 0, %8}], [%2], %11;\n}"
                 ::"r"(sa), "r"(sw), "r"(bar), "r"(bytes), "l"(wmap), "r"(wblk), "l"(amap), "r"(arow), "r"(kc), "r"(amode), "h"((uint16_t)3), "l"(POL_NORMAL), "r"(wk) : "memory");
}
__device__ __forceinline__ void load_operand(uint32_t dst, uint32_t bar, const CUtensorMap* full, const CUtensorMap* half, int row, int blk,
                                             uint32_t rank, bool solo, uint64_t pol) {
    asm volatile("{\n.reg .pred p, q, r;\n.reg .b32 d, b;\nelect.sync _|p, 0xffffffff;\nsetp.ne.and.u32 q, %7, 0, p;\nsetp.eq.and.u32 r, %7, 0, p;\n"
                 "mad.lo.u32 d, %6, 16384, %0;\nadd.u32 b, %5, %6;\n"
                 "@p mbarrier.arrive.expect_tx.shared::cta.b64 _, [%1], 32768;\n"
                 "@q cp.async.bulk.tensor.3d.shared::cluster.global.mbarrier::complete_tx::bytes.L2::cache_hint [%0], [%2, {0, %4, %5}], [%1], %9;\n"
                 "@r cp.async.bulk.tensor.3d.shared::cluster.global.mbarrier::complete_tx::bytes.multicast::cluster.L2::cache_hint [d], [%3, {0, %4, b}], [%1], %8, %9;\n}"
                 ::"r"(dst), "r"(bar), "l"(full), "l"(half), "r"(row), "r"(blk), "r"(rank), "r"((uint32_t)solo), "h"((uint16_t)3), "l"(pol) : "memory");
}
__device__ __forceinline__ void tma_load_par(uint32_t dst, const CUtensorMap* map, uint32_t bar, int pair, int blk) {
    asm volatile("cp.async.bulk.tensor.4d.shared::cluster.global.mbarrier::complete_tx::bytes.L2::cache_hint [%0], [%1, {0, %3, 0, %4}], [%2], %5;"
                 ::"r"(dst), "l"(map), "r"(bar), "r"(pair), "r"(blk), "l"(POL_NORMAL) : "memory");
}
__device__ __forceinline__ void tma_store_par(const CUtensorMap* map, uint32_t src, int pair, int parity, int blk) {
    asm volatile("cp.async.bulk.tensor.4d.global.shared::cta.bulk_group.L2::cache_hint [%0, {0, %2, %3, %4}], [%1], %5;"
                 ::"l"(map), "r"(src), "r"(pair), "r"(parity), "r"(blk), "l"(POL_STREAM) : "memory");
}
__device__ __forceinline__ void tma_store_3d(const CUtensorMap* map, uint32_t src, int c0, int c1, int c2, uint64_t pol) {
    asm volatile("cp.async.bulk.tensor.3d.global.shared::cta.bulk_group.L2::cache_hint [%0, {%2, %3, %4}], [%1], %5;"
                 ::"l"(map), "r"(src), "r"(c0), "r"(c1), "r"(c2), "l"(pol) : "memory");
}
__device__ __forceinline__ void tma_reduce_add_3d(const CUtensorMap* map, uint32_t src, int c0, int c1, int c2) {
    asm volatile("cp.reduce.async.bulk.tensor.3d.global.shared::cta.add.tile.bulk_group [%0, {%2, %3, %4}], [%1];"
                 ::"l"(map), "r"(src), "r"(c0), "r"(c1), "r"(c2) : "memory");
}
__device__ __forceinline__ void bulk_commit() { asm volatile("cp.async.bulk.commit_group;" ::: "memory"); }
template <int N> __device__ __forceinline__ void bulk_wait_read() { asm volatile("cp.async.bulk.wait_group.read %0;" ::"n"(N) : "memory"); }
template <int N> __device__ __forceinline__ void bulk_wait() { asm volatile("cp.async.bulk.wait_group %0;" ::"n"(N) : "memory"); }
__device__ __forceinline__ void fence_async_smem() { asm volatile("fence.proxy.async.shared::cta;" ::: "memory"); }
__device__ __forceinline__ void fence_async_global() { asm volatile("fence.proxy.async.global;" ::: "memory"); }
__device__ __forceinline__ uint32_t ld_acquire(const uint32_t* p) {
    uint32_t v;
    asm volatile("ld.acquire.gpu.global.u32 %0, [%1];" : "=r"(v) : "l"(p) : "memory");
    return v;
}
__device__ __forceinline__ uint32_t ld_relaxed(const uint32_t* p) {
    uint32_t v;
    asm volatile("ld.relaxed.gpu.global.u32 %0, [%1];" : "=r"(v) : "l"(p) : "memory");
    return v;
}
__device__ __forceinline__ void fence_acquire() { asm volatile("fence.acquire.gpu;\nfence.proxy.async.global;" ::: "memory"); }
__device__ __forceinline__ void red_release(uint32_t* p) {
    asm volatile("red.release.gpu.global.add.u32 [%0], 1;" ::"l"(p) : "memory");
}
__device__ __forceinline__ void red_relaxed(uint32_t* p) {
    asm volatile("red.relaxed.gpu.global.add.u32 [%0], 1;" ::"l"(p) : "memory");
}
__device__ __forceinline__ void prefetch_map(const CUtensorMap* map) { asm volatile("prefetch.tensormap [%0];" ::"l"(map) : "memory"); }
__device__ __forceinline__ void trap_if(bool c) { asm volatile("{\n.reg .pred p;\nsetp.ne.u32 p, %0, 0;\n@p trap;\n}" ::"r"((uint32_t)c)); }
__device__ __forceinline__ void setup_arrive() {
    asm volatile("bar.sync 0;\nbarrier.cluster.arrive.relaxed.aligned;" ::: "memory");
}
__device__ __forceinline__ void setup_wait() { asm volatile("barrier.cluster.wait.aligned;" ::: "memory"); }
__device__ __forceinline__ uint32_t cluster_rank() { uint32_t r; asm("mov.u32 %0, %%cluster_ctarank;" : "=r"(r)); return r; }
__device__ __forceinline__ void named_sync(int id, int n) { asm volatile("bar.sync %0, %1;" ::"r"(id), "r"(n) : "memory"); }
__device__ __forceinline__ void named_arrive(int id, int n) { asm volatile("bar.arrive %0, %1;" ::"r"(id), "r"(n) : "memory"); }
__device__ __forceinline__ void named_sync_if(bool c, int id, int n) {
    asm volatile("{\n.reg .pred p;\nsetp.ne.u32 p, %0, 0;\n@p bar.sync %1, %2;\n}" ::"r"((uint32_t)c), "r"(id), "r"(n) : "memory");
}
__device__ __forceinline__ void named_arrive_if(bool c, int id, int n) {
    asm volatile("{\n.reg .pred p;\nsetp.ne.u32 p, %0, 0;\n@p bar.arrive %1, %2;\n}" ::"r"((uint32_t)c), "r"(id), "r"(n) : "memory");
}
template <int V> struct IC { static constexpr int v = V; };
template <int N> __device__ __forceinline__ void reg_dec() { asm volatile("setmaxnreg.dec.sync.aligned.u32 %0;" ::"n"(N)); }
template <int N> __device__ __forceinline__ void reg_inc() { asm volatile("setmaxnreg.inc.sync.aligned.u32 %0;" ::"n"(N)); }

__device__ __forceinline__ void wg_fence() { asm volatile("wgmma.fence.sync.aligned;" ::: "memory"); }
__device__ __forceinline__ void wg_commit() { asm volatile("wgmma.commit_group.sync.aligned;" ::: "memory"); }
template <int N> __device__ __forceinline__ void wg_wait() { asm volatile("wgmma.wait_group.sync.aligned %0;" ::"n"(N) : "memory"); }
template <int N> __device__ __forceinline__ void fence_regs(float (&r)[N]) {
#pragma unroll
    for (int i = 0; i < N; i++) asm volatile("" : "+f"(r[i])::"memory");
}
template <int N> __device__ __forceinline__ void fence_regs(uint32_t (&r)[N]) {
#pragma unroll
    for (int i = 0; i < N; i++) asm volatile("" : "+r"(r[i])::"memory");
}
__device__ __forceinline__ uint32_t desc_lo(uint32_t addr, uint32_t lbo) { return ((addr & 0x3FFFF) >> 4) | ((lbo >> 4) << 16); }
__device__ __forceinline__ int uniform(int v) { return __shfl_sync(0xffffffffu, v, 0); }
__device__ __forceinline__ uint32_t pack_bf16(float lo, float hi) {
    uint32_t r;
    asm("cvt.rn.bf16x2.f32 %0, %1, %2;" : "=r"(r) : "f"(hi), "f"(lo));
    return r;
}
__device__ __forceinline__ void stmatrix_x4(uint32_t addr, uint32_t r0, uint32_t r1, uint32_t r2, uint32_t r3) {
    asm volatile("stmatrix.sync.aligned.m8n8.x4.shared.b16 [%0], {%1, %2, %3, %4};"
                 ::"r"(addr), "r"(r0), "r"(r1), "r"(r2), "r"(r3) : "memory");
}
__device__ __forceinline__ void stmatrix_x4(uint32_t addr, uint32_t r0, uint32_t r1, uint32_t r2, uint32_t r3, bool trans) {
    asm volatile("{\n.reg .pred p;\nsetp.ne.u32 p, %5, 0;\n@p stmatrix.sync.aligned.m8n8.x4.trans.shared.b16 [%0], {%1, %2, %3, %4};\n"
                 "@!p stmatrix.sync.aligned.m8n8.x4.shared.b16 [%0], {%1, %2, %3, %4};\n}"
                 ::"r"(addr), "r"(r0), "r"(r1), "r"(r2), "r"(r3), "r"((uint32_t)trans) : "memory");
}
__device__ __forceinline__ void ldmatrix_x4_t(uint32_t addr, uint32_t (&r)[4]) {
    asm volatile("ldmatrix.sync.aligned.m8n8.x4.trans.shared.b16 {%0, %1, %2, %3}, [%4];"
                 : "=r"(r[0]), "=r"(r[1]), "=r"(r[2]), "=r"(r[3]) : "r"(addr) : "memory");
}
__device__ __forceinline__ void mma_16816(float (&d)[4], uint32_t a0, uint32_t a1, uint32_t a2, uint32_t a3, uint32_t b0, uint32_t b1) {
    asm("mma.sync.aligned.m16n8k16.row.col.f32.bf16.bf16.f32 {%0, %1, %2, %3}, {%4, %5, %6, %7}, {%8, %9}, {%0, %1, %2, %3};"
        : "+f"(d[0]), "+f"(d[1]), "+f"(d[2]), "+f"(d[3]) : "r"(a0), "r"(a1), "r"(a2), "r"(a3), "r"(b0), "r"(b1));
}
__device__ __forceinline__ void order_after(float v, uint32_t scratch) {
    asm volatile("{\n.reg .pred p;\nsetp.gt.f32 p, %0, 0f70000000;\n@p st.shared.u32 [%1], 0;\n}" ::"f"(v), "r"(scratch) : "memory");
}
__device__ __forceinline__ float rcp(float x) { float y; asm("rcp.approx.ftz.f32 %0, %1;" : "=f"(y) : "f"(x)); return y; }
__device__ __forceinline__ float ex2(float x) { float y; asm("ex2.approx.ftz.f32 %0, %1;" : "=f"(y) : "f"(x)); return y; }

template <int OA, int OB>
__device__ __forceinline__ void wgmma_ss_n256(float (&d0)[64], float (&d1)[64], uint32_t da, uint32_t db) {
    asm volatile("{\n.reg .b32 ta, tb;\n.reg .b64 da, db;\nadd.u32 ta, %128, %130;\nadd.u32 tb, %129, %131;\n"
        "mov.b64 da, {ta, 0x40000040};\nmov.b64 db, {tb, 0x40000040};\n"
        "wgmma.mma_async.sync.aligned.m64n256k16.f32.bf16.bf16 {%0, %1, %2, %3, %4, %5, %6, %7, %8, %9, %10, %11, %12, %13, %14, %15, %16, %17, %18, %19, %20, %21, %22, %23, %24, %25, %26, %27, %28, %29, %30, %31, %32, %33, %34, %35, %36, %37, %38, %39, %40, %41, %42, %43, %44, %45, %46, %47, %48, %49, %50, %51, %52, %53, %54, %55, %56, %57, %58, %59, %60, %61, %62, %63, %64, %65, %66, %67, %68, %69, %70, %71, %72, %73, %74, %75, %76, %77, %78, %79, %80, %81, %82, %83, %84, %85, %86, %87, %88, %89, %90, %91, %92, %93, %94, %95, %96, %97, %98, %99, %100, %101, %102, %103, %104, %105, %106, %107, %108, %109, %110, %111, %112, %113, %114, %115, %116, %117, %118, %119, %120, %121, %122, %123, %124, %125, %126, %127}, da, db, 1, 1, 1, 0, 1;\n}\n"
        : "+f"(d0[0]), "+f"(d0[1]), "+f"(d0[2]), "+f"(d0[3]), "+f"(d0[4]), "+f"(d0[5]), "+f"(d0[6]), "+f"(d0[7]), "+f"(d0[8]), "+f"(d0[9]), "+f"(d0[10]), "+f"(d0[11]), "+f"(d0[12]), "+f"(d0[13]), "+f"(d0[14]), "+f"(d0[15]), "+f"(d0[16]), "+f"(d0[17]), "+f"(d0[18]), "+f"(d0[19]), "+f"(d0[20]), "+f"(d0[21]), "+f"(d0[22]), "+f"(d0[23]), "+f"(d0[24]), "+f"(d0[25]), "+f"(d0[26]), "+f"(d0[27]), "+f"(d0[28]), "+f"(d0[29]), "+f"(d0[30]), "+f"(d0[31]), "+f"(d0[32]), "+f"(d0[33]), "+f"(d0[34]), "+f"(d0[35]), "+f"(d0[36]), "+f"(d0[37]), "+f"(d0[38]), "+f"(d0[39]), "+f"(d0[40]), "+f"(d0[41]), "+f"(d0[42]), "+f"(d0[43]), "+f"(d0[44]), "+f"(d0[45]), "+f"(d0[46]), "+f"(d0[47]), "+f"(d0[48]), "+f"(d0[49]), "+f"(d0[50]), "+f"(d0[51]), "+f"(d0[52]), "+f"(d0[53]), "+f"(d0[54]), "+f"(d0[55]), "+f"(d0[56]), "+f"(d0[57]), "+f"(d0[58]), "+f"(d0[59]), "+f"(d0[60]), "+f"(d0[61]), "+f"(d0[62]), "+f"(d0[63]), "+f"(d1[0]), "+f"(d1[1]), "+f"(d1[2]), "+f"(d1[3]), "+f"(d1[4]), "+f"(d1[5]), "+f"(d1[6]), "+f"(d1[7]), "+f"(d1[8]), "+f"(d1[9]), "+f"(d1[10]), "+f"(d1[11]), "+f"(d1[12]), "+f"(d1[13]), "+f"(d1[14]), "+f"(d1[15]), "+f"(d1[16]), "+f"(d1[17]), "+f"(d1[18]), "+f"(d1[19]), "+f"(d1[20]), "+f"(d1[21]), "+f"(d1[22]), "+f"(d1[23]), "+f"(d1[24]), "+f"(d1[25]), "+f"(d1[26]), "+f"(d1[27]), "+f"(d1[28]), "+f"(d1[29]), "+f"(d1[30]), "+f"(d1[31]), "+f"(d1[32]), "+f"(d1[33]), "+f"(d1[34]), "+f"(d1[35]), "+f"(d1[36]), "+f"(d1[37]), "+f"(d1[38]), "+f"(d1[39]), "+f"(d1[40]), "+f"(d1[41]), "+f"(d1[42]), "+f"(d1[43]), "+f"(d1[44]), "+f"(d1[45]), "+f"(d1[46]), "+f"(d1[47]), "+f"(d1[48]), "+f"(d1[49]), "+f"(d1[50]), "+f"(d1[51]), "+f"(d1[52]), "+f"(d1[53]), "+f"(d1[54]), "+f"(d1[55]), "+f"(d1[56]), "+f"(d1[57]), "+f"(d1[58]), "+f"(d1[59]), "+f"(d1[60]), "+f"(d1[61]), "+f"(d1[62]), "+f"(d1[63])
        : "r"(da), "r"(db), "n"(OA), "n"(OB));
}

__device__ __forceinline__ void wgmma_ss_n256_init(float (&d0)[64], float (&d1)[64], uint32_t da, uint32_t db) {
    asm volatile("{\n.reg .b64 da, db;\n"
        "mov.b64 da, {%128, 0x40000040};\nmov.b64 db, {%129, 0x40000040};\n"
        "wgmma.mma_async.sync.aligned.m64n256k16.f32.bf16.bf16 {%0, %1, %2, %3, %4, %5, %6, %7, %8, %9, %10, %11, %12, %13, %14, %15, %16, %17, %18, %19, %20, %21, %22, %23, %24, %25, %26, %27, %28, %29, %30, %31, %32, %33, %34, %35, %36, %37, %38, %39, %40, %41, %42, %43, %44, %45, %46, %47, %48, %49, %50, %51, %52, %53, %54, %55, %56, %57, %58, %59, %60, %61, %62, %63, %64, %65, %66, %67, %68, %69, %70, %71, %72, %73, %74, %75, %76, %77, %78, %79, %80, %81, %82, %83, %84, %85, %86, %87, %88, %89, %90, %91, %92, %93, %94, %95, %96, %97, %98, %99, %100, %101, %102, %103, %104, %105, %106, %107, %108, %109, %110, %111, %112, %113, %114, %115, %116, %117, %118, %119, %120, %121, %122, %123, %124, %125, %126, %127}, da, db, 0, 1, 1, 0, 1;\n}\n"
        : "=f"(d0[0]), "=f"(d0[1]), "=f"(d0[2]), "=f"(d0[3]), "=f"(d0[4]), "=f"(d0[5]), "=f"(d0[6]), "=f"(d0[7]), "=f"(d0[8]), "=f"(d0[9]), "=f"(d0[10]), "=f"(d0[11]), "=f"(d0[12]), "=f"(d0[13]), "=f"(d0[14]), "=f"(d0[15]), "=f"(d0[16]), "=f"(d0[17]), "=f"(d0[18]), "=f"(d0[19]), "=f"(d0[20]), "=f"(d0[21]), "=f"(d0[22]), "=f"(d0[23]), "=f"(d0[24]), "=f"(d0[25]), "=f"(d0[26]), "=f"(d0[27]), "=f"(d0[28]), "=f"(d0[29]), "=f"(d0[30]), "=f"(d0[31]), "=f"(d0[32]), "=f"(d0[33]), "=f"(d0[34]), "=f"(d0[35]), "=f"(d0[36]), "=f"(d0[37]), "=f"(d0[38]), "=f"(d0[39]), "=f"(d0[40]), "=f"(d0[41]), "=f"(d0[42]), "=f"(d0[43]), "=f"(d0[44]), "=f"(d0[45]), "=f"(d0[46]), "=f"(d0[47]), "=f"(d0[48]), "=f"(d0[49]), "=f"(d0[50]), "=f"(d0[51]), "=f"(d0[52]), "=f"(d0[53]), "=f"(d0[54]), "=f"(d0[55]), "=f"(d0[56]), "=f"(d0[57]), "=f"(d0[58]), "=f"(d0[59]), "=f"(d0[60]), "=f"(d0[61]), "=f"(d0[62]), "=f"(d0[63]), "=f"(d1[0]), "=f"(d1[1]), "=f"(d1[2]), "=f"(d1[3]), "=f"(d1[4]), "=f"(d1[5]), "=f"(d1[6]), "=f"(d1[7]), "=f"(d1[8]), "=f"(d1[9]), "=f"(d1[10]), "=f"(d1[11]), "=f"(d1[12]), "=f"(d1[13]), "=f"(d1[14]), "=f"(d1[15]), "=f"(d1[16]), "=f"(d1[17]), "=f"(d1[18]), "=f"(d1[19]), "=f"(d1[20]), "=f"(d1[21]), "=f"(d1[22]), "=f"(d1[23]), "=f"(d1[24]), "=f"(d1[25]), "=f"(d1[26]), "=f"(d1[27]), "=f"(d1[28]), "=f"(d1[29]), "=f"(d1[30]), "=f"(d1[31]), "=f"(d1[32]), "=f"(d1[33]), "=f"(d1[34]), "=f"(d1[35]), "=f"(d1[36]), "=f"(d1[37]), "=f"(d1[38]), "=f"(d1[39]), "=f"(d1[40]), "=f"(d1[41]), "=f"(d1[42]), "=f"(d1[43]), "=f"(d1[44]), "=f"(d1[45]), "=f"(d1[46]), "=f"(d1[47]), "=f"(d1[48]), "=f"(d1[49]), "=f"(d1[50]), "=f"(d1[51]), "=f"(d1[52]), "=f"(d1[53]), "=f"(d1[54]), "=f"(d1[55]), "=f"(d1[56]), "=f"(d1[57]), "=f"(d1[58]), "=f"(d1[59]), "=f"(d1[60]), "=f"(d1[61]), "=f"(d1[62]), "=f"(d1[63])
        : "r"(da), "r"(db));
}

template <int TB, int OA, int OB>
__device__ __forceinline__ void wgmma_ss_n128_init(float (&d)[64], uint32_t da, uint32_t db) {
    asm volatile("{\n.reg .b32 ta, tb;\n.reg .b64 da, db;\nadd.u32 ta, %64, %66;\nadd.u32 tb, %65, %67;\n"
        "mov.b64 da, {ta, 0x40000040};\nmov.b64 db, {tb, 0x40000040};\n"
        "wgmma.mma_async.sync.aligned.m64n128k16.f32.bf16.bf16 {%0, %1, %2, %3, %4, %5, %6, %7, %8, %9, %10, %11, %12, %13, %14, %15, %16, %17, %18, %19, %20, %21, %22, %23, %24, %25, %26, %27, %28, %29, %30, %31, %32, %33, %34, %35, %36, %37, %38, %39, %40, %41, %42, %43, %44, %45, %46, %47, %48, %49, %50, %51, %52, %53, %54, %55, %56, %57, %58, %59, %60, %61, %62, %63}, da, db, 0, 1, 1, 0, %68;\n}\n"
        : "=f"(d[0]), "=f"(d[1]), "=f"(d[2]), "=f"(d[3]), "=f"(d[4]), "=f"(d[5]), "=f"(d[6]), "=f"(d[7]), "=f"(d[8]), "=f"(d[9]), "=f"(d[10]), "=f"(d[11]), "=f"(d[12]), "=f"(d[13]), "=f"(d[14]), "=f"(d[15]), "=f"(d[16]), "=f"(d[17]), "=f"(d[18]), "=f"(d[19]), "=f"(d[20]), "=f"(d[21]), "=f"(d[22]), "=f"(d[23]), "=f"(d[24]), "=f"(d[25]), "=f"(d[26]), "=f"(d[27]), "=f"(d[28]), "=f"(d[29]), "=f"(d[30]), "=f"(d[31]), "=f"(d[32]), "=f"(d[33]), "=f"(d[34]), "=f"(d[35]), "=f"(d[36]), "=f"(d[37]), "=f"(d[38]), "=f"(d[39]), "=f"(d[40]), "=f"(d[41]), "=f"(d[42]), "=f"(d[43]), "=f"(d[44]), "=f"(d[45]), "=f"(d[46]), "=f"(d[47]), "=f"(d[48]), "=f"(d[49]), "=f"(d[50]), "=f"(d[51]), "=f"(d[52]), "=f"(d[53]), "=f"(d[54]), "=f"(d[55]), "=f"(d[56]), "=f"(d[57]), "=f"(d[58]), "=f"(d[59]), "=f"(d[60]), "=f"(d[61]), "=f"(d[62]), "=f"(d[63])
        : "r"(da), "r"(db), "n"(OA), "n"(OB), "n"(TB));
}

template <int OA, int OB>
__device__ __forceinline__ void wgmma_ss_n128_tb0(float (&d)[64], uint32_t da, uint32_t db, int scale_d) {
    asm volatile("{\n.reg .pred p;\n.reg .b32 ta, tb;\n.reg .b64 da, db;\nsetp.ne.b32 p, %66, 0;\nadd.u32 ta, %64, %67;\nadd.u32 tb, %65, %68;\n"
        "mov.b64 da, {ta, 0x40000040};\nmov.b64 db, {tb, 0x40000040};\n"
        "wgmma.mma_async.sync.aligned.m64n128k16.f32.bf16.bf16 "
        "{%0, %1, %2, %3, %4, %5, %6, %7, %8, %9, %10, %11, %12, %13, %14, %15, %16, %17, %18, %19, %20, %21, %22, %23, %24, %25, %26, %27, %28, %29, %30, %31, %32, %33, %34, %35, %36, %37, %38, %39, %40, %41, %42, %43, %44, %45, %46, %47, %48, %49, %50, %51, %52, %53, %54, %55, %56, %57, %58, %59, %60, %61, %62, %63}, da, db, p, 1, 1, 0, 0;\n}\n"
        : "+f"(d[0]), "+f"(d[1]), "+f"(d[2]), "+f"(d[3]), "+f"(d[4]), "+f"(d[5]), "+f"(d[6]), "+f"(d[7]), "+f"(d[8]), "+f"(d[9]), "+f"(d[10]), "+f"(d[11]), "+f"(d[12]), "+f"(d[13]), "+f"(d[14]), "+f"(d[15]), "+f"(d[16]), "+f"(d[17]), "+f"(d[18]), "+f"(d[19]), "+f"(d[20]), "+f"(d[21]), "+f"(d[22]), "+f"(d[23]), "+f"(d[24]), "+f"(d[25]), "+f"(d[26]), "+f"(d[27]), "+f"(d[28]), "+f"(d[29]), "+f"(d[30]), "+f"(d[31]), "+f"(d[32]), "+f"(d[33]), "+f"(d[34]), "+f"(d[35]), "+f"(d[36]), "+f"(d[37]), "+f"(d[38]), "+f"(d[39]), "+f"(d[40]), "+f"(d[41]), "+f"(d[42]), "+f"(d[43]), "+f"(d[44]), "+f"(d[45]), "+f"(d[46]), "+f"(d[47]), "+f"(d[48]), "+f"(d[49]), "+f"(d[50]), "+f"(d[51]), "+f"(d[52]), "+f"(d[53]), "+f"(d[54]), "+f"(d[55]), "+f"(d[56]), "+f"(d[57]), "+f"(d[58]), "+f"(d[59]), "+f"(d[60]), "+f"(d[61]), "+f"(d[62]), "+f"(d[63])
        : "r"(da), "r"(db), "r"(scale_d), "n"(OA), "n"(OB));
}

template <int OB>
__device__ __forceinline__ void wgmma_rs_n128_tb1(float (&d)[64], uint32_t a0, uint32_t a1, uint32_t a2, uint32_t a3, uint32_t db, int scale_d) {
    asm volatile("{\n.reg .pred p;\n.reg .b32 tb;\n.reg .b64 db;\nsetp.ne.b32 p, %69, 0;\nadd.u32 tb, %68, %70;\n"
        "mov.b64 db, {tb, 0x40000040};\n"
        "wgmma.mma_async.sync.aligned.m64n128k16.f32.bf16.bf16 "
        "{%0, %1, %2, %3, %4, %5, %6, %7, %8, %9, %10, %11, %12, %13, %14, %15, %16, %17, %18, %19, %20, %21, %22, %23, %24, %25, %26, %27, %28, %29, %30, %31, %32, %33, %34, %35, %36, %37, %38, %39, %40, %41, %42, %43, %44, %45, %46, %47, %48, %49, %50, %51, %52, %53, %54, %55, %56, %57, %58, %59, %60, %61, %62, %63}, {%64, %65, %66, %67}, db, p, 1, 1, 1;\n}\n"
        : "+f"(d[0]), "+f"(d[1]), "+f"(d[2]), "+f"(d[3]), "+f"(d[4]), "+f"(d[5]), "+f"(d[6]), "+f"(d[7]), "+f"(d[8]), "+f"(d[9]), "+f"(d[10]), "+f"(d[11]), "+f"(d[12]), "+f"(d[13]), "+f"(d[14]), "+f"(d[15]), "+f"(d[16]), "+f"(d[17]), "+f"(d[18]), "+f"(d[19]), "+f"(d[20]), "+f"(d[21]), "+f"(d[22]), "+f"(d[23]), "+f"(d[24]), "+f"(d[25]), "+f"(d[26]), "+f"(d[27]), "+f"(d[28]), "+f"(d[29]), "+f"(d[30]), "+f"(d[31]), "+f"(d[32]), "+f"(d[33]), "+f"(d[34]), "+f"(d[35]), "+f"(d[36]), "+f"(d[37]), "+f"(d[38]), "+f"(d[39]), "+f"(d[40]), "+f"(d[41]), "+f"(d[42]), "+f"(d[43]), "+f"(d[44]), "+f"(d[45]), "+f"(d[46]), "+f"(d[47]), "+f"(d[48]), "+f"(d[49]), "+f"(d[50]), "+f"(d[51]), "+f"(d[52]), "+f"(d[53]), "+f"(d[54]), "+f"(d[55]), "+f"(d[56]), "+f"(d[57]), "+f"(d[58]), "+f"(d[59]), "+f"(d[60]), "+f"(d[61]), "+f"(d[62]), "+f"(d[63])
        : "r"(a0), "r"(a1), "r"(a2), "r"(a3), "r"(db), "r"(scale_d), "n"(OB));
}

__device__ __forceinline__ uint32_t stage_addr(uint32_t block, int warp, int lane) {
    return block + (warp * 16 + (lane & 7) + ((lane >> 3) & 1) * 8) * 128 + (((lane >> 4) ^ (lane & 7)) << 4);
}
template <int OFF, int N>
__device__ __forceinline__ void stage_packed_64x64(uint32_t a0, int off, const uint32_t (&v)[N]) {
#pragma unroll
    for (int j = 0; j < 8; j += 2) {
        uint32_t a = a0;
        if (j) asm volatile("xor.b32 %0, %1, %2;" : "=r"(a) : "r"(a0), "r"(j << 4));
        stmatrix_x4(a + off, v[OFF + j * 2], v[OFF + j * 2 + 1], v[OFF + j * 2 + 2], v[OFF + j * 2 + 3]);
    }
}

template <int OFF, int N>
__device__ __forceinline__ void stage_packed_64x64(const uint32_t (&a)[4], int off, const uint32_t (&v)[N]) {
#pragma unroll
    for (int j = 0; j < 4; j++) stmatrix_x4(a[j] + off, v[OFF + j * 4], v[OFF + j * 4 + 1], v[OFF + j * 4 + 2], v[OFF + j * 4 + 3]);
}

template <int OFF, int N>
__device__ __forceinline__ void stage_packed_64x64(const uint32_t (&a)[4], int off, const uint32_t (&v)[N], bool trans) {
#pragma unroll
    for (int j = 0; j < 4; j++) stmatrix_x4(a[j] + off, v[OFF + j * 4], v[OFF + j * 4 + 1], v[OFF + j * 4 + 2], v[OFF + j * 4 + 3], trans);
}

constexpr int MAX_JOBS = 24;
constexpr int MAX_ROUNDS = 44;
constexpr int T_P = 0, T_O = 1, T_A = 2;
constexpr int HQ_A = 4, HQ_B = 28;
__host__ __device__ constexpr int unit_head(int g) { return g + (g < 4 ? HQ_A : HQ_B - 4); }
constexpr int G_STAGE = 49152;
constexpr int OFF_Q0 = 0, OFF_K0 = 32768, OFF_Q1 = 65536, OFF_K1 = 98304, OFF_V0 = 131072, OFF_V1 = 163840;
constexpr int OFF_STG = 196608;
constexpr int OFF_BAR = 229376;
constexpr int SMEM_BYTES = OFF_BAR + 640;
constexpr int TURN_THREADS = 288;

struct Params {
    CUtensorMap amap[2];
    CUtensorMap wmap[4];
    CUtensorMap x_par, wo_a, wo_b, qkv_st, qkv_ld, qkv_half, st_par, out_st;
    const __nv_bfloat16* xp;
    const __nv_bfloat16* gate_w;
    __nv_bfloat16* out;
    uint16_t first[NUM_SMS / 2];
    int16_t jobs[NUM_SMS][MAX_JOBS];
    uint16_t rounds[NUM_SMS / 2][MAX_ROUNDS];
};

constexpr int O_STAGGER = 4;
constexpr int O_F0 = 35, O_H1 = 5;
constexpr int O_FLEX = 16, O_H0 = O_F0 + 8, O_T0 = 8, O_T1 = 64 - O_F0 - O_FLEX - O_H1;
__device__ __forceinline__ int o_head(int job) { return (job & 32) ? O_H1 : O_H0; }
__device__ __forceinline__ int o_tail(int job) { return (job & 32) ? O_T1 : O_T0; }
__device__ __forceinline__ uint32_t o_state(uint32_t word, int have) {
    uint32_t v;
    asm volatile("{\n.reg .pred p, q;\n.reg .u32 c, t;\nmov.u32 c, 0;\n"
                 "SPIN:\nld.volatile.shared.u32 %0, [%1];\nand.b32 t, %0, 1;\nsetp.ne.u32 q, t, 0;\nsetp.gt.or.u32 p, %0, %2, q;\n@p bra DONE;\n"
                 "add.u32 c, c, 1;\nsetp.lt.u32 q, c, 16777216;\n@q bra SPIN;\ntrap;\nDONE:\n}"
                 : "=r"(v) : "r"(word), "r"(2 * have + 1) : "memory");
    return v;
}

template <class T> __device__ __forceinline__ T* page_ptr(int off) {
    extern __shared__ __align__(1024) uint8_t smem_raw[];
    return *reinterpret_cast<T* volatile*>(smem_raw + OFF_BAR + off);
}
template <int SLEEP_NS = 0>
__device__ __forceinline__ bool wait_flags(bool active, int idx, uint32_t target, bool block = true) {
    for (uint32_t tries = 0;; tries++) {
        const bool ok = !active | ((int32_t)(ld_acquire(g_flags + idx) - target) >= 0);
        if (__all_sync(0xffffffffu, ok)) break;
        if (!block) return false;
        if (SLEEP_NS) __nanosleep(SLEEP_NS);
        trap_if(tries > (1u << 22));
    }
    fence_async_global();
    return true;
}

__global__ void __cluster_dims__(2, 1, 1) __launch_bounds__(384, 1)
fused_kernel(const __grid_constant__ Params p) {
    extern __shared__ __align__(1024) uint8_t smem_raw[];
    const uint32_t base = smem_u32(smem_raw);
    const uint32_t bars = base + OFF_BAR;
    const uint32_t gfull = bars, gempty = bars + 32, sfull = bars + 64, sempty = bars + 96;
    const uint32_t qfull = bars + 128, qempty = bars + 144, kfull = bars + 160, kempty = bars + 176;
    const uint32_t vfull = bars + 192, vempty = bars + 208, lready = bars + 224, hout = bars + 240;
    const uint32_t tfull = bars + 256, aready = bars + 272, gatefull = bars + 280;
    const uint32_t otile = bars + 528;
    const uint32_t olim = bars + 504;
    const uint32_t stg = base + OFF_STG;
    uint32_t* rounds = reinterpret_cast<uint32_t*>(smem_raw + OFF_BAR + 416);
    const int tid = threadIdx.x, warp = uniform(tid >> 5), lane = tid & 31, wg = warp >> 2;
    const uint32_t rank = cluster_rank();
    int* jobs = reinterpret_cast<int*>(smem_raw + OFF_BAR + 312);
    auto w_map = [&](uint32_t rec, uint32_t half) INL { return &p.wmap[(rec & 8) ? 2 + half : ((rec >> 15) && half ? 0 : rec >> 4 & 1)]; };
    auto w_blk = [&](uint32_t rec, uint32_t half) INL -> int {
        const int col = rec >> 6 & 15;
        if (rec & 8) return (col + (rec & 16)) * 2;
        return rec >> 14 == 0 ? col * 4 + half * 2 : (rec >> 14 == 1 ? 16 + half * 16 + col * 2 : (half ? unit_head(col) : col) * 2);
    };
    auto load_a = [&](uint32_t rec, uint32_t sa, uint32_t bar, int kc) INL {
        if (rec >> 14) tma_load_par(sa, &p.x_par, bar, (rec & 7) * 128 + rank * 64, kc);
        else           tma_load_3d(sa, &p.amap[rec >> 3 & 1], bar, 0, (rec & 7) * 256 + rank * 128, kc);
    };
    auto load_round = [&](uint32_t rec, int st0, uint32_t parity) INL {
        const CUtensorMap* wm = w_map(rec, rank);
        const CUtensorMap* am = rec >> 14 ? &p.x_par : &p.amap[rec >> 3 & 1];
        const int wb = w_blk(rec, rank), kc0 = (rec >> 10 & 3) * 4, arow = ((rec & 7) * 256 + rank * 128) >> (rec >> 14 ? 1 : 0);
        const uint32_t bytes = (rec & 4096) ? G_STAGE - 16384 : G_STAGE, amode = (rec & 4096) ? 0 : (rec >> 14 ? 2 : 1);
#pragma unroll 1
        for (int st = st0; st < 4; st++) {
            const uint32_t sa = base + st * G_STAGE;
            mbar_wait(gempty + st * 8, parity);
            load_kstep(sa, sa + 16384 + rank * 16384, gfull + st * 8, bytes, wm, kc0 + st, wb, am, arow, kc0 + st, amode);
        }
    };
    if (warp < 1) {
        const uint32_t rec0 = p.first[blockIdx.x >> 1];
        if (elect_one()) {
#pragma unroll
            for (int st = 0; st < SOLO_STAGES; st++) mbar_init(gfull + st * 8, 1);
            fence_async_smem();
#pragma unroll
            for (int st = 0; st < SOLO_STAGES; st++) {
                const uint32_t sa = base + st * G_STAGE;
                mbar_expect_tx(gfull + st * 8, G_STAGE);
                load_a(rec0, sa, gfull + st * 8, st);
                tma_load_3d(sa + 16384, w_map(rec0, 0), gfull + st * 8, 0, st * 64, w_blk(rec0, 0));
                tma_load_3d(sa + 32768, w_map(rec0, 1), gfull + st * 8, 0, st * 64, w_blk(rec0, 1));
            }
            asm volatile("fence.mbarrier_init.release.cluster;" ::: "memory");
        }
        __syncwarp();
    } else if (warp == 1) {
        if (elect_one()) {
#pragma unroll
            for (int i = SOLO_STAGES; i < 39; i++)
                mbar_init(bars + i * 8, (0x0CC000F0ull >> i & 1) ? 16 : ((0x300000F00ull >> i & 1) ? 4 : ((0xC0000ull >> i & 1) ? 8 : 1)));
            asm volatile("fence.mbarrier_init.release.cluster;" ::: "memory");
            fence_async_smem();
        }
        __syncwarp();
    } else if (warp == 2) {
        const int jl = lane < MAX_JOBS ? p.jobs[blockIdx.x][lane] : -1;
        if (lane <= MAX_JOBS) jobs[lane] = jl;
        if ((jl >> 12) == T_O) *reinterpret_cast<volatile uint32_t*>(smem_raw + OFF_BAR + 504) = 2 * o_head(jl);
        if (lane == 31) *reinterpret_cast<volatile uint32_t*>(smem_raw + OFF_BAR + 528) = 0;
    } else if (warp == 3) {
        if (lane == 31) *reinterpret_cast<ulonglong2*>(smem_raw + OFF_BAR + 512) = make_ulonglong2((uint64_t)g_halo, (uint64_t)g_gate);
        if (lane < MAX_ROUNDS / 2) rounds[lane] = reinterpret_cast<const uint32_t*>(p.rounds[blockIdx.x >> 1])[lane];
    }
    setup_arrive();
    if (warp > 3) {
        reg_inc<232>();
        const int w = wg - 1, wwarp = warp & 3;
        const uint32_t slot_a = stage_addr(stg + w * 16384, wwarp, lane);
        const uint32_t bars_peer = uniform(mapa(bars, rank ^ 1));
        auto arrive_pair = [&](uint32_t bar, bool pred = true) INL { warp_arrive_pair(bar, bars_peer + (bar - bars), pred); };
        uint32_t gph = 0;
        uint32_t sph = 1;
        int jb = 0;
        int job = uniform(jobs[0]);
        auto next_job = [&]() INL { jb++; job = uniform(jobs[jb]); };
        auto slot_wait = [&](int q) INL { mbar_wait(sempty + (w * 2 + (q & 1)) * 8, (q >> 1) ^ sph ^ 1); };
        auto signal = [&](int q) INL {
            __syncwarp();
            warp_arrive(sfull + (w * 2 + (q & 1)) * 8);
        };
        uint32_t pk[64];
        float O[64];
        float oscale1 = 1.f;
        uint32_t slot4[4];
        bool ptrans = false;
        auto stage_quarter = [&](const int Q) INL {
            slot_wait(Q);
            if (Q == 0) stage_packed_64x64<0>(slot4, 0, pk, ptrans);
            if (Q == 1) stage_packed_64x64<16>(slot4, 8192, pk, ptrans);
            if (Q == 2) stage_packed_64x64<32>(slot4, 0, pk);
            if (Q == 3) stage_packed_64x64<48>(slot4, 8192, pk);
        };
        auto stage_pair = [&]() INL {
            slot_wait(1);
            stage_packed_64x64<0>(slot4, 0, pk, ptrans);
            stage_packed_64x64<16>(slot4, 8192, pk, ptrans);
        };
        auto signal_both = [&]() INL {
            __syncwarp();
            warp_arrive2(sfull + w * 16, sfull + w * 16 + 8);
        };
        uint32_t un = 0;
        auto lane_id = [&]() INL { uint32_t ln; asm volatile("mov.u32 %0, %%laneid;" : "=r"(ln)); return ln; };
        auto v_addr = [&](uint32_t ln) INL { return stg + w * 16384 + (wwarp * 16 + (ln & 7)) * 128 + (((ln >> 3) ^ (ln & 7)) << 4); };
        auto v_off = [&](uint32_t a, const int h) INL { return (a ^ ((h & 1) * 64)) + (h >> 1) * 8192; };
        auto halo_ptr = [&](int mt, int g, int slot, uint32_t ln) INL { return page_ptr<uint4>(512) + (((mt * 8 + g) * 2 + w) * 5 + slot) * 128 + ln; };
        auto pack_k = [&](const float (&acc)[64]) INL {
#pragma unroll
            for (int j = 0; j < 16; j++) { pk[j] = pack_bf16(acc[4 * j], acc[4 * j + 1]); pk[16 + j] = pack_bf16(acc[4 * j + 2], acc[4 * j + 3]); }
        };
        auto unit_export = [&](int cur) INL {
            const uint32_t ln = lane_id();
            uint4* dst = halo_ptr((cur & 7) * 2 + rank, cur >> 3 & 7, wwarp, ln);
            slot_wait(1);
            stage_packed_64x64<32>(slot4, 0, pk);
            stage_packed_64x64<48>(slot4, 8192, pk);
#pragma unroll
            for (int h = 0; h < 4; h++) __stcg(dst + h * 32, make_uint4(pk[16 + h * 4], pk[17 + h * 4], pk[18 + h * 4], pk[19 + h * 4]));
            __syncwarp();
            if (wwarp == 3) {
                const uint32_t va = v_addr(ln) + 1024;
#pragma unroll
                for (int h = 0; h < 4; h++) {
                    uint32_t t[4];
                    ldmatrix_x4_t(v_off(va, h), t);
                    pk[32 + h * 4] = t[0]; pk[33 + h * 4] = t[1]; pk[34 + h * 4] = t[2]; pk[35 + h * 4] = t[3];
                }
#pragma unroll
                for (int h = 0; h < 4; h++) __stcg(dst + 128 + h * 32, make_uint4(pk[32 + h * 4], pk[33 + h * 4], pk[34 + h * 4], pk[35 + h * 4]));
                __syncwarp();
                warp_arrive(hout + w * 8);
            }
        };
        auto unit_import = [&](int cur) INL {
            const uint32_t ln = lane_id();
            const int mt = (cur & 7) * 2 + rank;
            mbar_wait(lready + un * 8, 0);
            un++;
            const uint4* src = halo_ptr(wwarp ? mt : max(mt - 1, 0), cur >> 3 & 7, (wwarp + 3) & 3, ln);
#pragma unroll
            for (int h = 0; h < 4; h++) {
                const uint4 t = __ldcg(src + h * 32);
                pk[32 + h * 4] = t.x; pk[33 + h * 4] = t.y; pk[34 + h * 4] = t.z; pk[35 + h * 4] = t.w;
            }
            if (wwarp) {
                const uint32_t va = v_addr(ln) - 1024;
#pragma unroll
                for (int h = 0; h < 4; h++) {
                    uint32_t t[4];
                    ldmatrix_x4_t(v_off(va, h), t);
                    pk[48 + h * 4] = t[0]; pk[49 + h * 4] = t[1]; pk[50 + h * 4] = t[2]; pk[51 + h * 4] = t[3];
                }
            } else {
#pragma unroll
                for (int h = 0; h < 4; h++) {
                    const uint4 t = __ldcg(src + 128 + h * 32);
                    pk[48 + h * 4] = t.x; pk[49 + h * 4] = t.y; pk[50 + h * 4] = t.z; pk[51 + h * 4] = t.w;
                }
            }
        };
        auto unit_attend = [&](const float (&q)[64], int cur) INL {
            const float cs = 0.17677669529663687f * 1.4426950408889634f;
            const uint32_t ln = lane_id();
            const int g = ln >> 2, c2 = (ln & 3) * 2, mt = (cur & 7) * 2 + rank;
            uint32_t qf[32], vo[8][4];
#pragma unroll
            for (int i = 0; i < 32; i++) qf[i] = pack_bf16(q[2 * i], q[2 * i + 1]);
            fence_regs(qf);
            const float* gp = page_ptr<float>(520) + mt * 128 + wwarp * 32 + g * 2 + w;
            const float lg0 = 1.f - __ldcg(gp), lg1 = 1.f - __ldcg(gp + 16);
            const uint32_t va = stg + w * 16384 + (wwarp * 16 + (ln & 7) + (ln >> 4) * 8) * 128 + ((((ln >> 3) & 1) ^ (ln & 7)) << 4);
#pragma unroll
            for (int i = 0; i < 8; i++) ldmatrix_x4_t((va ^ ((i & 3) * 32)) + (i >> 2) * 8192, vo[i]);
            const bool m0 = c2 > g, m1 = c2 + 1 > g, first = mt + wwarp == 0;
            const uint32_t mk = (m0 ? 0xffffu : 0u) | (m1 ? 0xffff0000u : 0u);
#pragma unroll
            for (int h = 0; h < 4; h++) {
                float s[3][4] = {};
#pragma unroll
                for (int k = 0; k < 2; k++) {
                    const int i = h * 8 + k * 4, j = h * 4 + k * 2;
                    mma_16816(s[0], qf[i], qf[i + 1], qf[i + 2], qf[i + 3], pk[32 + j], pk[33 + j]);
                    mma_16816(s[1], qf[i], qf[i + 1], qf[i + 2], qf[i + 3], pk[j], pk[j + 1]);
                    mma_16816(s[2], qf[i], qf[i + 1], qf[i + 2], qf[i + 3], pk[16 + j], pk[17 + j]);
                }
                if (first) s[0][0] = s[0][1] = -INFINITY;
                float u0 = m0 ? s[0][0] : s[1][0], u1 = m1 ? s[0][1] : s[1][1], v0 = m0 ? s[1][2] : s[2][2], v1 = m1 ? s[1][3] : s[2][3];
                float mu = fmaxf(u0, u1), mv = fmaxf(v0, v1);
                mu = fmaxf(mu, __shfl_xor_sync(0xffffffffu, mu, 1)); mv = fmaxf(mv, __shfl_xor_sync(0xffffffffu, mv, 1));
                mu = fmaxf(mu, __shfl_xor_sync(0xffffffffu, mu, 2)); mv = fmaxf(mv, __shfl_xor_sync(0xffffffffu, mv, 2));
                mu *= -cs; mv *= -cs;
                u0 = ex2(fmaf(u0, cs, mu)); u1 = ex2(fmaf(u1, cs, mu)); v0 = ex2(fmaf(v0, cs, mv)); v1 = ex2(fmaf(v1, cs, mv));
                float lu = u0 + u1, lv = v0 + v1;
                lu += __shfl_xor_sync(0xffffffffu, lu, 1); lv += __shfl_xor_sync(0xffffffffu, lv, 1);
                lu += __shfl_xor_sync(0xffffffffu, lu, 2); lv += __shfl_xor_sync(0xffffffffu, lv, 2);
                const float su = lg0 * rcp(lu), sv = lg1 * rcp(lv);
                const uint32_t pu = pack_bf16(u0 * su, u1 * su), pv = pack_bf16(v0 * sv, v1 * sv);
#pragma unroll
                for (int d = 0; d < 2; d++) {
                    const uint32_t (&vv)[4] = vo[h * 2 + d];
                    float oa[4] = {}, ob[4] = {};
                    mma_16816(oa, pk[48 + h * 4 + d * 2], pk[49 + h * 4 + d * 2], vv[0], vv[1], pu & mk, pu & ~mk);
                    mma_16816(ob, vv[0], vv[1], vv[2], vv[3], pv & mk, pv & ~mk);
                    qf[h * 8 + d * 4] = pack_bf16(oa[0], oa[1]); qf[h * 8 + d * 4 + 1] = pack_bf16(ob[0], ob[1]);
                    qf[h * 8 + d * 4 + 2] = pack_bf16(oa[2], oa[3]); qf[h * 8 + d * 4 + 3] = pack_bf16(ob[2], ob[3]);
                }
            }
#pragma unroll
            for (int i = 0; i < 32; i++) pk[i] = qf[i];
            named_sync(3 + w, 128);
        };
        auto pack_half = [&](const float (&acc)[64], const int OFF, float scale) INL {
#pragma unroll
            for (int i = 0; i < 32; i++) pk[OFF + i] = pack_bf16(acc[2 * i] * scale, acc[2 * i + 1] * scale);
        };
        auto gemm_run = [&]() INL {
                float acc0[64], acc1[64];
#pragma unroll
                for (int i = 0; i < 64; i++) pk[i] = 0;
#pragma unroll
                for (int j = 0; j < 4; j++) asm volatile("xor.b32 %0, %1, %2;" : "=r"(slot4[j]) : "r"(slot_a), "r"(j << 5));
                const uint32_t dA = desc_lo(base + w * 8192, 0), dB = desc_lo(base + 16384, 8192);
                auto wait_full = [&](int st) INL { mbar_wait_hot(gfull + st * 8, gph); };
                auto release = [&](int st) INL { arrive_pair(gempty + st * 8); };
                bool pend = false;
                auto kstep = [&](auto st_, const int Q, bool ending = false) INL {
                    constexpr int st = decltype(st_)::v, OA = st * (G_STAGE >> 4);
                    wait_full(st);
                    if (st == 2) named_sync_if(ending && w, 6, 256);
                    wg_fence();
                    wgmma_ss_n256<OA, OA>(acc0, acc1, dA, dB);
                    wg_commit();
                    wg_wait<1>();
                    release((st + 3) & 3);
                    wg_fence();
                    wgmma_ss_n256<OA + 2, OA + 128>(acc0, acc1, dA, dB);
                    wgmma_ss_n256<OA + 4, OA + 256>(acc0, acc1, dA, dB);
                    if (st == 3) named_arrive_if(ending && !w, 6, 256);
                    wgmma_ss_n256<OA + 6, OA + 384>(acc0, acc1, dA, dB);
                    wg_commit();
                    if (Q >= 0) { stage_quarter(Q); signal(Q); }
                    KTRACE(w);
                };
                wait_full(0);
                GTRACE(w);
                while (true) {
                    wg_fence();
                    wgmma_ss_n256_init(acc0, acc1, dA, dB);
                    wgmma_ss_n256<2, 128>(acc0, acc1, dA, dB);
                    wgmma_ss_n256<4, 256>(acc0, acc1, dA, dB);
                    wgmma_ss_n256<6, 384>(acc0, acc1, dA, dB);
                    wg_commit();
                    KTRACE(w);
                    const int cur = job;
                    const bool is_o = cur >= (T_O << 12), unit2 = (cur >> 6) == 3;
                    const int tail = o_tail(cur);
                    int lim = is_o ? o_head(cur) + tail : (cur < 256 ? 16 : 8);
                    int left = unit2 ? 11 : lim - (is_o ? O_STAGGER + 1 : 1);
                    bool imp = unit2;
                    next_job();
                    if (__builtin_expect(unit2, 0)) { if (tid == TRACE_TID) PTRACE(4); unit_export(cur); if (tid == TRACE_TID) PTRACE(5); }
                    if (pend) {
                        kstep(IC<1>{}, 0);
                        kstep(IC<2>{}, -1);
                        kstep(IC<3>{}, 1);
                        GTRACE(w);
                        gph ^= 1;
                        kstep(IC<0>{}, -1);
                        kstep(IC<1>{}, 2);
                        kstep(IC<2>{}, 3, left == 7);
                        kstep(IC<3>{}, -1, left == 7);
                        GTRACE(w);
                        gph ^= 1;
                        left -= 7;
                        if (left > 0) { kstep(IC<0>{}, -1); left--; }
                    }
                    int last_st = 3;
#pragma unroll 1
                    while (left > 0) {
                        auto ends = [&]() INL -> bool {
                            if (__builtin_expect(--left > 0, 1)) return false;
                            if (is_o) {
                                const uint32_t v = uniform(o_state(olim, lim - tail));
                                const int n = (v >> 1) + ((v & 1) ? 0 : tail);
                                left = n - lim; lim = n;
                            }
                            return left == 0;
                        };
                        kstep(IC<1>{}, -1);
                        if (ends()) { last_st = 1; break; }
                        kstep(IC<2>{}, -1, left == 2 && !is_o && !imp);
                        if (ends()) { last_st = 2; break; }
                        kstep(IC<3>{}, -1, left == 1 && !is_o && !imp);
                        GTRACE(w);
                        gph ^= 1;
                        if (ends()) {
                            if (!imp) break;
                            if (tid == TRACE_TID) PTRACE(6);
                            unit_import(cur);
                            if (tid == TRACE_TID) PTRACE(7);
                            imp = false; left = 4;
                        }
                        kstep(IC<0>{}, -1);
                        if (ends()) { last_st = 0; break; }
                    }
                    if (is_o) {
                        if (w) {
                            wg_wait<0>();
                            release(last_st);
                            named_sync(6, 256);
                        }
#pragma unroll 1
                        for (int i = 1; i <= O_STAGGER; i++) {
                            const int st = (last_st + i) & 3;
                            if (i > 1 && st == 0) gph ^= 1;
                            wait_full(st);
                            const uint32_t a = dA + st * (G_STAGE >> 4), b = dB + st * (G_STAGE >> 4);
                            wg_fence();
                            wgmma_ss_n256<0, 0>(acc0, acc1, a, b);
                            wgmma_ss_n256<2, 128>(acc0, acc1, a, b);
                            wgmma_ss_n256<4, 256>(acc0, acc1, a, b);
                            wgmma_ss_n256<6, 384>(acc0, acc1, a, b);
                            wg_commit();
                            named_arrive_if(!w && i == O_STAGGER, 6, 256);
                            wg_wait<1>();
                            arrive_pair(gempty + last_st * 8, i == 1 && !w);
                        }
                        slot_wait(1);
                        wg_wait<0>();
                        fence_regs(acc0);
                        fence_regs(acc1);
                        auto put = [&](const float (&acc)[64], const int Q, int off) INL {
#pragma unroll
                            for (int j = 0; j < 4; j++) {
                                const float* o = acc + Q * 32 + j * 8;
                                stmatrix_x4(slot4[j] + off, pack_bf16(o[0], o[1]), pack_bf16(o[2], o[3]), pack_bf16(o[4], o[5]), pack_bf16(o[6], o[7]));
                            }
                        };
                        put(acc0, 0, 0);
                        signal(0);
                        put(acc0, 1, 8192);
                        signal(1);
                        put(acc1, 0, -OFF_STG - w * 8192);
                        put(acc1, 1, G_STAGE - OFF_STG - w * 8192);
                        __syncwarp();
                        warp_arrive(tfull + w * 8);
#pragma unroll
                        for (int i = 1; i <= O_STAGGER; i++) release((last_st + i) & 3);
                        GTRACE(w);
#pragma unroll
                        for (int i = 0; i < 64; i++) O[i] = 0.f;
                        break;
                    }
                    if (tid == 128 && !is_o) PTRACE(12);
                    oscale1 = cur < 128 || unit2 ? Q_SCALE : 1.f;
                    ptrans = unit2;
                    if (tid == TRACE_TID && unit2) PTRACE(1);
                    named_arrive_if(w && job >= (T_A << 12), 1, TURN_THREADS);
                    wg_wait<0>();
                    fence_regs(acc0);
                    fence_regs(acc1);
                    release(3);
                    if (tid == TRACE_TID && unit2) PTRACE(2);
                    if (__builtin_expect(unit2, 0)) { unit_attend(acc0, cur); if (tid == TRACE_TID) PTRACE(3); }
                    else if (__builtin_expect((cur >> 6) == 2, 0)) pack_k(acc0);
                    else if (cur < 128) pack_half(acc0, 0, Q_SCALE);
                    else pack_half(acc0, 0, 1.f);
                    if (job >= (T_A << 12)) {
                        stage_pair();
                        signal_both();
#pragma unroll
                        for (int i = 0; i < 64; i++) asm volatile("mov.b32 %0, %1;" : "=f"(O[i]) : "f"(acc1[i]));
                        break;
                    }
                    if (cur < 128 || unit2) pack_half(acc1, 32, Q_SCALE);
                    else pack_half(acc1, 32, 1.f);
                    fence_regs(pk);
                    wait_full(0);
                    pend = (cur >> 6) != 2;
                }
        };
        setup_wait();
#pragma unroll 1
        while (true) {
        gemm_run();
        if (job < 0) break;
        if (tid == 128) PTRACE(11);
        GTRACE(w);
        {
            {
                sph ^= 1;
                uint32_t step = ~0u, ajob = ~0u;
                const int r0 = w * 64 + wwarp * 16 + (lane >> 2);
                float S[64];
                uint32_t P[32] = {};
                fence_regs(P);
                float m0 = 0.f, m1 = 0.f, l0 = 0.25f, l1 = 0.25f, g0 = oscale1, g1 = oscale1, e0 = 0.f, e1 = 0.f;
                constexpr float SUM_MAX = 1.1529215e18f;
                float sum_max = SUM_MAX;
                int rem = 0;
                int maskrem = 0;
                uint32_t starts = 1;
                auto issue_S = [&]() INL {
                    const uint32_t da = desc_lo(base + OFF_Q0 + w * 8192, 0) + (ajob & 1) * ((OFF_Q1 - OFF_Q0) >> 4);
                    const uint32_t db = desc_lo(base + OFF_K0, 0) + (step & 1) * ((OFF_K1 - OFF_K0) >> 4);
                    wg_fence();
                    wgmma_ss_n128_init<0, 0, 0>(S, da, db);
                    wgmma_ss_n128_tb0<2, 2>(S, da, db, 1);
                    wgmma_ss_n128_tb0<4, 4>(S, da, db, 1);
                    wgmma_ss_n128_tb0<6, 6>(S, da, db, 1);
                    wgmma_ss_n128_tb0<1024, 1024>(S, da, db, 1);
                    wgmma_ss_n128_tb0<1026, 1026>(S, da, db, 1);
                    wgmma_ss_n128_tb0<1028, 1028>(S, da, db, 1);
                    wgmma_ss_n128_tb0<1030, 1030>(S, da, db, 1);
                    wg_commit();
                };
                auto issue_PV = [&](uint32_t t, int pass) INL {
                    const uint32_t db = desc_lo(base + OFF_V0, 16384) + (t & 1) * ((OFF_V1 - OFF_V0) >> 4);
                    mbar_wait_hot(vfull + (t & 1) * 8, (t >> 1) & 1);
                    wg_fence();
                    wgmma_rs_n128_tb1<0>(O, P[0], P[1], P[2], P[3], db, !(starts & 2));
                    wgmma_rs_n128_tb1<128>(O, P[4], P[5], P[6], P[7], db, 1);
                    wgmma_rs_n128_tb1<256>(O, P[8], P[9], P[10], P[11], db, 1);
                    wgmma_rs_n128_tb1<384>(O, P[12], P[13], P[14], P[15], db, 1);
                    if (pass) named_arrive(pass, TURN_THREADS);
                    wgmma_rs_n128_tb1<512>(O, P[16], P[17], P[18], P[19], db, 1);
                    wgmma_rs_n128_tb1<640>(O, P[20], P[21], P[22], P[23], db, 1);
                    wgmma_rs_n128_tb1<768>(O, P[24], P[25], P[26], P[27], db, 1);
                    wgmma_rs_n128_tb1<896>(O, P[28], P[29], P[30], P[31], db, 1);
                    wg_commit();
                };
                auto pv_done = [&](uint32_t t) INL {
                    wg_wait<0>();
                    fence_regs(O);
                    arrive_pair(vempty + (t & 1) * 8, t != ~0u);
                };
                auto row_max = [&](float& a0, float& a1) INL {
                    a0 = fmaxf(S[0], S[1]); a1 = fmaxf(S[2], S[3]);
#pragma unroll
                    for (int j = 1; j < 16; j++) {
                        a0 = fmaxf(a0, fmaxf(S[j * 4], S[j * 4 + 1]));
                        a1 = fmaxf(a1, fmaxf(S[j * 4 + 2], S[j * 4 + 3]));
                    }
                    a0 = fmaxf(a0, __shfl_xor_sync(0xffffffffu, a0, 1));
                    a1 = fmaxf(a1, __shfl_xor_sync(0xffffffffu, a1, 1));
                    a0 = fmaxf(a0, __shfl_xor_sync(0xffffffffu, a0, 2));
                    a1 = fmaxf(a1, __shfl_xor_sync(0xffffffffu, a1, 2));
                };
                auto mask_diag = [&]() INL {
                    const int d = (r0 & 63) - (lane & 3) * 2;
                    auto mask_block = [&](const int J0) INL {
                        bool up0 = false, up1 = false;
#pragma unroll
                        for (int j = 0; j < 8; j++) {
                            const bool c0 = j * 8 > d, c1 = j * 8 + 1 > d;
                            if (c0) S[(J0 + j) * 4] = -INFINITY;
                            if (c1) S[(J0 + j) * 4 + 1] = -INFINITY;
                            if (up0) S[(J0 + j) * 4 + 2] = -INFINITY;
                            if (up1) S[(J0 + j) * 4 + 3] = -INFINITY;
                            up0 = c0; up1 = c1;
                        }
                    };
                    if (w) {
                        mask_block(8);
                    } else {
                        mask_block(0);
#pragma unroll
                        for (int i = 32; i < 64; i++) S[i] = -INFINITY;
                    }
                };
                auto exp_part = [&](float& t0, float& t1, const int J0, const int J1, const bool SUB) INL {
#pragma unroll
                    for (int j = J0; j < J1; j++) {
                        const float e0 = ex2(SUB ? S[j * 4] - m0 : S[j * 4]), e1 = ex2(SUB ? S[j * 4 + 1] - m0 : S[j * 4 + 1]);
                        const float e2 = ex2(SUB ? S[j * 4 + 2] - m1 : S[j * 4 + 2]), e3 = ex2(SUB ? S[j * 4 + 3] - m1 : S[j * 4 + 3]);
                        t0 = (j ? t0 : l0) + (e0 + e1);
                        t1 = (j ? t1 : l1) + (e2 + e3);
                        P[j * 2] = pack_bf16(e0, e1);
                        P[j * 2 + 1] = pack_bf16(e2, e3);
                    }
                };
                auto exp_head = [&](float& t0, float& t1, auto j1_) INL {
                    constexpr int J1 = decltype(j1_)::v;
                    float E[J1 * 4];
#pragma unroll
                    for (int j = 0; j < J1; j++) {
#pragma unroll
                        for (int e = 0; e < 4; e++) E[j * 4 + e] = ex2(S[j * 4 + e]);
                        t0 = (j ? t0 : l0) + (E[j * 4] + E[j * 4 + 1]);
                        t1 = (j ? t1 : l1) + (E[j * 4 + 2] + E[j * 4 + 3]);
                    }
                    order_after(t0 + t1, bars + 508);
                    pv_done(step - 1);
                    fence_regs(P);
                    fence_regs(S);
                    fence_regs(E);
#pragma unroll
                    for (int i = 0; i < J1 * 2; i++) P[i] = pack_bf16(E[i * 2], E[i * 2 + 1]);
                };
                auto close_job = [&]() INL {
                    l0 += __shfl_xor_sync(0xffffffffu, l0, 1); l1 += __shfl_xor_sync(0xffffffffu, l1, 1);
                    l0 += __shfl_xor_sync(0xffffffffu, l0, 2); l1 += __shfl_xor_sync(0xffffffffu, l1, 2);
                    e0 = g0 * rcp(l0); e1 = g1 * rcp(l1);
                };
                auto put_O = [&]() INL {
                    mbar_wait_hot(sempty + (w * 2 + 1) * 8, sph ^ 1);
                    uint32_t a[4];
#pragma unroll
                    for (int j = 0; j < 4; j++) asm volatile("xor.b32 %0, %1, %2;" : "=r"(a[j]) : "r"(slot_a), "r"(j << 5));
#pragma unroll
                    for (int q = 0; q < 8; q++) {
                        const float* o = O + q * 8;
                        stmatrix_x4(a[q & 3] + (q >> 2) * 8192, pack_bf16(o[0] * e0, o[1] * e0), pack_bf16(o[2] * e1, o[3] * e1),
                                    pack_bf16(o[4] * e0, o[5] * e0), pack_bf16(o[6] * e1, o[7] * e1));
                    }
                    sph ^= 1;
                    signal_both();
                };
                auto exp_plain = [&](float& t0, float& t1) INL {
                    exp_head(t0, t1, IC<5>{});
                    exp_part(t0, t1, 5, 16, false);
                    fence_regs(P);
                };
                auto exp_diag = [&](float& t0, float& t1) INL {
                    const int d = warp - 4, dd = (r0 & 7) - (int)(slot_a >> 6 & 6);
                    auto tri = [&](const int B) INL {
                        if (0 > dd) S[8 * B] = S[8 * B + 6] = -INFINITY;
                        if (1 > dd) S[8 * B + 1] = S[8 * B + 7] = -INFINITY;
                        S[8 * B + 4] = S[8 * B + 5] = -INFINITY;
                        asm volatile("" ::: "memory");
                    };
                    auto blocks = [&](const int B) INL {
                        auto zero = [&](const int B0) INL {
#pragma unroll
                            for (int i = 4 * B0; i < 4 * B + 12; i++) P[i] = 0;
                            asm volatile("" ::: "memory");
                        };
                        auto block = [&](const int B0) INL { exp_part(t0, t1, 2 * B0, 2 * B0 + 2, false); asm volatile("" ::: "memory"); };
                        if (d < B) zero(B);
                        else {
                            block(B);
                            if (d < B + 1) zero(B + 1);
                            else {
                                block(B + 1);
                                if (d < B + 2) zero(B + 2); else block(B + 2);
                            }
                        }
                    };
                    if (d > 3) {
                        if (d < 6) { if (d == 4) tri(4); else tri(5); } else { if (d == 6) tri(6); else tri(7); }
                        exp_head(t0, t1, IC<5>{});
                        exp_part(t0, t1, 5, 10, false);
                        blocks(5);
                    } else {
                        if (d < 2) { if (d == 0) tri(0); else tri(1); } else { if (d == 2) tri(2); else tri(3); }
                        exp_head(t0, t1, IC<2>{});
#pragma unroll
                        for (int i = 16; i < 32; i++) P[i] = 0;
                        blocks(1);
                    }
                    fence_regs(P);
                };
                auto unsafe_tile = [&](float t0, float t1, bool fresh) INL -> bool {
                    const bool unsafe = !(t0 + t1 <= sum_max) |
                                        (fresh & ((slot_a & 0x180) == 0) & !(fminf(t0, t1) >= 8.6736174e-19f));
                    return __any_sync(0xffffffffu, unsafe);
                };
                auto redo_tile = [&](float& t0, float& t1, bool fresh) INL {
                    wg_wait<0>();
                    fence_regs(O);
                    if (rem == maskrem) mask_diag();
                    float a0, a1;
                    row_max(a0, a1);
                    if (!fresh) { a0 = fmaxf(a0, m0); a1 = fmaxf(a1, m1); }
                    const float c0 = fresh ? 1.f : ex2(m0 - a0), c1 = fresh ? 1.f : ex2(m1 - a1);
                    m0 = a0; m1 = a1; sum_max = -1.f;
                    l0 *= c0; l1 *= c1;
#pragma unroll
                    for (int j = 0; j < 16; j++) { O[j * 4] *= c0; O[j * 4 + 1] *= c0; O[j * 4 + 2] *= c1; O[j * 4 + 3] *= c1; }
                    exp_part(t0, t1, 0, 16, true);
                };
                auto finish = [&]() INL {
                    if (starts & 2) put_O();
                    named_sync(1 + w, TURN_THREADS);
                    TRACE_MARK(0, w, step + 1);
                    issue_PV(step, w == 0 ? 2 : 0);
                    close_job();
                    pv_done(step);
                    put_O();
                };
                auto open_job = [&]() INL {
                    ajob++; rem = (job & 15) + 1; maskrem = (job & 512) ? 0 : job & 15;
                };
                auto do_step = [&]() INL -> bool {
                    float t0, t1;
                    const bool fresh = starts & 1, pending = starts & 2;
                    rem--; step++;
                    named_sync(1 + w, TURN_THREADS);
                    TRACE_MARK(0, w, step);
                    issue_S();
                    if (__builtin_expect(pending || fresh, 0)) {
                        if (pending) put_O();
                        if (fresh) {
                            close_job();
                            g0 = __ldcg(g_gate + (job & 15) * 128 + r0); g1 = __ldcg(g_gate + (job & 15) * 128 + r0 + 8);
                            l0 = 0.f; l1 = 0.f; m0 = 0.f; m1 = 0.f; sum_max = SUM_MAX;
                            if (step == 0) {
                                wg_fence();
                                wg_commit();
                                named_arrive(2 - w, TURN_THREADS);
                                goto issued;
                            }
                        }
                    }
                    issue_PV(step - 1, 2 - w);
                issued:
                    starts = (starts << 1 & 2) | (rem == 0);
                    TRACE_MARK(1, w, step);
                    wg_wait<1>();
                    fence_regs(S);
                    arrive_pair(kempty + (step & 1) * 8);
                    TRACE_MARK(2, w, step);
                    if (__builtin_expect(rem != maskrem, 1)) {
                        exp_plain(t0, t1);
                        if (__builtin_expect(!unsafe_tile(t0, t1, false) && starts == 0, 1)) {
                            l0 = t0; l1 = t1;
                            TRACE_MARK(3, w, step);
                            return true;
                        }
                    } else {
                        exp_diag(t0, t1);
                    }
                    if (unsafe_tile(t0, t1, fresh)) redo_tile(t0, t1, fresh);
                    l0 = t0; l1 = t1;
                    TRACE_MARK(3, w, step);
                    if (rem == 0) {
                        warp_arrive(qempty + (ajob & 1) * 8);
                        next_job();
                        if ((job >> 12) != T_A) return false;
                        open_job();
                    }
                    return true;
                };
                open_job();
#pragma unroll 1
                while (do_step()) {}
                finish();
            }
        }
        GTRACE(w);
        jb = uniform(jb); job = uniform(job); sph = uniform(sph); gph = uniform(gph);
        if (job < 0) break;
        }
    } else {
        reg_dec<40>();
        if (base & 1023) __trap();
        setup_wait();
        volatile uint32_t* epoch_word = reinterpret_cast<volatile uint32_t*>(smem_raw + OFF_BAR + 532);
        uint32_t epoch1 = 0;
        const int jb0 = __ffs(__ballot_sync(0xffffffffu, lane <= MAX_JOBS && (jobs[min(lane, MAX_JOBS)] >> 12) != T_P)) - 1;
        if (warp > 0) {
        if (warp == 3) { epoch1 = uniform(ld_acquire(g_flags + F_DONE)) / NUM_SMS + 1; if (lane == 0) *epoch_word = epoch1; }
        {
            if (warp == 1 && elect_one()) {
#pragma unroll
                for (int i = 0; i < 7; i++) prefetch_map(&p.amap[0] + i);
            }
            __syncwarp();
            if (warp < 3) __nanosleep(jobs[0] < 256 ? GATE_DELAY_LONG_NS : GATE_DELAY_SHORT_NS);
            if (tid == TRACE_GATE) PTRACE(10);
            float* gate_vals = reinterpret_cast<float*>(smem_raw + OFF_BAR + 576);
            if (warp == 3) {
                if (blockIdx.x == 0) g_flags[F_SPLIT + lane] = g_flags[F_TICKET + lane] = 0;
                named_sync(5, 96);
                if (lane < 16 && blockIdx.x + lane * NUM_SMS < SEQ) g_gate[blockIdx.x + lane * NUM_SMS] = 1.f / (1.f + __expf(-gate_vals[lane]));
                if (tid == TRACE_GATE) PTRACE(9);
                __threadfence();
                __syncwarp();
                if (lane == 0) red_release(g_flags + F_GATE);
            } else {
                const uint32_t bar = gatefull + (warp - 1) * 16;
                auto fetch = [&](int r) INL {
                    if (lane == 0) mbar_expect_tx(bar + (r & 2) * 4, 4096);
                    __syncwarp();
                    if (lane < 2) asm volatile("cp.async.bulk.shared::cluster.global.mbarrier::complete_tx::bytes [%0], [%1], 2048, [%2];"
                                               ::"r"(stg + ((warp - 1) * 8 + r + lane) * 2048), "l"(p.xp + (size_t)min((int)blockIdx.x + ((warp - 1) * 8 + r + lane) * NUM_SMS, SEQ - 1) * DM), "r"(bar + (r & 2) * 4) : "memory");
                };
                fetch(0); fetch(2);
                uint32_t gw[16];
#pragma unroll
                for (int i = 0; i < 4; i++) {
                    const uint4 t = __ldg(reinterpret_cast<const uint4*>(p.gate_w) + i * 32 + lane);
                    gw[i * 4] = t.x; gw[i * 4 + 1] = t.y; gw[i * 4 + 2] = t.z; gw[i * 4 + 3] = t.w;
                }
#pragma unroll 1
                for (int r = 0; r < 8; r += 2) {
                    mbar_wait(bar + (r & 2) * 4, r >> 2);
                    if (r < 4) fetch(r + 4);
                    fence_regs(gw);
                    float acc0 = 0.f, acc1 = 0.f;
#pragma unroll
                    for (int i = 0; i < 4; i++) {
                        const uint4* xr = reinterpret_cast<const uint4*>(smem_raw + OFF_STG + ((warp - 1) * 8 + r) * 2048) + i * 32 + lane;
                        const uint4 a = xr[0], c = xr[128];
                        const uint32_t av[4] = {a.x, a.y, a.z, a.w}, cv[4] = {c.x, c.y, c.z, c.w};
#pragma unroll
                        for (int e = 0; e < 4; e++) {
                            const float lo = __uint_as_float(gw[i * 4 + e] << 16), hi = __uint_as_float(gw[i * 4 + e] & 0xffff0000u);
                            acc0 = fmaf(__uint_as_float(av[e] << 16), lo, acc0);
                            acc1 = fmaf(__uint_as_float(cv[e] << 16), lo, acc1);
                            acc0 = fmaf(__uint_as_float(av[e] & 0xffff0000u), hi, acc0);
                            acc1 = fmaf(__uint_as_float(cv[e] & 0xffff0000u), hi, acc1);
                        }
                    }
                    float t = (lane < 16 ? acc0 : acc1) + __shfl_xor_sync(0xffffffffu, lane < 16 ? acc1 : acc0, 16);
#pragma unroll
                    for (int o = 8; o > 0; o >>= 1) t += __shfl_xor_sync(0xffffffffu, t, o);
                    if ((lane & 15) == 0) gate_vals[(warp - 1) * 8 + r + (lane >> 4)] = t;
                }
                warp_arrive2(sempty + (warp - 1) * 16, sempty + (warp - 1) * 16 + 8);
                named_arrive(5, 96);
                if (tid == TRACE_GATE) PTRACE(9);
            }
            if (tid == TRACE_GATE) PTRACE(8);
        }
        if (warp < 3) {
            if (elect_one()) {
                const int w = warp - 1;
                uint32_t qn = 0, un = 0;
                prefetch_map(&p.qkv_st); prefetch_map(&p.st_par);
                for (int jb = 0; jb < MAX_JOBS; jb++) {
                    const int job = jobs[jb];
                    if (job < 0) break;
                    const int type = job >> 12, pl = type == T_O ? o_state(otile, 0) >> 1 : job & 0xFFF;
                    const CUtensorMap* map = &p.qkv_st;
                    int nq = 4, mt, ob0, ob1, flag, flag2 = -1;
                    bool par = false;
                    if (type <= T_O) {
                        const int n = pl >> 3;
                        mt = (pl & 7) * 2 + rank;
                        if (type == T_O)  {
                            map = &p.out_st; ob0 = (n & 3) * 4; ob1 = ob0 + 2; flag = -1;
                            for (uint32_t tries = 0; (int32_t)(ld_acquire(g_flags + F_OUT + pl * 2 + rank) - *epoch_word) < 0; tries++) {
                                __nanosleep(300);
                                if (tries > (1u << 22)) __trap();
                            }
                            fence_async_global();
                        }
                        else if (n < 16)  { ob0 = n * 4; ob1 = ob0 + 2; flag = F_Q + n * 32 + mt; flag2 = flag + 16; }
                        else if (n < 24)  {
                            mbar_wait(hout + w * 8, un++ & 1);
                            nq = ob0 = ob1 = 0; flag = F_H + mt * 8 + (n & 7);
                        } else if (n < 32) {
                            par = true; ob0 = 192 + (n & 7) * 2; ob1 = unit_head(n & 7) * 2;
                            flag = F_CTX + mt * 40 + 32 + (n & 7); flag2 = F_Q + ob1 * 8 + mt;
                        } else            { ob0 = n * 2; ob1 = ob0 + 64; flag = F_KV + (n - 32) * 16 + mt; }
                    } else {
                        nq = 2; mt = pl & 15; ob0 = ob1 = ((pl >> 4) & 31) * 2; flag = F_CTX + mt * 40 + ((pl >> 4) & 31);
                    }
                    for (int q = 0; q < nq; q++, qn++) {
                        const uint32_t slot = w * 2 + (qn & 1);
                        const int blk = (q < 2 ? ob0 : ob1) + (q & 1);
                        if (type == T_O && q == 2) {
                            mbar_wait(tfull + w * 8, 0);
                            fence_async_smem();
                            tma_reduce_add_3d(map, base + w * 8192, 0, mt * 128 + w * 64, ob1);
                            tma_reduce_add_3d(map, base + G_STAGE + w * 8192, 0, mt * 128 + w * 64, ob1 + 1);
                            bulk_commit();
                            break;
                        }
                        mbar_wait(sfull + slot * 8, (qn >> 1) & 1);
                        fence_async_smem();
                        if (type == T_O) {
                            tma_reduce_add_3d(map, stg + slot * 8192, 0, mt * 128 + w * 64, blk);
                        } else if (par) {
                            tma_store_par(&p.st_par, stg + slot * 8192, mt * 64, w, blk);
                        } else {
                            tma_store_3d(map, stg + slot * 8192, 0, mt * 128 + w * 64, blk, POL_STREAM);
                        }
                        bulk_commit();
                        if (type == T_O) continue;
                        if (!(q & 1)) continue;
                        bulk_wait_read<1>();
                        mbar_arrive(sempty + (slot ^ 1) * 8);
                        bulk_wait_read<0>();
                        mbar_arrive(sempty + slot * 8);
                    }
                    bulk_wait<0>();
                    END_MARK(jb);
                    if (flag >= 0) {
                        asm volatile("fence.release.gpu;" ::: "memory");
                        red_relaxed(g_flags + flag);
                        if (flag2 >= 0) red_relaxed(g_flags + flag2);
                    }
                }
            }
        } else {
            int jb = 0;
            for (int un = 0; (jobs[jb] >> 12) == T_P; jb++) {
                const int n = jobs[jb] >> 3, mt = (jobs[jb] & 7) * 2 + rank;
                if ((n >> 3) != 3) continue;
                wait_flags<200>(lane == 31 || (lane == 0 && mt > 0), lane == 31 ? F_GATE : F_H + max(mt - 1, 0) * 8 + (n & 7),
                                epoch1 * (lane == 31 ? GATE_COUNT : 2));
                if (lane == 0) mbar_arrive(lready + un * 8);
                un++;
            }
            if ((jobs[jb] >> 12) != T_A) {
                wait_flags<200>(lane == 0, F_GATE, epoch1 * GATE_COUNT);
                if (lane == 0) { mbar_arrive(aready); red_relaxed(g_flags + F_DONE); }
            } else {
                const int jh = jobs[jb] >> 4 & 31, jq = jobs[jb] & 15;
                wait_flags<100>(lane <= jq || lane >= 30, lane == 31 ? F_GATE : (lane == 30 ? F_Q + jh * 16 + jq : F_KV + jh * 16 + (lane & 15)),
                                epoch1 * (lane == 31 ? GATE_COUNT : 2));
                if (lane == 0) { mbar_arrive(aready); red_relaxed(g_flags + F_DONE); }
            int left = 0, nxt = jobs[jb];
            uint32_t ajob = 0;
#pragma unroll 1
            for (uint32_t astep = 0;; astep++) {
                if (left == 0) {
                    if ((nxt >> 12) != T_A) break;
                    left = (nxt & 15) + 1;
                    nxt = jobs[++jb];
                    mbar_wait(qfull + (ajob & 1) * 8, (ajob >> 1) & 1);
                    ajob++;
                }
                left--;
                mbar_wait(kfull + (astep & 1) * 8, (astep >> 1) & 1);
                named_sync(1, TURN_THREADS);
                named_sync(2, TURN_THREADS);
            }
            named_sync(1, TURN_THREADS);
            named_sync(2, TURN_THREADS);
            }
            if (jobs[jb] == (T_O << 12)) {
                mbar_wait(gatefull, 0);
                const int tile = o_state(otile, 0) >> 1;
                uint4* dst = reinterpret_cast<uint4*>(p.out) + ((tile & 7) * 256 + rank * 128) * (DM / 8) + (tile >> 3) * 32 + lane;
#pragma unroll 4
                for (int r = 0; r < 128; r++) {
                    dst[r * (DM / 8)] = make_uint4(0, 0, 0, 0);
                    if ((r & 3) == 3) __nanosleep(CLEAR_GAP_NS);
                }
                __threadfence();
                fence_async_global();
                __syncwarp();
                if (lane == 0) red_release(g_flags + F_OUT + tile * 2 + rank);
            }
        }
        } else {
            uint32_t gph = 1;
            int vrow = 0, vblk = 0;
            bool vsolo = false;
            auto load_kv = [&](uint32_t dst, uint32_t bar, int row, int blk, bool solo) INL {
                load_operand(dst, bar, &p.qkv_ld, &p.qkv_half, row, blk, rank, solo, POL_NORMAL);
            };
            auto load_v = [&](uint32_t t) INL {
                if (t == 0) mbar_wait(gempty + 24, gph);
                mbar_wait(vempty + (t & 1) * 8, ((t >> 1) & 1) ^ 1);
                load_kv(base + ((t & 1) ? OFF_V1 : OFF_V0), vfull + (t & 1) * 8, vrow, vblk, vsolo);
            };
            int jb = jb0;
            int cur = uniform(jobs[jb]);
            auto announce = [&](uint32_t word, uint32_t v) INL {
                asm volatile("{\n.reg .pred p;\nsetp.lt.u32 p, %2, 2;\n@p red.relaxed.cluster.shared::cluster.max.u32 [%0], %1;\n}"
                             ::"r"(mapa(word, lane & 1)), "r"(v), "r"(lane) : "memory");
                __syncwarp();
            };
            uint32_t ticket = 0;
            auto draw_ticket = [&](int ojob) INL {
                asm volatile("{\n.reg .pred p;\nsetp.ne.u32 p, %2, 0;\n@p atom.relaxed.gpu.global.inc.u32 %0, [%1], 0x7fffffff;\n}"
                             : "+r"(ticket) : "l"(g_flags + F_TICKET + (ojob >> 5 & 1)), "r"((uint32_t)(rank == 0 && lane == 0)) : "memory");
                __syncwarp();
            };
            int pl = 0;
            uint32_t seen_a = 0, seen_b = 0;
            auto ask_ctx = [&]() INL {
                const uint32_t* f = g_flags + F_CTX + ((pl & 7) * 2 + rank) * 40;
                seen_a = ld_relaxed(f + lane); seen_b = ld_relaxed(f + 32 + (lane & 7));
            };
            auto open_tile = [&](int ojob) INL {
                if (rank == 0) {
                    const uint32_t t = uniform(ticket);
                    announce(otile, 2 * ((ojob & 32) ? 31 - t : t) + 1);
                }
                pl = (ojob & 32) | uniform(o_state(otile, 0) >> 1);
                ask_ctx();
            };
            const uint16_t* recs = reinterpret_cast<const uint16_t*>(rounds);
            uint32_t rec = uniform(recs[0]), nrec = uniform(recs[1]);
            int st0 = SOLO_STAGES;
#pragma unroll 1
            for (int r = 2; rec != 0xFFFF; r++) {
                const uint32_t nnrec = recs[r];
                load_round(rec, st0, gph);
                gph ^= 1;
                st0 = 0;
                rec = nrec; nrec = uniform(nnrec);
                if (nrec == 0xFFFF || (rec & 8192)) {
                    if (nrec != 0xFFFF) {
                        prefetch_map(&p.qkv_ld); prefetch_map(&p.qkv_half);
                        if ((cur >> 12) == T_O) { prefetch_map(&p.wo_a); prefetch_map(&p.wo_b); prefetch_map(&p.out_st); }
                    } else if ((cur >> 12) == T_O) {
                        if (rec != 0xFFFF) {
                            mbar_wait(aready, 0);
                            draw_ticket(cur);
                        } else {
                            open_tile(cur);
                        }
                    }
                }
            }
            int nxt = cur;
            uint32_t astep = 0;
            if ((cur >> 12) == T_A) {
            {
                const int jh = cur >> 4 & 31, jq = cur & 15, j0 = (cur & 512) ? 0 : jq;
                mbar_wait(aready, 0);
                fence_async_global();
                mbar_wait(gempty, gph);
                load_operand(base + OFF_Q0, qfull, &p.qkv_ld, &p.qkv_ld, jq * 128, jh * 2, 0, true, POL_STREAM);
                PTRACE(17);
                mbar_wait(gempty + 8, gph);
                load_kv(base + OFF_K0, kfull, j0 * 128, 64 + jh * 2, j0 == jq && (jq & 1));
                PTRACE(16);
            }
            epoch1 = *epoch_word;
            jb++;
            nxt = uniform(jobs[jb]);
            int i = 0;
            uint32_t ajob = 1;
            bool q_issued = false;
#pragma unroll 1
            while (true) {
                const int qt = cur & 15;
                const bool last = i == qt;
                const int j = (cur & 512) ? i : qt - i, blk = (cur >> 4 & 31) * 2;
                const bool solo = j == qt && (qt & 1);
                {
                    const uint32_t sl = astep & 1;
                    if (astep == 0) {
                        mbar_wait(gempty + 16, gph);
                    } else {
                        mbar_wait(kempty + sl * 8, ((astep >> 1) & 1) ^ 1);
                        load_kv(base + (sl ? OFF_K1 : OFF_K0), kfull + sl * 8, j * 128, 64 + blk, solo);
                        if (astep == 1) PTRACE(14);
                        load_v(astep - 1);
                        if (astep == 1) PTRACE(15);
                    }
                }
                vrow = j * 128; vblk = 128 + blk; vsolo = solo;
                astep++;
                if ((nxt >> 12) != T_A) {
                    if (last) break;
                } else if (!q_issued && (last || i == 2 || (i > 2 && i >= qt - 2))) {
                    const int jh = nxt >> 4 & 31, jq = nxt & 15;
                    q_issued = wait_flags(lane <= jq || lane >= 30, lane == 31 ? F_GATE : (lane == 30 ? F_Q + jh * 16 + jq : F_KV + jh * 16 + (lane & 15)),
                                          epoch1 * (lane == 31 ? GATE_COUNT : 2), last);
                    if (q_issued) {
                        mbar_wait(qempty + (ajob & 1) * 8, ((ajob >> 1) & 1) ^ 1);
                        load_operand(base + ((ajob & 1) ? OFF_Q1 : OFF_Q0), qfull + (ajob & 1) * 8, &p.qkv_ld, &p.qkv_ld, jq * 128, jh * 2, 0, true, POL_STREAM);
                    }
                }
                i++;
                if (last) {
                    cur = nxt; jb++; nxt = uniform(jobs[jb]); i = 0; ajob++; q_issued = false;
                    if ((nxt >> 12) == T_O) { prefetch_map(&p.wo_a); prefetch_map(&p.wo_b); prefetch_map(&p.out_st); }
                }
            }
            if (nxt >= 0) draw_ticket(nxt);
            load_v(astep - 1);
            if (nxt >= 0) open_tile(nxt);
            }
            int nks = 0;
            if (nxt >= 0) {
                epoch1 = *epoch_word;
                const int m0 = (pl & 7) * 256 + rank * 128, nb = (pl >> 3 & 3) * 4 + rank * 2, part = pl >> 5 & 1;
                uint32_t ready_a = 0, ready_b = 0;
                uint32_t claim_even = 0, claim_odd = 0;
                const int head = o_head(pl), tail = o_tail(pl);
                int lim = head;
                bool known = false;
#pragma unroll 1
                for (int ks = 0;; ks++) {
                    const int st = ks & 3;
                    if (rank == 0) {
                        auto exchange = [&](uint32_t& claim) INL {
                            if (ks + 1 >= head) {
                                known = (uint32_t)uniform(claim) >= O_FLEX;
                                if (!known) lim = ks + 2;
                                announce(olim, known ? 2 * (lim + tail) + 1 : 2 * lim);
                            }
                            asm volatile("{\n.reg .pred p;\nsetp.ne.u32 p, %2, 0;\n@p atom.relaxed.gpu.global.inc.u32 %0, [%1], 0x7fffffff;\n}"
                                         : "+r"(claim) : "l"(g_flags + F_SPLIT + (pl & 31)), "r"((uint32_t)(!known && lane == 0)) : "memory");
                            __syncwarp();
                        };
                        if (!known && ks + 3 >= head) { if (ks & 1) exchange(claim_odd); else exchange(claim_even); }
                    } else if (!known && ks >= lim) {
                        const uint32_t v = uniform(o_state(olim, ks));
                        known = v & 1;
                        lim = (v >> 1) - (known ? tail : 0);
                    }
                    if (ks >= lim + tail) { nks = ks; break; }
                    if (ks == CLEAR_KS && !part) warp_arrive(gatefull);
                    int acol;
                    if (ks >= lim) acol = (part ? 64 - O_T1 : 200) + ks - lim;
                    else if (part) acol = ks < O_H1 ? O_F0 + ks : O_F0 + 2 * O_H1 + O_FLEX - 1 - ks;
                    else acol = ks < 8 ? 192 + ks : (ks < O_H0 ? ks - 8 : ks - 8 + O_H1);
                    for (uint32_t tries = 0; !(((acol < 192 ? ready_a : ready_b) >> (acol >> 1 & 31)) & 1); tries++) {
                        if (ks | tries) ask_ctx();
                        ready_a = __ballot_sync(0xffffffffu, (int32_t)(seen_a - epoch1 * 2) >= 0);
                        ready_b = __ballot_sync(0xffffffffu, (int32_t)(seen_b - epoch1 * 2) >= 0);
                        fence_acquire();
                        trap_if(tries > (1u << 22));
                    }
                    {
                        const uint32_t sa = base + st * G_STAGE;
                        if (ks < 4 && astep) mbar_wait((ks < 2 ? kempty : vempty) + ((astep - 1) & 1) * 8, ((astep - 1) >> 1) & 1);
                        else mbar_wait(gempty + st * 8, gph);
                        load_kstep(sa, sa + 16384 + rank * 16384, gfull + st * 8, G_STAGE, acol >= 192 ? &p.wo_b : &p.wo_a, acol & 63, nb,
                                   &p.qkv_half, m0, acol, 1);
                    }
                    if (st == 3) gph ^= 1;
                }
            }
            if (lane == 0) {
                if (nxt >= 0) for (int s = 0; s < 4; s++) mbar_wait(gempty + s * 8, gph ^ (s < (nks & 3)));
                else for (uint32_t t = astep; t < astep + 2; t++) {
                    mbar_wait(kempty + (t & 1) * 8, ((t >> 1) & 1) ^ 1);
                    mbar_wait(vempty + (t & 1) * 8, ((t >> 1) & 1) ^ 1);
                }
            }
        }
    }
}

typedef CUresult (*EncodeFn)(CUtensorMap*, CUtensorMapDataType, cuuint32_t, void*, const cuuint64_t*, const cuuint64_t*,
                             const cuuint32_t*, const cuuint32_t*, CUtensorMapInterleave, CUtensorMapSwizzle,
                             CUtensorMapL2promotion, CUtensorMapFloatOOBfill);

void make_map3(EncodeFn enc, CUtensorMap* m, const void* ptr, int rows, int cols, int box_rows, int box_blks, bool blocked = false) {
    cuuint64_t dims[3] = {64, (cuuint64_t)rows, (cuuint64_t)(cols / 64)};
    cuuint64_t strides[2] = {blocked ? 128 : (cuuint64_t)cols * 2, blocked ? (cuuint64_t)rows * 128 : 128};
    cuuint32_t box[3] = {64, (cuuint32_t)box_rows, (cuuint32_t)box_blks};
    cuuint32_t es[3] = {1, 1, 1};
    enc(m, CU_TENSOR_MAP_DATA_TYPE_BFLOAT16, 3, const_cast<void*>(ptr), dims, strides, box, es, CU_TENSOR_MAP_INTERLEAVE_NONE,
        CU_TENSOR_MAP_SWIZZLE_128B, CU_TENSOR_MAP_L2_PROMOTION_L2_256B, CU_TENSOR_MAP_FLOAT_OOB_FILL_NONE);
}

Params h_params;

const int16_t k_jobs[NUM_SMS][MAX_JOBS] = {
    {339,153,217,8890,8339,8802,8311,9042,8405,9008,8551,9134,8677,4128,-1,-1,-1,-1,-1,-1,-1,-1,-1,-1},
    {339,153,217,8891,8338,8803,8310,9043,8404,9009,8550,9135,8676,4128,-1,-1,-1,-1,-1,-1,-1,-1,-1,-1},
    {40,0,307,8888,8289,8720,8259,8854,8539,8898,8627,8998,8655,4128,-1,-1,-1,-1,-1,-1,-1,-1,-1,-1},
    {40,0,307,8889,8288,8721,8258,8855,8538,8899,8626,8999,8654,4128,-1,-1,-1,-1,-1,-1,-1,-1,-1,-1},
    {10,157,221,8706,8269,8820,8457,9006,8687,4128,-1,-1,-1,-1,-1,-1,-1,-1,-1,-1,-1,-1,-1,-1},
    {10,157,221,8707,8268,8821,8456,9007,8686,4128,-1,-1,-1,-1,-1,-1,-1,-1,-1,-1,-1,-1,-1,-1},
    {132,196,296,8730,8333,8940,8503,9082,8697,4128,-1,-1,-1,-1,-1,-1,-1,-1,-1,-1,-1,-1,-1,-1},
    {132,196,296,8731,8332,8941,8502,9083,8696,4128,-1,-1,-1,-1,-1,-1,-1,-1,-1,-1,-1,-1,-1,-1},
    {128,192,8758,8199,8774,8313,9026,8415,9130,8663,4128,-1,-1,-1,-1,-1,-1,-1,-1,-1,-1,-1,-1,-1},
    {128,192,8759,8198,8775,8312,9027,8414,9131,8662,4128,-1,-1,-1,-1,-1,-1,-1,-1,-1,-1,-1,-1,-1},
    {133,197,8742,8369,8704,8285,8768,8543,9022,8601,4128,-1,-1,-1,-1,-1,-1,-1,-1,-1,-1,-1,-1,-1},
    {133,197,8743,8368,8705,8284,8769,8542,9023,8600,4128,-1,-1,-1,-1,-1,-1,-1,-1,-1,-1,-1,-1,-1},
    {131,195,38,8708,8265,8932,8461,8896,8631,9076,8585,4128,-1,-1,-1,-1,-1,-1,-1,-1,-1,-1,-1,-1},
    {131,195,38,8709,8264,8933,8460,8897,8630,9077,8584,4128,-1,-1,-1,-1,-1,-1,-1,-1,-1,-1,-1,-1},
    {137,201,8750,8331,8816,8533,8912,8411,9078,8671,4128,-1,-1,-1,-1,-1,-1,-1,-1,-1,-1,-1,-1,-1},
    {137,201,8751,8330,8817,8532,8913,8410,9079,8670,4128,-1,-1,-1,-1,-1,-1,-1,-1,-1,-1,-1,-1,-1},
    {43,264,440,8744,8201,8858,8417,8954,8483,9016,8649,9152,8691,4128,-1,-1,-1,-1,-1,-1,-1,-1,-1,-1},
    {43,264,440,8745,8200,8859,8416,8955,8482,9017,8648,9153,8690,4128,-1,-1,-1,-1,-1,-1,-1,-1,-1,-1},
    {151,215,8876,8299,8964,8445,9146,8703,4128,-1,-1,-1,-1,-1,-1,-1,-1,-1,-1,-1,-1,-1,-1,-1},
    {151,215,8877,8298,8965,8444,9147,8702,4128,-1,-1,-1,-1,-1,-1,-1,-1,-1,-1,-1,-1,-1,-1,-1},
    {470,5,159,223,8772,8281,8936,8407,9066,8651,4128,-1,-1,-1,-1,-1,-1,-1,-1,-1,-1,-1,-1,-1},
    {470,5,159,223,8773,8280,8937,8406,9067,8650,4128,-1,-1,-1,-1,-1,-1,-1,-1,-1,-1,-1,-1,-1},
    {136,200,444,8760,8275,8848,8477,9040,8525,9148,8681,4128,-1,-1,-1,-1,-1,-1,-1,-1,-1,-1,-1,-1},
    {136,200,444,8761,8274,8849,8476,9041,8524,9149,8680,4128,-1,-1,-1,-1,-1,-1,-1,-1,-1,-1,-1,-1},
    {46,510,462,310,8764,8293,8862,8439,9064,8653,4128,-1,-1,-1,-1,-1,-1,-1,-1,-1,-1,-1,-1,-1},
    {46,510,462,310,8765,8292,8863,8438,9065,8652,4128,-1,-1,-1,-1,-1,-1,-1,-1,-1,-1,-1,-1,-1},
    {145,209,8894,8335,8942,8485,9098,8695,4128,-1,-1,-1,-1,-1,-1,-1,-1,-1,-1,-1,-1,-1,-1,-1},
    {145,209,8895,8334,8943,8484,9099,8694,4128,-1,-1,-1,-1,-1,-1,-1,-1,-1,-1,-1,-1,-1,-1,-1},
    {140,204,8878,8329,8934,8441,9070,8685,4128,-1,-1,-1,-1,-1,-1,-1,-1,-1,-1,-1,-1,-1,-1,-1},
    {140,204,8879,8328,8935,8440,9071,8684,4128,-1,-1,-1,-1,-1,-1,-1,-1,-1,-1,-1,-1,-1,-1,-1},
    {146,210,504,8884,8301,8966,8527,9128,8603,4128,-1,-1,-1,-1,-1,-1,-1,-1,-1,-1,-1,-1,-1,-1},
    {146,210,504,8885,8300,8967,8526,9129,8602,4128,-1,-1,-1,-1,-1,-1,-1,-1,-1,-1,-1,-1,-1,-1},
    {14,6,8868,8245,8806,8267,8938,8547,9000,8611,9108,8643,4128,-1,-1,-1,-1,-1,-1,-1,-1,-1,-1,-1},
    {14,6,8869,8244,8807,8266,8939,8546,9001,8610,9109,8642,4128,-1,-1,-1,-1,-1,-1,-1,-1,-1,-1,-1},
    {144,208,8748,8211,8836,8463,9004,8591,4128,-1,-1,-1,-1,-1,-1,-1,-1,-1,-1,-1,-1,-1,-1,-1},
    {144,208,8749,8210,8837,8462,9005,8590,4128,-1,-1,-1,-1,-1,-1,-1,-1,-1,-1,-1,-1,-1,-1,-1},
    {12,4,8740,8243,8724,8287,8930,8435,8900,8517,9086,8659,4128,-1,-1,-1,-1,-1,-1,-1,-1,-1,-1,-1},
    {12,4,8741,8242,8725,8286,8931,8434,8901,8516,9087,8658,4128,-1,-1,-1,-1,-1,-1,-1,-1,-1,-1,-1},
    {143,207,8866,8353,8752,8205,8830,8409,9056,8561,9140,8581,9104,8679,4128,-1,-1,-1,-1,-1,-1,-1,-1,-1},
    {143,207,8867,8352,8753,8204,8831,8408,9057,8560,9141,8580,9105,8678,4128,-1,-1,-1,-1,-1,-1,-1,-1,-1},
    {147,211,8872,8297,8834,8459,9030,8437,9100,8665,4128,-1,-1,-1,-1,-1,-1,-1,-1,-1,-1,-1,-1,-1},
    {147,211,8873,8296,8835,8458,9031,8436,9101,8664,4128,-1,-1,-1,-1,-1,-1,-1,-1,-1,-1,-1,-1,-1},
    {41,1,8766,8327,8828,8399,9126,8667,4128,-1,-1,-1,-1,-1,-1,-1,-1,-1,-1,-1,-1,-1,-1,-1},
    {41,1,8767,8326,8829,8398,9127,8666,4128,-1,-1,-1,-1,-1,-1,-1,-1,-1,-1,-1,-1,-1,-1,-1},
    {150,214,8882,8223,8832,8473,8980,8413,9094,8669,4128,-1,-1,-1,-1,-1,-1,-1,-1,-1,-1,-1,-1,-1},
    {150,214,8883,8222,8833,8472,8981,8412,9095,8668,4128,-1,-1,-1,-1,-1,-1,-1,-1,-1,-1,-1,-1,-1},
    {141,205,33,8726,8341,8976,8479,9024,8449,9136,8501,9144,8683,4128,-1,-1,-1,-1,-1,-1,-1,-1,-1,-1},
    {141,205,33,8727,8340,8977,8478,9025,8448,9137,8500,9145,8682,4128,-1,-1,-1,-1,-1,-1,-1,-1,-1,-1},
    {277,405,152,216,8718,8475,8902,8403,9150,8661,4128,-1,-1,-1,-1,-1,-1,-1,-1,-1,-1,-1,-1,-1},
    {277,405,152,216,8719,8474,8903,8402,9151,8660,4128,-1,-1,-1,-1,-1,-1,-1,-1,-1,-1,-1,-1,-1},
    {139,203,8886,8203,8856,8433,9032,8393,9080,8599,4128,-1,-1,-1,-1,-1,-1,-1,-1,-1,-1,-1,-1,-1},
    {139,203,8887,8202,8857,8432,9033,8392,9081,8598,4128,-1,-1,-1,-1,-1,-1,-1,-1,-1,-1,-1,-1,-1},
    {149,213,8746,8303,8982,8397,9084,8645,4128,-1,-1,-1,-1,-1,-1,-1,-1,-1,-1,-1,-1,-1,-1,-1},
    {149,213,8747,8302,8983,8396,9085,8644,4128,-1,-1,-1,-1,-1,-1,-1,-1,-1,-1,-1,-1,-1,-1,-1},
    {138,202,8870,8221,8860,8395,9060,8607,4128,-1,-1,-1,-1,-1,-1,-1,-1,-1,-1,-1,-1,-1,-1,-1},
    {138,202,8871,8220,8861,8394,9061,8606,4128,-1,-1,-1,-1,-1,-1,-1,-1,-1,-1,-1,-1,-1,-1,-1},
    {134,198,8738,8225,8728,8283,8962,8541,8992,8499,9074,8609,9124,8595,9184,8693,4128,-1,-1,-1,-1,-1,-1,-1},
    {134,198,8739,8224,8729,8282,8963,8540,8993,8498,9075,8608,9125,8594,9185,8692,4128,-1,-1,-1,-1,-1,-1,-1},
    {142,206,8874,8271,8818,8447,9068,8647,4128,-1,-1,-1,-1,-1,-1,-1,-1,-1,-1,-1,-1,-1,-1,-1},
    {142,206,8875,8270,8819,8446,9069,8646,4128,-1,-1,-1,-1,-1,-1,-1,-1,-1,-1,-1,-1,-1,-1,-1},
    {47,498,506,306,8892,8277,8784,8467,9048,8535,9020,8579,9088,8657,9186,8689,4128,-1,-1,-1,-1,-1,-1,-1},
    {47,498,506,306,8893,8276,8785,8466,9049,8534,9021,8578,9089,8656,9187,8688,4128,-1,-1,-1,-1,-1,-1,-1},
    {148,212,8762,8279,8826,8523,9002,8605,4128,-1,-1,-1,-1,-1,-1,-1,-1,-1,-1,-1,-1,-1,-1,-1},
    {148,212,8763,8278,8827,8522,9003,8604,4128,-1,-1,-1,-1,-1,-1,-1,-1,-1,-1,-1,-1,-1,-1,-1},
    {276,404,268,500,450,490,374,390,430,380,356,412,168,232,9018,8701,-1,-1,-1,-1,-1,-1,-1,-1},
    {276,404,268,500,450,490,374,390,430,380,356,412,168,232,9019,8700,-1,-1,-1,-1,-1,-1,-1,-1},
    {11,403,459,507,329,393,369,377,417,361,433,167,231,9132,8699,-1,-1,-1,-1,-1,-1,-1,-1,-1},
    {11,403,459,507,329,393,369,377,417,361,433,167,231,9133,8698,-1,-1,-1,-1,-1,-1,-1,-1,-1},
    {350,486,502,262,302,334,318,87,52,100,179,243,4096,-1,-1,-1,-1,-1,-1,-1,-1,-1,-1,-1},
    {350,486,502,262,302,334,318,87,52,100,179,243,4096,-1,-1,-1,-1,-1,-1,-1,-1,-1,-1,-1},
    {340,158,222,492,60,108,76,172,236,4096,-1,-1,-1,-1,-1,-1,-1,-1,-1,-1,-1,-1,-1,-1},
    {340,158,222,492,60,108,76,172,236,4096,-1,-1,-1,-1,-1,-1,-1,-1,-1,-1,-1,-1,-1,-1},
    {42,3,35,59,107,360,408,181,245,4096,-1,-1,-1,-1,-1,-1,-1,-1,-1,-1,-1,-1,-1,-1},
    {42,3,35,59,107,360,408,181,245,4096,-1,-1,-1,-1,-1,-1,-1,-1,-1,-1,-1,-1,-1,-1},
    {45,156,220,396,85,109,93,180,244,4096,-1,-1,-1,-1,-1,-1,-1,-1,-1,-1,-1,-1,-1,-1},
    {45,156,220,396,85,109,93,180,244,4096,-1,-1,-1,-1,-1,-1,-1,-1,-1,-1,-1,-1,-1,-1},
    {466,482,266,258,37,69,53,77,183,247,4096,-1,-1,-1,-1,-1,-1,-1,-1,-1,-1,-1,-1,-1},
    {466,482,266,258,37,69,53,77,183,247,4096,-1,-1,-1,-1,-1,-1,-1,-1,-1,-1,-1,-1,-1},
    {471,407,463,442,290,322,314,386,478,382,366,414,182,246,4096,-1,-1,-1,-1,-1,-1,-1,-1,-1},
    {471,407,463,442,290,322,314,386,478,382,366,414,182,246,4096,-1,-1,-1,-1,-1,-1,-1,-1,-1},
    {469,349,485,501,445,333,317,373,477,423,439,415,173,237,4096,-1,-1,-1,-1,-1,-1,-1,-1,-1},
    {469,349,485,501,445,333,317,373,477,423,439,415,173,237,4096,-1,-1,-1,-1,-1,-1,-1,-1,-1},
    {8,269,309,453,449,489,385,425,422,358,92,188,252,4096,-1,-1,-1,-1,-1,-1,-1,-1,-1,-1},
    {8,269,309,453,449,489,385,425,422,358,92,188,252,4096,-1,-1,-1,-1,-1,-1,-1,-1,-1,-1},
    {343,287,487,263,303,455,495,391,51,91,160,224,4096,-1,-1,-1,-1,-1,-1,-1,-1,-1,-1,-1},
    {343,287,487,263,303,455,495,391,51,91,160,224,4096,-1,-1,-1,-1,-1,-1,-1,-1,-1,-1,-1},
    {464,272,480,456,288,488,392,61,379,363,435,176,240,4096,-1,-1,-1,-1,-1,-1,-1,-1,-1,-1},
    {464,272,480,456,288,488,392,61,379,363,435,176,240,4096,-1,-1,-1,-1,-1,-1,-1,-1,-1,-1},
    {336,280,400,256,448,320,312,384,424,416,352,432,472,171,235,4096,-1,-1,-1,-1,-1,-1,-1,-1},
    {336,280,400,256,448,320,312,384,424,416,352,432,472,171,235,4096,-1,-1,-1,-1,-1,-1,-1,-1},
    {337,273,265,155,219,368,376,479,359,102,184,248,4096,-1,-1,-1,-1,-1,-1,-1,-1,-1,-1,-1},
    {337,273,265,155,219,368,376,479,359,102,184,248,4096,-1,-1,-1,-1,-1,-1,-1,-1,-1,-1,-1},
    {468,284,508,260,300,324,332,388,104,72,174,238,4096,-1,-1,-1,-1,-1,-1,-1,-1,-1,-1,-1},
    {468,284,508,260,300,324,332,388,104,72,174,238,4096,-1,-1,-1,-1,-1,-1,-1,-1,-1,-1,-1},
    {338,281,2,34,66,110,78,175,239,4096,-1,-1,-1,-1,-1,-1,-1,-1,-1,-1,-1,-1,-1,-1},
    {338,281,2,34,66,110,78,175,239,4096,-1,-1,-1,-1,-1,-1,-1,-1,-1,-1,-1,-1,-1,-1},
    {130,194,39,63,55,95,103,97,4096,-1,-1,-1,-1,-1,-1,-1,-1,-1,-1,-1,-1,-1,-1,-1},
    {130,194,39,63,55,95,103,97,4096,-1,-1,-1,-1,-1,-1,-1,-1,-1,-1,-1,-1,-1,-1,-1},
    {135,199,454,494,67,83,365,413,191,255,4096,-1,-1,-1,-1,-1,-1,-1,-1,-1,-1,-1,-1,-1},
    {135,199,454,494,67,83,365,413,191,255,4096,-1,-1,-1,-1,-1,-1,-1,-1,-1,-1,-1,-1,-1},
    {348,484,460,308,292,452,316,372,428,420,476,101,187,251,4096,-1,-1,-1,-1,-1,-1,-1,-1,-1},
    {348,484,460,308,292,452,316,372,428,420,476,101,187,251,4096,-1,-1,-1,-1,-1,-1,-1,-1,-1},
    {13,154,218,58,106,74,178,242,4096,-1,-1,-1,-1,-1,-1,-1,-1,-1,-1,-1,-1,-1,-1,-1},
    {13,154,218,58,106,74,178,242,4096,-1,-1,-1,-1,-1,-1,-1,-1,-1,-1,-1,-1,-1,-1,-1},
    {465,481,457,505,289,328,71,111,79,166,230,4096,-1,-1,-1,-1,-1,-1,-1,-1,-1,-1,-1,-1},
    {465,481,457,505,289,328,71,111,79,166,230,4096,-1,-1,-1,-1,-1,-1,-1,-1,-1,-1,-1,-1},
    {44,270,446,294,326,65,81,89,161,225,4096,-1,-1,-1,-1,-1,-1,-1,-1,-1,-1,-1,-1,-1},
    {44,270,446,294,326,65,81,89,161,225,4096,-1,-1,-1,-1,-1,-1,-1,-1,-1,-1,-1,-1,-1},
    {9,511,503,295,327,375,399,381,437,353,409,473,169,233,4096,-1,-1,-1,-1,-1,-1,-1,-1,-1},
    {9,511,503,295,327,375,399,381,437,353,409,473,169,233,4096,-1,-1,-1,-1,-1,-1,-1,-1,-1},
    {347,283,483,259,291,491,331,371,431,383,367,99,186,250,4096,-1,-1,-1,-1,-1,-1,-1,-1,-1},
    {347,283,483,259,291,491,331,371,431,383,367,99,186,250,4096,-1,-1,-1,-1,-1,-1,-1,-1,-1},
    {274,282,458,261,293,493,397,389,429,421,357,75,189,253,4096,-1,-1,-1,-1,-1,-1,-1,-1,-1},
    {274,282,458,261,293,493,397,389,429,421,357,75,189,253,4096,-1,-1,-1,-1,-1,-1,-1,-1,-1},
    {278,286,406,32,64,56,48,88,170,234,4096,-1,-1,-1,-1,-1,-1,-1,-1,-1,-1,-1,-1,-1},
    {278,286,406,32,64,56,48,88,170,234,4096,-1,-1,-1,-1,-1,-1,-1,-1,-1,-1,-1,-1,-1},
    {279,351,271,447,298,330,394,370,426,378,354,434,164,228,4096,-1,-1,-1,-1,-1,-1,-1,-1,-1},
    {279,351,271,447,298,330,394,370,426,378,354,434,164,228,4096,-1,-1,-1,-1,-1,-1,-1,-1,-1},
    {344,345,497,257,297,321,313,82,50,90,98,96,4096,-1,-1,-1,-1,-1,-1,-1,-1,-1,-1,-1},
    {344,345,497,257,297,321,313,82,50,90,98,96,4096,-1,-1,-1,-1,-1,-1,-1,-1,-1,-1,-1},
    {129,193,311,335,319,86,438,364,436,163,227,4096,-1,-1,-1,-1,-1,-1,-1,-1,-1,-1,-1,-1},
    {129,193,311,335,319,86,438,364,436,163,227,4096,-1,-1,-1,-1,-1,-1,-1,-1,-1,-1,-1,-1},
    {341,285,509,461,301,325,398,80,418,362,410,474,177,241,4096,-1,-1,-1,-1,-1,-1,-1,-1,-1},
    {341,285,509,461,301,325,398,80,418,362,410,474,177,241,4096,-1,-1,-1,-1,-1,-1,-1,-1,-1},
    {342,275,267,499,299,451,395,57,49,73,185,249,4096,-1,-1,-1,-1,-1,-1,-1,-1,-1,-1,-1},
    {342,275,267,499,299,451,395,57,49,73,185,249,4096,-1,-1,-1,-1,-1,-1,-1,-1,-1,-1,-1},
    {346,402,496,304,443,323,315,387,427,419,355,411,165,229,4096,-1,-1,-1,-1,-1,-1,-1,-1,-1},
    {346,402,496,304,443,323,315,387,427,419,355,411,165,229,4096,-1,-1,-1,-1,-1,-1,-1,-1,-1},
    {15,401,305,441,70,62,54,94,190,254,4096,-1,-1,-1,-1,-1,-1,-1,-1,-1,-1,-1,-1,-1},
    {15,401,305,441,70,62,54,94,190,254,4096,-1,-1,-1,-1,-1,-1,-1,-1,-1,-1,-1,-1,-1},
    {467,7,36,68,84,105,475,162,226,4096,-1,-1,-1,-1,-1,-1,-1,-1,-1,-1,-1,-1,-1,-1},
    {467,7,36,68,84,105,475,162,226,4096,-1,-1,-1,-1,-1,-1,-1,-1,-1,-1,-1,-1,-1,-1},
};

void build_rounds() {
    for (int c = 0; c < NUM_SMS / 2; c++) {
        const int16_t* jobs = h_params.jobs[2 * c];
        int nr = 0, prev_key = -1, last = 0;
        for (int j = 0; (jobs[j] >> 12) == T_P; j++) {
            const int n = jobs[j] >> 3, a = n >= 32, unit = n >= 16 && n < 32 ? (n >> 3) - 1 : 0, cnt = a ? 2 : 4;
            const int key = (jobs[j] & 7) | a << 3 | (unit > 0) << 4;
            const int wm = n < 16 ? 0 : (n < 32 ? 1 : n >> 4 & 1), col = n < 16 ? n : (n < 32 ? n & 7 : n & 15);
            const bool keep = key == prev_key, final_tile = (jobs[j + 1] >> 12) != T_P;
            const int k0 = keep ? last : 0;
            for (int r = 0; r < cnt; r++) {
                last = (k0 + r) % cnt;
                h_params.rounds[c][nr++] = (uint16_t)((key & 15) | wm << 4 | col << 6 | last << 10 | (keep && r == 0) << 12 | (final_tile && r == 0) << 13 | unit << 14);
            }
            prev_key = key;
        }
        while (nr < MAX_ROUNDS) h_params.rounds[c][nr++] = 0xFFFF;
        h_params.first[c] = h_params.rounds[c][0];
    }
}

void build_schedule() {
    for (int c = 0; c < NUM_SMS; c++) {
        for (int j = 0; j < MAX_JOBS; j++) h_params.jobs[c][j] = k_jobs[c][j];
    }
    build_rounds();
}

}

extern "C" void kernel_launch(void* const* d_in, const int* in_sizes, int n_in, void* d_out, int out_size) {
    (void)in_sizes; (void)n_in; (void)out_size;
    static EncodeFn enc = nullptr;
    if (!enc) {
        cudaDriverEntryPointQueryResult qr;
        void* fn = nullptr;
        cudaGetDriverEntryPoint("cuTensorMapEncodeTiled", &fn, cudaEnableDefault, &qr);
        enc = (EncodeFn)fn;
        cudaFuncSetAttribute(fused_kernel, cudaFuncAttributeMaxDynamicSharedMemorySize, SMEM_BYTES);
        build_schedule();
    }
    void* qkv;
    cudaGetSymbolAddress(&qkv, g_qkv);
    Params& p = h_params;
    make_map3(enc, &p.amap[0], d_in[0], SEQ, DM, 128, 1);
    make_map3(enc, &p.amap[1], d_in[1], SEQ, DC, 128, 1);
    make_map3(enc, &p.wmap[0], d_in[2], DM, 4096, 64, 2);
    make_map3(enc, &p.wmap[2], d_in[3], DC, 4096, 64, 2);
    make_map3(enc, &p.wmap[3], d_in[4], DC, 4096, 64, 2);
    make_map3(enc, &p.wmap[1], d_in[7], DM, 3072, 64, 2);
    make_map3(enc, &p.wo_a, d_in[5], 4096, DM, 64, 2);
    make_map3(enc, &p.wo_b, d_in[8], DM, DM, 64, 2);
    make_map3(enc, &p.qkv_st, qkv, SEQ, QKV_W, 64, 1, true);
    make_map3(enc, &p.qkv_ld, qkv, SEQ, QKV_W, 128, 2, true);
    make_map3(enc, &p.qkv_half, qkv, SEQ, QKV_W, 128, 1, true);
    {
        cuuint64_t dims[4] = {64, SEQ / 2, 2, QKV_W / 64}, strides[3] = {256, 128, (cuuint64_t)SEQ * 128};
        cuuint32_t box[4] = {64, 64, 1, 1}, es[4] = {1, 1, 1, 1};
        enc(&p.st_par, CU_TENSOR_MAP_DATA_TYPE_BFLOAT16, 4, qkv, dims, strides, box, es, CU_TENSOR_MAP_INTERLEAVE_NONE,
            CU_TENSOR_MAP_SWIZZLE_128B, CU_TENSOR_MAP_L2_PROMOTION_L2_256B, CU_TENSOR_MAP_FLOAT_OOB_FILL_NONE);
        dims[3] = DM / 64; strides[0] = DM * 4; strides[1] = DM * 2; strides[2] = 128; box[2] = 2;
        enc(&p.x_par, CU_TENSOR_MAP_DATA_TYPE_BFLOAT16, 4, d_in[0], dims, strides, box, es, CU_TENSOR_MAP_INTERLEAVE_NONE,
            CU_TENSOR_MAP_SWIZZLE_128B, CU_TENSOR_MAP_L2_PROMOTION_L2_256B, CU_TENSOR_MAP_FLOAT_OOB_FILL_NONE);
    }
    make_map3(enc, &p.out_st, d_out, SEQ, DM, 64, 1);
    p.xp = (const __nv_bfloat16*)d_in[0];
    p.gate_w = (const __nv_bfloat16*)d_in[9];
    p.out = (__nv_bfloat16*)d_out;
    fused_kernel<<<NUM_SMS, 384, SMEM_BYTES, cudaStreamPerThread>>>(p);
}
```

```cpp
#include <cuda_runtime.h>
#include <cuda_bf16.h>
#include <cuda.h>
#include <stdint.h>

#define INL __attribute__((always_inline))

namespace {

constexpr int SEQ = 2048;
constexpr int DM = 1024;
constexpr int DC = 512;
constexpr int QKV_W = 13312;
constexpr int NUM_SMS = 132;
constexpr int GATE_DELAY_SHORT_NS = 1000, GATE_DELAY_LONG_NS = 3000;
constexpr int CLEAR_KS = 30, CLEAR_GAP_NS = 100;
constexpr float Q_SCALE = 0.08838834764831845f * 1.4426950408889634f;
constexpr int SOLO_STAGES = 1;

__device__ __align__(1024) __nv_bfloat16 g_qkv[(size_t)SEQ * QKV_W];
__device__ float g_gate[SEQ];
__device__ uint4 g_halo[16 * 8 * 2 * 5 * 4 * 32];

constexpr int F_Q = 0;
constexpr int F_KV = 1792;
constexpr int F_H = 768;
constexpr int F_CTX = 960;
constexpr int F_GATE = 1600;
constexpr int F_DONE = 1632;
constexpr int F_SPLIT = 1664;
constexpr int F_TICKET = 1696;
constexpr int F_OUT = 1728;
constexpr int GATE_COUNT = NUM_SMS;
__device__ uint32_t g_flags[2304];

#define END_MARK(slot)
#define TRACE_MARK(k, w, i)
#define GTRACE(w)
#define KTRACE(w)
#define PTRACE(i)
#define TRACE_GATE 32
#define TRACE_TID 128

#define STRACE(i)

__device__ __forceinline__ uint32_t smem_u32(const void* p) { return (uint32_t)__cvta_generic_to_shared(p); }
__device__ __forceinline__ void mbar_init(uint32_t bar, uint32_t cnt) {
    asm volatile("mbarrier.init.shared::cta.b64 [%0], %1;" ::"r"(bar), "r"(cnt));
}
__device__ __forceinline__ void mbar_arrive(uint32_t bar) {
    asm volatile("mbarrier.arrive.shared::cta.b64 _, [%0];" ::"r"(bar) : "memory");
}
__device__ __forceinline__ bool elect_one() {
    uint32_t r;
    asm volatile("{\n.reg .pred p;\nelect.sync _|p, 0xffffffff;\nselp.b32 %0, 1, 0, p;\n}" : "=r"(r));
    return r != 0;
}
__device__ __forceinline__ uint32_t mapa(uint32_t addr, uint32_t cta) {
    uint32_t r;
    asm("mapa.shared::cluster.u32 %0, %1, %2;" : "=r"(r) : "r"(addr), "r"(cta));
    return r;
}
__device__ __forceinline__ void warp_arrive(uint32_t bar, bool pred = true) {
    asm volatile("{\n.reg .pred p, q;\nsetp.ne.u32 q, %1, 0;\nelect.sync _|p, 0xffffffff;\nand.pred p, p, q;\n"
                 "@p mbarrier.arrive.shared::cta.b64 _, [%0];\n}" ::"r"(bar), "r"((uint32_t)pred) : "memory");
}
__device__ __forceinline__ void warp_arrive2(uint32_t bar0, uint32_t bar1) {
    asm volatile("{\n.reg .pred p;\nelect.sync _|p, 0xffffffff;\n@p mbarrier.arrive.shared::cta.b64 _, [%0];\n"
                 "@p mbarrier.arrive.shared::cta.b64 _, [%1];\n}" ::"r"(bar0), "r"(bar1) : "memory");
}
__device__ __forceinline__ void warp_arrive_pair(uint32_t bar, uint32_t peer_bar, bool pred = true) {
    asm volatile("{\n.reg .pred p, q;\nsetp.ne.u32 q, %2, 0;\nelect.sync _|p, 0xffffffff;\nand.pred p, p, q;\n"
                 "@p mbarrier.arrive.shared::cluster.b64 _, [%1];\n@p mbarrier.arrive.shared::cta.b64 _, [%0];\n}"
                 ::"r"(bar), "r"(peer_bar), "r"((uint32_t)pred) : "memory");
}
__device__ __forceinline__ void mbar_expect_tx(uint32_t bar, uint32_t bytes) {
    asm volatile("mbarrier.arrive.expect_tx.shared::cta.b64 _, [%0], %1;" ::"r"(bar), "r"(bytes) : "memory");
}
constexpr int WAIT_HINT_NS = 20000, WAIT_TRIES = 200000;
__device__ __forceinline__ void mbar_wait(uint32_t bar, uint32_t parity) {
    asm volatile("{\n.reg .pred p;\n.reg .u32 c;\n"
                 "mbarrier.try_wait.parity.shared::cta.b64 p, [%0], %1;\n@p bra DONE;\nmov.u32 c, 0;\n"
                 "SPIN:\nmbarrier.try_wait.parity.shared::cta.b64 p, [%0], %1, %2;\n@p bra DONE;\n"
                 "add.u32 c, c, 1;\nsetp.lt.u32 p, c, %3;\n@p bra SPIN;\ntrap;\nDONE:\n}"
                 ::"r"(bar), "r"(parity), "n"(WAIT_HINT_NS), "n"(WAIT_TRIES) : "memory");
}
__device__ __forceinline__ void mbar_wait_hot(uint32_t bar, uint32_t parity) {
    asm volatile("{\n.reg .pred p, q;\n.reg .u32 c;\n.reg .u64 z;\nmov.u32 c, 0;\nmov.u64 z, 0;\n"
                 "SPIN:\nmbarrier.try_wait.parity.shared::cta.b64 p, [%0], %1;\n"
                 "add.u32 c, c, 1;\nsetp.lt.and.u32 q, c, 4194304, !p;\n@q bra SPIN;\n@!p st.global.u32 [z], c;\n}"
                 ::"r"(bar), "r"(parity) : "memory");
}
constexpr uint64_t POL_STREAM = 0x12F0000000000000ull;
constexpr uint64_t POL_NORMAL = 0x1000000000000000ull;
__device__ __forceinline__ void tma_load_3d(uint32_t dst, const CUtensorMap* map, uint32_t bar, int c0, int c1, int c2, uint64_t pol = POL_NORMAL) {
    asm volatile("cp.async.bulk.tensor.3d.shared::cluster.global.mbarrier::complete_tx::bytes.L2::cache_hint [%0], [%1, {%3, %4, %5}], [%2], %6;"
                 ::"r"(dst), "l"(map), "r"(bar), "r"(c0), "r"(c1), "r"(c2), "l"(pol) : "memory");
}
__device__ __forceinline__ void load_kstep(uint32_t sa, uint32_t sw, uint32_t bar, uint32_t bytes, const CUtensorMap* wmap, int wk, int wblk,
                                           const CUtensorMap* amap, int arow, int kc, uint32_t amode) {
    asm volatile("{\n.reg .pred p, q, r;\n.reg .b32 k;\nelect.sync _|p, 0xffffffff;\nsetp.eq.and.u32 q, %9, 1, p;\nsetp.eq.and.u32 r, %9, 2, p;\nshl.b32 k, %12, 6;\n"
                 "@p mbarrier.arrive.expect_tx.shared::cta.b64 _, [%2], %3;\n"
                 "@p cp.async.bulk.tensor.3d.shared::cluster.global.mbarrier::complete_tx::bytes.multicast::cluster.L2::cache_hint [%1], [%4, {0, k, %5}], [%2], %10, %11;\n"
                 "@q cp.async.bulk.tensor.3d.shared::cluster.global.mbarrier::complete_tx::bytes.L2::cache_hint [%0], [%6, {0, %7, %8}], [%2], %11;\n"
                 "@r cp.async.bulk.tensor.4d.shared::cluster.global.mbarrier::complete_tx::bytes.L2::cache_hint [%0], [%6, {0, %7, 0, %8}], [%2], %11;\n}"
                 ::"r"(sa), "r"(sw), "r"(bar), "r"(bytes), "l"(wmap), "r"(wblk), "l"(amap), "r"(arow), "r"(kc), "r"(amode), "h"((uint16_t)3), "l"(POL_NORMAL), "r"(wk) : "memory");
}
__device__ __forceinline__ void load_operand(uint32_t dst, uint32_t bar, const CUtensorMap* full, const CUtensorMap* half, int row, int blk,
                                             uint32_t rank, bool solo, uint64_t pol) {
    asm volatile("{\n.reg .pred p, q, r;\n.reg .b32 d, b;\nelect.sync _|p, 0xffffffff;\nsetp.ne.and.u32 q, %7, 0, p;\nsetp.eq.and.u32 r, %7, 0, p;\n"
                 "mad.lo.u32 d, %6, 16384, %0;\nadd.u32 b, %5, %6;\n"
                 "@p mbarrier.arrive.expect_tx.shared::cta.b64 _, [%1], 32768;\n"
                 "@q cp.async.bulk.tensor.3d.shared::cluster.global.mbarrier::complete_tx::bytes.L2::cache_hint [%0], [%2, {0, %4, %5}], [%1], %9;\n"
                 "@r cp.async.bulk.tensor.3d.shared::cluster.global.mbarrier::complete_tx::bytes.multicast::cluster.L2::cache_hint [d], [%3, {0, %4, b}], [%1], %8, %9;\n}"
                 ::"r"(dst), "r"(bar), "l"(full), "l"(half), "r"(row), "r"(blk), "r"(rank), "r"((uint32_t)solo), "h"((uint16_t)3), "l"(pol) : "memory");
}
__device__ __forceinline__ void tma_load_par(uint32_t dst, const CUtensorMap* map, uint32_t bar, int pair, int blk) {
    asm volatile("cp.async.bulk.tensor.4d.shared::cluster.global.mbarrier::complete_tx::bytes.L2::cache_hint [%0], [%1, {0, %3, 0, %4}], [%2], %5;"
                 ::"r"(dst), "l"(map), "r"(bar), "r"(pair), "r"(blk), "l"(POL_NORMAL) : "memory");
}
__device__ __forceinline__ void tma_store_par(const CUtensorMap* map, uint32_t src, int pair, int parity, int blk) {
    asm volatile("cp.async.bulk.tensor.4d.global.shared::cta.bulk_group.L2::cache_hint [%0, {0, %2, %3, %4}], [%1], %5;"
                 ::"l"(map), "r"(src), "r"(pair), "r"(parity), "r"(blk), "l"(POL_STREAM) : "memory");
}
__device__ __forceinline__ void tma_store_3d(const CUtensorMap* map, uint32_t src, int c0, int c1, int c2, uint64_t pol) {
    asm volatile("cp.async.bulk.tensor.3d.global.shared::cta.bulk_group.L2::cache_hint [%0, {%2, %3, %4}], [%1], %5;"
                 ::"l"(map), "r"(src), "r"(c0), "r"(c1), "r"(c2), "l"(pol) : "memory");
}
__device__ __forceinline__ void tma_reduce_add_3d(const CUtensorMap* map, uint32_t src, int c0, int c1, int c2) {
    asm volatile("cp.reduce.async.bulk.tensor.3d.global.shared::cta.add.tile.bulk_group [%0, {%2, %3, %4}], [%1];"
                 ::"l"(map), "r"(src), "r"(c0), "r"(c1), "r"(c2) : "memory");
}
__device__ __forceinline__ void bulk_commit() { asm volatile("cp.async.bulk.commit_group;" ::: "memory"); }
template <int N> __device__ __forceinline__ void bulk_wait_read() { asm volatile("cp.async.bulk.wait_group.read %0;" ::"n"(N) : "memory"); }
template <int N> __device__ __forceinline__ void bulk_wait() { asm volatile("cp.async.bulk.wait_group %0;" ::"n"(N) : "memory"); }
__device__ __forceinline__ void fence_async_smem() { asm volatile("fence.proxy.async.shared::cta;" ::: "memory"); }
__device__ __forceinline__ void fence_async_global() { asm volatile("fence.proxy.async.global;" ::: "memory"); }
__device__ __forceinline__ uint32_t ld_acquire(const uint32_t* p) {
    uint32_t v;
    asm volatile("ld.acquire.gpu.global.u32 %0, [%1];" : "=r"(v) : "l"(p) : "memory");
    return v;
}
__device__ __forceinline__ uint32_t ld_relaxed(const uint32_t* p) {
    uint32_t v;
    asm volatile("ld.relaxed.gpu.global.u32 %0, [%1];" : "=r"(v) : "l"(p) : "memory");
    return v;
}
__device__ __forceinline__ void fence_acquire() { asm volatile("fence.acquire.gpu;\nfence.proxy.async.global;" ::: "memory"); }
__device__ __forceinline__ void red_release(uint32_t* p) {
    asm volatile("red.release.gpu.global.add.u32 [%0], 1;" ::"l"(p) : "memory");
}
__device__ __forceinline__ void red_relaxed(uint32_t* p) {
    asm volatile("red.relaxed.gpu.global.add.u32 [%0], 1;" ::"l"(p) : "memory");
}
__device__ __forceinline__ void prefetch_map(const CUtensorMap* map) { asm volatile("prefetch.tensormap [%0];" ::"l"(map) : "memory"); }
__device__ __forceinline__ void trap_if(bool c) { asm volatile("{\n.reg .pred p;\nsetp.ne.u32 p, %0, 0;\n@p trap;\n}" ::"r"((uint32_t)c)); }
__device__ __forceinline__ void setup_arrive() {
    asm volatile("bar.sync 0;\nbarrier.cluster.arrive.relaxed.aligned;" ::: "memory");
}
__device__ __forceinline__ void setup_wait() { asm volatile("barrier.cluster.wait.aligned;" ::: "memory"); }
__device__ __forceinline__ uint32_t cluster_rank() { uint32_t r; asm("mov.u32 %0, %%cluster_ctarank;" : "=r"(r)); return r; }
__device__ __forceinline__ void named_sync(int id, int n) { asm volatile("bar.sync %0, %1;" ::"r"(id), "r"(n) : "memory"); }
__device__ __forceinline__ void named_arrive(int id, int n) { asm volatile("bar.arrive %0, %1;" ::"r"(id), "r"(n) : "memory"); }
__device__ __forceinline__ void named_sync_if(bool c, int id, int n) {
    asm volatile("{\n.reg .pred p;\nsetp.ne.u32 p, %0, 0;\n@p bar.sync %1, %2;\n}" ::"r"((uint32_t)c), "r"(id), "r"(n) : "memory");
}
__device__ __forceinline__ void named_arrive_if(bool c, int id, int n) {
    asm volatile("{\n.reg .pred p;\nsetp.ne.u32 p, %0, 0;\n@p bar.arrive %1, %2;\n}" ::"r"((uint32_t)c), "r"(id), "r"(n) : "memory");
}
template <int V> struct IC { static constexpr int v = V; };
template <int N> __device__ __forceinline__ void reg_dec() { asm volatile("setmaxnreg.dec.sync.aligned.u32 %0;" ::"n"(N)); }
template <int N> __device__ __forceinline__ void reg_inc() { asm volatile("setmaxnreg.inc.sync.aligned.u32 %0;" ::"n"(N)); }

__device__ __forceinline__ void wg_fence() { asm volatile("wgmma.fence.sync.aligned;" ::: "memory"); }
__device__ __forceinline__ void wg_commit() { asm volatile("wgmma.commit_group.sync.aligned;" ::: "memory"); }
template <int N> __device__ __forceinline__ void wg_wait() { asm volatile("wgmma.wait_group.sync.aligned %0;" ::"n"(N) : "memory"); }
template <int N> __device__ __forceinline__ void fence_regs(float (&r)[N]) {
#pragma unroll
    for (int i = 0; i < N; i++) asm volatile("" : "+f"(r[i])::"memory");
}
template <int N> __device__ __forceinline__ void fence_regs(uint32_t (&r)[N]) {
#pragma unroll
    for (int i = 0; i < N; i++) asm volatile("" : "+r"(r[i])::"memory");
}
__device__ __forceinline__ uint32_t desc_lo(uint32_t addr, uint32_t lbo) { return ((addr & 0x3FFFF) >> 4) | ((lbo >> 4) << 16); }
__device__ __forceinline__ int uniform(int v) { return __shfl_sync(0xffffffffu, v, 0); }
__device__ __forceinline__ uint32_t pack_bf16(float lo, float hi) {
    uint32_t r;
    asm("cvt.rn.bf16x2.f32 %0, %1, %2;" : "=r"(r) : "f"(hi), "f"(lo));
    return r;
}
__device__ __forceinline__ void stmatrix_x4(uint32_t addr, uint32_t r0, uint32_t r1, uint32_t r2, uint32_t r3) {
    asm volatile("stmatrix.sync.aligned.m8n8.x4.shared.b16 [%0], {%1, %2, %3, %4};"
                 ::"r"(addr), "r"(r0), "r"(r1), "r"(r2), "r"(r3) : "memory");
}
__device__ __forceinline__ void stmatrix_x4(uint32_t addr, uint32_t r0, uint32_t r1, uint32_t r2, uint32_t r3, bool trans) {
    asm volatile("{\n.reg .pred p;\nsetp.ne.u32 p, %5, 0;\n@p stmatrix.sync.aligned.m8n8.x4.trans.shared.b16 [%0], {%1, %2, %3, %4};\n"
                 "@!p stmatrix.sync.aligned.m8n8.x4.shared.b16 [%0], {%1, %2, %3, %4};\n}"
                 ::"r"(addr), "r"(r0), "r"(r1), "r"(r2), "r"(r3), "r"((uint32_t)trans) : "memory");
}
__device__ __forceinline__ void ldmatrix_x4_t(uint32_t addr, uint32_t (&r)[4]) {
    asm volatile("ldmatrix.sync.aligned.m8n8.x4.trans.shared.b16 {%0, %1, %2, %3}, [%4];"
                 : "=r"(r[0]), "=r"(r[1]), "=r"(r[2]), "=r"(r[3]) : "r"(addr) : "memory");
}
__device__ __forceinline__ void mma_16816(float (&d)[4], uint32_t a0, uint32_t a1, uint32_t a2, uint32_t a3, uint32_t b0, uint32_t b1) {
    asm("mma.sync.aligned.m16n8k16.row.col.f32.bf16.bf16.f32 {%0, %1, %2, %3}, {%4, %5, %6, %7}, {%8, %9}, {%0, %1, %2, %3};"
        : "+f"(d[0]), "+f"(d[1]), "+f"(d[2]), "+f"(d[3]) : "r"(a0), "r"(a1), "r"(a2), "r"(a3), "r"(b0), "r"(b1));
}
__device__ __forceinline__ void order_after(float v, uint32_t scratch) {
    asm volatile("{\n.reg .pred p;\nsetp.gt.f32 p, %0, 0f70000000;\n@p st.shared.u32 [%1], 0;\n}" ::"f"(v), "r"(scratch) : "memory");
}
template <int N> __device__ __forceinline__ void code_pad() {
    if constexpr (N > 0) {
        asm volatile("pmevent 0;");
        code_pad<N - 1>();
    }
}
#define PAD_G 0
#define PAD_A 0
#define PAD_R 0
__device__ __forceinline__ float rcp(float x) { float y; asm("rcp.approx.ftz.f32 %0, %1;" : "=f"(y) : "f"(x)); return y; }
__device__ __forceinline__ float ex2(float x) { float y; asm("ex2.approx.ftz.f32 %0, %1;" : "=f"(y) : "f"(x)); return y; }

template <int OA, int OB>
__device__ __forceinline__ void wgmma_ss_n256(float (&d0)[64], float (&d1)[64], uint32_t da, uint32_t db) {
    asm volatile("{\n.reg .b32 ta, tb;\n.reg .b64 da, db;\nadd.u32 ta, %128, %130;\nadd.u32 tb, %129, %131;\n"
        "mov.b64 da, {ta, 0x40000040};\nmov.b64 db, {tb, 0x40000040};\n"
        "wgmma.mma_async.sync.aligned.m64n256k16.f32.bf16.bf16 {%0, %1, %2, %3, %4, %5, %6, %7, %8, %9, %10, %11, %12, %13, %14, %15, %16, %17, %18, %19, %20, %21, %22, %23, %24, %25, %26, %27, %28, %29, %30, %31, %32, %33, %34, %35, %36, %37, %38, %39, %40, %41, %42, %43, %44, %45, %46, %47, %48, %49, %50, %51, %52, %53, %54, %55, %56, %57, %58, %59, %60, %61, %62, %63, %64, %65, %66, %67, %68, %69, %70, %71, %72, %73, %74, %75, %76, %77, %78, %79, %80, %81, %82, %83, %84, %85, %86, %87, %88, %89, %90, %91, %92, %93, %94, %95, %96, %97, %98, %99, %100, %101, %102, %103, %104, %105, %106, %107, %108, %109, %110, %111, %112, %113, %114, %115, %116, %117, %118, %119, %120, %121, %122, %123, %124, %125, %126, %127}, da, db, 1, 1, 1, 0, 1;\n}\n"
        : "+f"(d0[0]), "+f"(d0[1]), "+f"(d0[2]), "+f"(d0[3]), "+f"(d0[4]), "+f"(d0[5]), "+f"(d0[6]), "+f"(d0[7]), "+f"(d0[8]), "+f"(d0[9]), "+f"(d0[10]), "+f"(d0[11]), "+f"(d0[12]), "+f"(d0[13]), "+f"(d0[14]), "+f"(d0[15]), "+f"(d0[16]), "+f"(d0[17]), "+f"(d0[18]), "+f"(d0[19]), "+f"(d0[20]), "+f"(d0[21]), "+f"(d0[22]), "+f"(d0[23]), "+f"(d0[24]), "+f"(d0[25]), "+f"(d0[26]), "+f"(d0[27]), "+f"(d0[28]), "+f"(d0[29]), "+f"(d0[30]), "+f"(d0[31]), "+f"(d0[32]), "+f"(d0[33]), "+f"(d0[34]), "+f"(d0[35]), "+f"(d0[36]), "+f"(d0[37]), "+f"(d0[38]), "+f"(d0[39]), "+f"(d0[40]), "+f"(d0[41]), "+f"(d0[42]), "+f"(d0[43]), "+f"(d0[44]), "+f"(d0[45]), "+f"(d0[46]), "+f"(d0[47]), "+f"(d0[48]), "+f"(d0[49]), "+f"(d0[50]), "+f"(d0[51]), "+f"(d0[52]), "+f"(d0[53]), "+f"(d0[54]), "+f"(d0[55]), "+f"(d0[56]), "+f"(d0[57]), "+f"(d0[58]), "+f"(d0[59]), "+f"(d0[60]), "+f"(d0[61]), "+f"(d0[62]), "+f"(d0[63]), "+f"(d1[0]), "+f"(d1[1]), "+f"(d1[2]), "+f"(d1[3]), "+f"(d1[4]), "+f"(d1[5]), "+f"(d1[6]), "+f"(d1[7]), "+f"(d1[8]), "+f"(d1[9]), "+f"(d1[10]), "+f"(d1[11]), "+f"(d1[12]), "+f"(d1[13]), "+f"(d1[14]), "+f"(d1[15]), "+f"(d1[16]), "+f"(d1[17]), "+f"(d1[18]), "+f"(d1[19]), "+f"(d1[20]), "+f"(d1[21]), "+f"(d1[22]), "+f"(d1[23]), "+f"(d1[24]), "+f"(d1[25]), "+f"(d1[26]), "+f"(d1[27]), "+f"(d1[28]), "+f"(d1[29]), "+f"(d1[30]), "+f"(d1[31]), "+f"(d1[32]), "+f"(d1[33]), "+f"(d1[34]), "+f"(d1[35]), "+f"(d1[36]), "+f"(d1[37]), "+f"(d1[38]), "+f"(d1[39]), "+f"(d1[40]), "+f"(d1[41]), "+f"(d1[42]), "+f"(d1[43]), "+f"(d1[44]), "+f"(d1[45]), "+f"(d1[46]), "+f"(d1[47]), "+f"(d1[48]), "+f"(d1[49]), "+f"(d1[50]), "+f"(d1[51]), "+f"(d1[52]), "+f"(d1[53]), "+f"(d1[54]), "+f"(d1[55]), "+f"(d1[56]), "+f"(d1[57]), "+f"(d1[58]), "+f"(d1[59]), "+f"(d1[60]), "+f"(d1[61]), "+f"(d1[62]), "+f"(d1[63])
        : "r"(da), "r"(db), "n"(OA), "n"(OB));
}

__device__ __forceinline__ void wgmma_ss_n256_init(float (&d0)[64], float (&d1)[64], uint32_t da, uint32_t db) {
    asm volatile("{\n.reg .b64 da, db;\n"
        "mov.b64 da, {%128, 0x40000040};\nmov.b64 db, {%129, 0x40000040};\n"
        "wgmma.mma_async.sync.aligned.m64n256k16.f32.bf16.bf16 {%0, %1, %2, %3, %4, %5, %6, %7, %8, %9, %10, %11, %12, %13, %14, %15, %16, %17, %18, %19, %20, %21, %22, %23, %24, %25, %26, %27, %28, %29, %30, %31, %32, %33, %34, %35, %36, %37, %38, %39, %40, %41, %42, %43, %44, %45, %46, %47, %48, %49, %50, %51, %52, %53, %54, %55, %56, %57, %58, %59, %60, %61, %62, %63, %64, %65, %66, %67, %68, %69, %70, %71, %72, %73, %74, %75, %76, %77, %78, %79, %80, %81, %82, %83, %84, %85, %86, %87, %88, %89, %90, %91, %92, %93, %94, %95, %96, %97, %98, %99, %100, %101, %102, %103, %104, %105, %106, %107, %108, %109, %110, %111, %112, %113, %114, %115, %116, %117, %118, %119, %120, %121, %122, %123, %124, %125, %126, %127}, da, db, 0, 1, 1, 0, 1;\n}\n"
        : "=f"(d0[0]), "=f"(d0[1]), "=f"(d0[2]), "=f"(d0[3]), "=f"(d0[4]), "=f"(d0[5]), "=f"(d0[6]), "=f"(d0[7]), "=f"(d0[8]), "=f"(d0[9]), "=f"(d0[10]), "=f"(d0[11]), "=f"(d0[12]), "=f"(d0[13]), "=f"(d0[14]), "=f"(d0[15]), "=f"(d0[16]), "=f"(d0[17]), "=f"(d0[18]), "=f"(d0[19]), "=f"(d0[20]), "=f"(d0[21]), "=f"(d0[22]), "=f"(d0[23]), "=f"(d0[24]), "=f"(d0[25]), "=f"(d0[26]), "=f"(d0[27]), "=f"(d0[28]), "=f"(d0[29]), "=f"(d0[30]), "=f"(d0[31]), "=f"(d0[32]), "=f"(d0[33]), "=f"(d0[34]), "=f"(d0[35]), "=f"(d0[36]), "=f"(d0[37]), "=f"(d0[38]), "=f"(d0[39]), "=f"(d0[40]), "=f"(d0[41]), "=f"(d0[42]), "=f"(d0[43]), "=f"(d0[44]), "=f"(d0[45]), "=f"(d0[46]), "=f"(d0[47]), "=f"(d0[48]), "=f"(d0[49]), "=f"(d0[50]), "=f"(d0[51]), "=f"(d0[52]), "=f"(d0[53]), "=f"(d0[54]), "=f"(d0[55]), "=f"(d0[56]), "=f"(d0[57]), "=f"(d0[58]), "=f"(d0[59]), "=f"(d0[60]), "=f"(d0[61]), "=f"(d0[62]), "=f"(d0[63]), "=f"(d1[0]), "=f"(d1[1]), "=f"(d1[2]), "=f"(d1[3]), "=f"(d1[4]), "=f"(d1[5]), "=f"(d1[6]), "=f"(d1[7]), "=f"(d1[8]), "=f"(d1[9]), "=f"(d1[10]), "=f"(d1[11]), "=f"(d1[12]), "=f"(d1[13]), "=f"(d1[14]), "=f"(d1[15]), "=f"(d1[16]), "=f"(d1[17]), "=f"(d1[18]), "=f"(d1[19]), "=f"(d1[20]), "=f"(d1[21]), "=f"(d1[22]), "=f"(d1[23]), "=f"(d1[24]), "=f"(d1[25]), "=f"(d1[26]), "=f"(d1[27]), "=f"(d1[28]), "=f"(d1[29]), "=f"(d1[30]), "=f"(d1[31]), "=f"(d1[32]), "=f"(d1[33]), "=f"(d1[34]), "=f"(d1[35]), "=f"(d1[36]), "=f"(d1[37]), "=f"(d1[38]), "=f"(d1[39]), "=f"(d1[40]), "=f"(d1[41]), "=f"(d1[42]), "=f"(d1[43]), "=f"(d1[44]), "=f"(d1[45]), "=f"(d1[46]), "=f"(d1[47]), "=f"(d1[48]), "=f"(d1[49]), "=f"(d1[50]), "=f"(d1[51]), "=f"(d1[52]), "=f"(d1[53]), "=f"(d1[54]), "=f"(d1[55]), "=f"(d1[56]), "=f"(d1[57]), "=f"(d1[58]), "=f"(d1[59]), "=f"(d1[60]), "=f"(d1[61]), "=f"(d1[62]), "=f"(d1[63])
        : "r"(da), "r"(db));
}

template <int TB, int OA, int OB>
__device__ __forceinline__ void wgmma_ss_n128_init(float (&d)[64], uint32_t da, uint32_t db) {
    asm volatile("{\n.reg .b32 ta, tb;\n.reg .b64 da, db;\nadd.u32 ta, %64, %66;\nadd.u32 tb, %65, %67;\n"
        "mov.b64 da, {ta, 0x40000040};\nmov.b64 db, {tb, 0x40000040};\n"
        "wgmma.mma_async.sync.aligned.m64n128k16.f32.bf16.bf16 {%0, %1, %2, %3, %4, %5, %6, %7, %8, %9, %10, %11, %12, %13, %14, %15, %16, %17, %18, %19, %20, %21, %22, %23, %24, %25, %26, %27, %28, %29, %30, %31, %32, %33, %34, %35, %36, %37, %38, %39, %40, %41, %42, %43, %44, %45, %46, %47, %48, %49, %50, %51, %52, %53, %54, %55, %56, %57, %58, %59, %60, %61, %62, %63}, da, db, 0, 1, 1, 0, %68;\n}\n"
        : "=f"(d[0]), "=f"(d[1]), "=f"(d[2]), "=f"(d[3]), "=f"(d[4]), "=f"(d[5]), "=f"(d[6]), "=f"(d[7]), "=f"(d[8]), "=f"(d[9]), "=f"(d[10]), "=f"(d[11]), "=f"(d[12]), "=f"(d[13]), "=f"(d[14]), "=f"(d[15]), "=f"(d[16]), "=f"(d[17]), "=f"(d[18]), "=f"(d[19]), "=f"(d[20]), "=f"(d[21]), "=f"(d[22]), "=f"(d[23]), "=f"(d[24]), "=f"(d[25]), "=f"(d[26]), "=f"(d[27]), "=f"(d[28]), "=f"(d[29]), "=f"(d[30]), "=f"(d[31]), "=f"(d[32]), "=f"(d[33]), "=f"(d[34]), "=f"(d[35]), "=f"(d[36]), "=f"(d[37]), "=f"(d[38]), "=f"(d[39]), "=f"(d[40]), "=f"(d[41]), "=f"(d[42]), "=f"(d[43]), "=f"(d[44]), "=f"(d[45]), "=f"(d[46]), "=f"(d[47]), "=f"(d[48]), "=f"(d[49]), "=f"(d[50]), "=f"(d[51]), "=f"(d[52]), "=f"(d[53]), "=f"(d[54]), "=f"(d[55]), "=f"(d[56]), "=f"(d[57]), "=f"(d[58]), "=f"(d[59]), "=f"(d[60]), "=f"(d[61]), "=f"(d[62]), "=f"(d[63])
        : "r"(da), "r"(db), "n"(OA), "n"(OB), "n"(TB));
}

template <int OA, int OB>
__device__ __forceinline__ void wgmma_ss_n128_tb0(float (&d)[64], uint32_t da, uint32_t db, int scale_d) {
    asm volatile("{\n.reg .pred p;\n.reg .b32 ta, tb;\n.reg .b64 da, db;\nsetp.ne.b32 p, %66, 0;\nadd.u32 ta, %64, %67;\nadd.u32 tb, %65, %68;\n"
        "mov.b64 da, {ta, 0x40000040};\nmov.b64 db, {tb, 0x40000040};\n"
        "wgmma.mma_async.sync.aligned.m64n128k16.f32.bf16.bf16 "
        "{%0, %1, %2, %3, %4, %5, %6, %7, %8, %9, %10, %11, %12, %13, %14, %15, %16, %17, %18, %19, %20, %21, %22, %23, %24, %25, %26, %27, %28, %29, %30, %31, %32, %33, %34, %35, %36, %37, %38, %39, %40, %41, %42, %43, %44, %45, %46, %47, %48, %49, %50, %51, %52, %53, %54, %55, %56, %57, %58, %59, %60, %61, %62, %63}, da, db, p, 1, 1, 0, 0;\n}\n"
        : "+f"(d[0]), "+f"(d[1]), "+f"(d[2]), "+f"(d[3]), "+f"(d[4]), "+f"(d[5]), "+f"(d[6]), "+f"(d[7]), "+f"(d[8]), "+f"(d[9]), "+f"(d[10]), "+f"(d[11]), "+f"(d[12]), "+f"(d[13]), "+f"(d[14]), "+f"(d[15]), "+f"(d[16]), "+f"(d[17]), "+f"(d[18]), "+f"(d[19]), "+f"(d[20]), "+f"(d[21]), "+f"(d[22]), "+f"(d[23]), "+f"(d[24]), "+f"(d[25]), "+f"(d[26]), "+f"(d[27]), "+f"(d[28]), "+f"(d[29]), "+f"(d[30]), "+f"(d[31]), "+f"(d[32]), "+f"(d[33]), "+f"(d[34]), "+f"(d[35]), "+f"(d[36]), "+f"(d[37]), "+f"(d[38]), "+f"(d[39]), "+f"(d[40]), "+f"(d[41]), "+f"(d[42]), "+f"(d[43]), "+f"(d[44]), "+f"(d[45]), "+f"(d[46]), "+f"(d[47]), "+f"(d[48]), "+f"(d[49]), "+f"(d[50]), "+f"(d[51]), "+f"(d[52]), "+f"(d[53]), "+f"(d[54]), "+f"(d[55]), "+f"(d[56]), "+f"(d[57]), "+f"(d[58]), "+f"(d[59]), "+f"(d[60]), "+f"(d[61]), "+f"(d[62]), "+f"(d[63])
        : "r"(da), "r"(db), "r"(scale_d), "n"(OA), "n"(OB));
}

template <int OB>
__device__ __forceinline__ void wgmma_rs_n128_tb1(float (&d)[64], uint32_t a0, uint32_t a1, uint32_t a2, uint32_t a3, uint32_t db, int scale_d) {
    asm volatile("{\n.reg .pred p;\n.reg .b32 tb;\n.reg .b64 db;\nsetp.ne.b32 p, %69, 0;\nadd.u32 tb, %68, %70;\n"
        "mov.b64 db, {tb, 0x40000040};\n"
        "wgmma.mma_async.sync.aligned.m64n128k16.f32.bf16.bf16 "
        "{%0, %1, %2, %3, %4, %5, %6, %7, %8, %9, %10, %11, %12, %13, %14, %15, %16, %17, %18, %19, %20, %21, %22, %23, %24, %25, %26, %27, %28, %29, %30, %31, %32, %33, %34, %35, %36, %37, %38, %39, %40, %41, %42, %43, %44, %45, %46, %47, %48, %49, %50, %51, %52, %53, %54, %55, %56, %57, %58, %59, %60, %61, %62, %63}, {%64, %65, %66, %67}, db, p, 1, 1, 1;\n}\n"
        : "+f"(d[0]), "+f"(d[1]), "+f"(d[2]), "+f"(d[3]), "+f"(d[4]), "+f"(d[5]), "+f"(d[6]), "+f"(d[7]), "+f"(d[8]), "+f"(d[9]), "+f"(d[10]), "+f"(d[11]), "+f"(d[12]), "+f"(d[13]), "+f"(d[14]), "+f"(d[15]), "+f"(d[16]), "+f"(d[17]), "+f"(d[18]), "+f"(d[19]), "+f"(d[20]), "+f"(d[21]), "+f"(d[22]), "+f"(d[23]), "+f"(d[24]), "+f"(d[25]), "+f"(d[26]), "+f"(d[27]), "+f"(d[28]), "+f"(d[29]), "+f"(d[30]), "+f"(d[31]), "+f"(d[32]), "+f"(d[33]), "+f"(d[34]), "+f"(d[35]), "+f"(d[36]), "+f"(d[37]), "+f"(d[38]), "+f"(d[39]), "+f"(d[40]), "+f"(d[41]), "+f"(d[42]), "+f"(d[43]), "+f"(d[44]), "+f"(d[45]), "+f"(d[46]), "+f"(d[47]), "+f"(d[48]), "+f"(d[49]), "+f"(d[50]), "+f"(d[51]), "+f"(d[52]), "+f"(d[53]), "+f"(d[54]), "+f"(d[55]), "+f"(d[56]), "+f"(d[57]), "+f"(d[58]), "+f"(d[59]), "+f"(d[60]), "+f"(d[61]), "+f"(d[62]), "+f"(d[63])
        : "r"(a0), "r"(a1), "r"(a2), "r"(a3), "r"(db), "r"(scale_d), "n"(OB));
}

__device__ __forceinline__ uint32_t stage_addr(uint32_t block, int warp, int lane) {
    return block + (warp * 16 + (lane & 7) + ((lane >> 3) & 1) * 8) * 128 + (((lane >> 4) ^ (lane & 7)) << 4);
}
template <int OFF, int N>
__device__ __forceinline__ void stage_packed_64x64(uint32_t a0, int off, const uint32_t (&v)[N]) {
#pragma unroll
    for (int j = 0; j < 8; j += 2) {
        uint32_t a = a0;
        if (j) asm volatile("xor.b32 %0, %1, %2;" : "=r"(a) : "r"(a0), "r"(j << 4));
        stmatrix_x4(a + off, v[OFF + j * 2], v[OFF + j * 2 + 1], v[OFF + j * 2 + 2], v[OFF + j * 2 + 3]);
    }
}

template <int OFF, int N>
__device__ __forceinline__ void stage_packed_64x64(const uint32_t (&a)[4], int off, const uint32_t (&v)[N]) {
#pragma unroll
    for (int j = 0; j < 4; j++) stmatrix_x4(a[j] + off, v[OFF + j * 4], v[OFF + j * 4 + 1], v[OFF + j * 4 + 2], v[OFF + j * 4 + 3]);
}

template <int OFF, int N>
__device__ __forceinline__ void stage_packed_64x64(const uint32_t (&a)[4], int off, const uint32_t (&v)[N], bool trans) {
#pragma unroll
    for (int j = 0; j < 4; j++) stmatrix_x4(a[j] + off, v[OFF + j * 4], v[OFF + j * 4 + 1], v[OFF + j * 4 + 2], v[OFF + j * 4 + 3], trans);
}

constexpr int MAX_JOBS = 24;
constexpr int MAX_ROUNDS = 44;
constexpr int T_P = 0, T_O = 1, T_A = 2;
constexpr int HQ_A = 4, HQ_B = 28;
__host__ __device__ constexpr int unit_head(int g) { return g + (g < 4 ? HQ_A : HQ_B - 4); }
constexpr int G_STAGE = 49152;
constexpr int OFF_Q0 = 0, OFF_K0 = 32768, OFF_Q1 = 65536, OFF_K1 = 98304, OFF_V0 = 131072, OFF_V1 = 163840;
constexpr int OFF_STG = 196608;
constexpr int OFF_BAR = 229376;
constexpr int SMEM_BYTES = OFF_BAR + 640;
constexpr int TURN_THREADS = 288;

struct Params {
    CUtensorMap amap[2];
    CUtensorMap wmap[4];
    CUtensorMap x_par, wo_a, wo_b, qkv_st, qkv_ld, qkv_half, st_par, out_st;
    const __nv_bfloat16* xp;
    const __nv_bfloat16* gate_w;
    __nv_bfloat16* out;
    uint16_t first[NUM_SMS / 2];
    int16_t jobs[NUM_SMS][MAX_JOBS];
    uint16_t rounds[NUM_SMS / 2][MAX_ROUNDS];
};

constexpr int O_STAGGER = 4;
constexpr int O_F0 = 35, O_H1 = 5;
constexpr int O_FLEX = 16, O_H0 = O_F0 + 8, O_T0 = 8, O_T1 = 64 - O_F0 - O_FLEX - O_H1;
__device__ __forceinline__ int o_head(int job) { return (job & 32) ? O_H1 : O_H0; }
__device__ __forceinline__ int o_tail(int job) { return (job & 32) ? O_T1 : O_T0; }
__device__ __forceinline__ uint32_t o_state(uint32_t word, int have) {
    uint32_t v;
    asm volatile("{\n.reg .pred p, q;\n.reg .u32 c, t;\nmov.u32 c, 0;\n"
                 "SPIN:\nld.volatile.shared.u32 %0, [%1];\nand.b32 t, %0, 1;\nsetp.ne.u32 q, t, 0;\nsetp.gt.or.u32 p, %0, %2, q;\n@p bra DONE;\n"
                 "add.u32 c, c, 1;\nsetp.lt.u32 q, c, 16777216;\n@q bra SPIN;\ntrap;\nDONE:\n}"
                 : "=r"(v) : "r"(word), "r"(2 * have + 1) : "memory");
    return v;
}

template <class T> __device__ __forceinline__ T* page_ptr(int off) {
    extern __shared__ __align__(1024) uint8_t smem_raw[];
    return *reinterpret_cast<T* volatile*>(smem_raw + OFF_BAR + off);
}
template <int SLEEP_NS = 0>
__device__ __forceinline__ bool wait_flags(bool active, int idx, uint32_t target, bool block = true) {
    for (uint32_t tries = 0;; tries++) {
        const bool ok = !active | ((int32_t)(ld_acquire(g_flags + idx) - target) >= 0);
        if (__all_sync(0xffffffffu, ok)) break;
        if (!block) return false;
        if (SLEEP_NS) __nanosleep(SLEEP_NS);
        trap_if(tries > (1u << 22));
    }
    fence_async_global();
    return true;
}

__global__ void __cluster_dims__(2, 1, 1) __launch_bounds__(384, 1)
fused_kernel(const __grid_constant__ Params p) {
    extern __shared__ __align__(1024) uint8_t smem_raw[];
    const uint32_t base = smem_u32(smem_raw);
    const uint32_t bars = base + OFF_BAR;
    const uint32_t gfull = bars, gempty = bars + 32, sfull = bars + 64, sempty = bars + 96;
    const uint32_t qfull = bars + 128, qempty = bars + 144, kfull = bars + 160, kempty = bars + 176;
    const uint32_t vfull = bars + 192, vempty = bars + 208, lready = bars + 224, hout = bars + 240;
    const uint32_t tfull = bars + 256, aready = bars + 272, gatefull = bars + 280;
    const uint32_t otile = bars + 528;
    const uint32_t olim = bars + 504;
    const uint32_t stg = base + OFF_STG;
    uint32_t* rounds = reinterpret_cast<uint32_t*>(smem_raw + OFF_BAR + 416);
    if (threadIdx.x < 32) STRACE(0);
    const int tid = threadIdx.x, warp = uniform(tid >> 5), lane = tid & 31, wg = warp >> 2;
    const uint32_t rank = cluster_rank();
    int* jobs = reinterpret_cast<int*>(smem_raw + OFF_BAR + 312);
    auto w_map = [&](uint32_t rec, uint32_t half) INL { return &p.wmap[(rec & 8) ? 2 + half : ((rec >> 15) && half ? 0 : rec >> 4 & 1)]; };
    auto w_blk = [&](uint32_t rec, uint32_t half) INL -> int {
        const int col = rec >> 6 & 15;
        if (rec & 8) return (col + (rec & 16)) * 2;
        return rec >> 14 == 0 ? col * 4 + half * 2 : (rec >> 14 == 1 ? 16 + half * 16 + col * 2 : (half ? unit_head(col) : col) * 2);
    };
    auto load_a = [&](uint32_t rec, uint32_t sa, uint32_t bar, int kc) INL {
        if (rec >> 14) tma_load_par(sa, &p.x_par, bar, (rec & 7) * 128 + rank * 64, kc);
        else           tma_load_3d(sa, &p.amap[rec >> 3 & 1], bar, 0, (rec & 7) * 256 + rank * 128, kc);
    };
    auto load_round = [&](uint32_t rec, int st0, uint32_t parity) INL {
        const CUtensorMap* wm = w_map(rec, rank);
        const CUtensorMap* am = rec >> 14 ? &p.x_par : &p.amap[rec >> 3 & 1];
        const int wb = w_blk(rec, rank), kc0 = (rec >> 10 & 3) * 4, arow = ((rec & 7) * 256 + rank * 128) >> (rec >> 14 ? 1 : 0);
        const uint32_t bytes = (rec & 4096) ? G_STAGE - 16384 : G_STAGE, amode = (rec & 4096) ? 0 : (rec >> 14 ? 2 : 1);
#pragma unroll 1
        for (int st = st0; st < 4; st++) {
            const uint32_t sa = base + st * G_STAGE;
            mbar_wait(gempty + st * 8, parity);
            load_kstep(sa, sa + 16384 + rank * 16384, gfull + st * 8, bytes, wm, kc0 + st, wb, am, arow, kc0 + st, amode);
        }
    };
    if (warp < 1) {
        const uint32_t rec0 = p.first[blockIdx.x >> 1];
        if (elect_one()) {
#pragma unroll
            for (int st = 0; st < SOLO_STAGES; st++) mbar_init(gfull + st * 8, 1);
            fence_async_smem();
#pragma unroll
            for (int st = 0; st < SOLO_STAGES; st++) {
                const uint32_t sa = base + st * G_STAGE;
                mbar_expect_tx(gfull + st * 8, G_STAGE);
                load_a(rec0, sa, gfull + st * 8, st);
                tma_load_3d(sa + 16384, w_map(rec0, 0), gfull + st * 8, 0, st * 64, w_blk(rec0, 0));
                tma_load_3d(sa + 32768, w_map(rec0, 1), gfull + st * 8, 0, st * 64, w_blk(rec0, 1));
            }
            asm volatile("fence.mbarrier_init.release.cluster;" ::: "memory");
        }
        __syncwarp();
    } else if (warp == 1) {
        if (elect_one()) {
#pragma unroll
            for (int i = SOLO_STAGES; i < 39; i++)
                mbar_init(bars + i * 8, (0x0CC000F0ull >> i & 1) ? 16 : ((0x300000F00ull >> i & 1) ? 4 : ((0xC0000ull >> i & 1) ? 8 : 1)));
            asm volatile("fence.mbarrier_init.release.cluster;" ::: "memory");
            fence_async_smem();
        }
        __syncwarp();
    } else if (warp == 2) {
        const int jl = lane < MAX_JOBS ? p.jobs[blockIdx.x][lane] : -1;
        if (lane <= MAX_JOBS) jobs[lane] = jl;
        if ((jl >> 12) == T_O) *reinterpret_cast<volatile uint32_t*>(smem_raw + OFF_BAR + 504) = 2 * o_head(jl);
        if (lane == 31) *reinterpret_cast<volatile uint32_t*>(smem_raw + OFF_BAR + 528) = 0;
    } else if (warp == 3) {
        if (lane == 31) *reinterpret_cast<ulonglong2*>(smem_raw + OFF_BAR + 512) = make_ulonglong2((uint64_t)g_halo, (uint64_t)g_gate);
        if (lane < MAX_ROUNDS / 2) rounds[lane] = reinterpret_cast<const uint32_t*>(p.rounds[blockIdx.x >> 1])[lane];
    }
    if (warp < 4) STRACE(1 + warp);
    setup_arrive();
    if (warp == 0) STRACE(5);
    if (warp > 3) {
        reg_inc<232>();
        const int w = wg - 1, wwarp = warp & 3;
        code_pad<PAD_G>();
        const uint32_t slot_a = stage_addr(stg + w * 16384, wwarp, lane);
        const uint32_t bars_peer = uniform(mapa(bars, rank ^ 1));
        auto arrive_pair = [&](uint32_t bar, bool pred = true) INL { warp_arrive_pair(bar, bars_peer + (bar - bars), pred); };
        uint32_t gph = 0;
        uint32_t sph = 1;
        int jb = 0;
        int job = uniform(jobs[0]);
        auto next_job = [&]() INL { jb++; job = uniform(jobs[jb]); };
        auto slot_wait = [&](int q) INL { mbar_wait(sempty + (w * 2 + (q & 1)) * 8, (q >> 1) ^ sph ^ 1); };
        auto signal = [&](int q) INL {
            __syncwarp();
            warp_arrive(sfull + (w * 2 + (q & 1)) * 8);
        };
        uint32_t pk[64];
        float O[64];
        float oscale1 = 1.f;
        uint32_t slot4[4];
        bool ptrans = false;
        auto stage_quarter = [&](const int Q) INL {
            slot_wait(Q);
            if (Q == 0) stage_packed_64x64<0>(slot4, 0, pk, ptrans);
            if (Q == 1) stage_packed_64x64<16>(slot4, 8192, pk, ptrans);
            if (Q == 2) stage_packed_64x64<32>(slot4, 0, pk);
            if (Q == 3) stage_packed_64x64<48>(slot4, 8192, pk);
        };
        auto stage_pair = [&]() INL {
            slot_wait(1);
            stage_packed_64x64<0>(slot4, 0, pk, ptrans);
            stage_packed_64x64<16>(slot4, 8192, pk, ptrans);
        };
        auto signal_both = [&]() INL {
            __syncwarp();
            warp_arrive2(sfull + w * 16, sfull + w * 16 + 8);
        };
        uint32_t un = 0;
        auto lane_id = [&]() INL { uint32_t ln; asm volatile("mov.u32 %0, %%laneid;" : "=r"(ln)); return ln; };
        auto v_addr = [&](uint32_t ln) INL { return stg + w * 16384 + (wwarp * 16 + (ln & 7)) * 128 + (((ln >> 3) ^ (ln & 7)) << 4); };
        auto v_off = [&](uint32_t a, const int h) INL { return (a ^ ((h & 1) * 64)) + (h >> 1) * 8192; };
        auto halo_ptr = [&](int mt, int g, int slot, uint32_t ln) INL { return page_ptr<uint4>(512) + (((mt * 8 + g) * 2 + w) * 5 + slot) * 128 + ln; };
        auto pack_k = [&](const float (&acc)[64]) INL {
#pragma unroll
            for (int j = 0; j < 16; j++) { pk[j] = pack_bf16(acc[4 * j], acc[4 * j + 1]); pk[16 + j] = pack_bf16(acc[4 * j + 2], acc[4 * j + 3]); }
        };
        auto unit_export = [&](int cur) INL {
            const uint32_t ln = lane_id();
            uint4* dst = halo_ptr((cur & 7) * 2 + rank, cur >> 3 & 7, wwarp, ln);
            slot_wait(1);
            stage_packed_64x64<32>(slot4, 0, pk);
            stage_packed_64x64<48>(slot4, 8192, pk);
#pragma unroll
            for (int h = 0; h < 4; h++) __stcg(dst + h * 32, make_uint4(pk[16 + h * 4], pk[17 + h * 4], pk[18 + h * 4], pk[19 + h * 4]));
            __syncwarp();
            if (wwarp == 3) {
                const uint32_t va = v_addr(ln) + 1024;
#pragma unroll
                for (int h = 0; h < 4; h++) {
                    uint32_t t[4];
                    ldmatrix_x4_t(v_off(va, h), t);
                    pk[32 + h * 4] = t[0]; pk[33 + h * 4] = t[1]; pk[34 + h * 4] = t[2]; pk[35 + h * 4] = t[3];
                }
#pragma unroll
                for (int h = 0; h < 4; h++) __stcg(dst + 128 + h * 32, make_uint4(pk[32 + h * 4], pk[33 + h * 4], pk[34 + h * 4], pk[35 + h * 4]));
                __syncwarp();
                warp_arrive(hout + w * 8);
            }
        };
        auto unit_import = [&](int cur) INL {
            const uint32_t ln = lane_id();
            const int mt = (cur & 7) * 2 + rank;
            mbar_wait(lready + un * 8, 0);
            un++;
            const uint4* src = halo_ptr(wwarp ? mt : max(mt - 1, 0), cur >> 3 & 7, (wwarp + 3) & 3, ln);
#pragma unroll
            for (int h = 0; h < 4; h++) {
                const uint4 t = __ldcg(src + h * 32);
                pk[32 + h * 4] = t.x; pk[33 + h * 4] = t.y; pk[34 + h * 4] = t.z; pk[35 + h * 4] = t.w;
            }
            if (wwarp) {
                const uint32_t va = v_addr(ln) - 1024;
#pragma unroll
                for (int h = 0; h < 4; h++) {
                    uint32_t t[4];
                    ldmatrix_x4_t(v_off(va, h), t);
                    pk[48 + h * 4] = t[0]; pk[49 + h * 4] = t[1]; pk[50 + h * 4] = t[2]; pk[51 + h * 4] = t[3];
                }
            } else {
#pragma unroll
                for (int h = 0; h < 4; h++) {
                    const uint4 t = __ldcg(src + 128 + h * 32);
                    pk[48 + h * 4] = t.x; pk[49 + h * 4] = t.y; pk[50 + h * 4] = t.z; pk[51 + h * 4] = t.w;
                }
            }
        };
        auto unit_attend = [&](const float (&q)[64], int cur) INL {
            const float cs = 0.17677669529663687f * 1.4426950408889634f;
            const uint32_t ln = lane_id();
            const int g = ln >> 2, c2 = (ln & 3) * 2, mt = (cur & 7) * 2 + rank;
            uint32_t qf[32], vo[8][4];
#pragma unroll
            for (int i = 0; i < 32; i++) qf[i] = pack_bf16(q[2 * i], q[2 * i + 1]);
            fence_regs(qf);
            const float* gp = page_ptr<float>(520) + mt * 128 + wwarp * 32 + g * 2 + w;
            const float lg0 = 1.f - __ldcg(gp), lg1 = 1.f - __ldcg(gp + 16);
            const uint32_t va = stg + w * 16384 + (wwarp * 16 + (ln & 7) + (ln >> 4) * 8) * 128 + ((((ln >> 3) & 1) ^ (ln & 7)) << 4);
#pragma unroll
            for (int i = 0; i < 8; i++) ldmatrix_x4_t((va ^ ((i & 3) * 32)) + (i >> 2) * 8192, vo[i]);
            const bool m0 = c2 > g, m1 = c2 + 1 > g, first = mt + wwarp == 0;
            const uint32_t mk = (m0 ? 0xffffu : 0u) | (m1 ? 0xffff0000u : 0u);
#pragma unroll
            for (int h = 0; h < 4; h++) {
                float s[3][4] = {};
#pragma unroll
                for (int k = 0; k < 2; k++) {
                    const int i = h * 8 + k * 4, j = h * 4 + k * 2;
                    mma_16816(s[0], qf[i], qf[i + 1], qf[i + 2], qf[i + 3], pk[32 + j], pk[33 + j]);
                    mma_16816(s[1], qf[i], qf[i + 1], qf[i + 2], qf[i + 3], pk[j], pk[j + 1]);
                    mma_16816(s[2], qf[i], qf[i + 1], qf[i + 2], qf[i + 3], pk[16 + j], pk[17 + j]);
                }
                if (first) s[0][0] = s[0][1] = -INFINITY;
                float u0 = m0 ? s[0][0] : s[1][0], u1 = m1 ? s[0][1] : s[1][1], v0 = m0 ? s[1][2] : s[2][2], v1 = m1 ? s[1][3] : s[2][3];
                float mu = fmaxf(u0, u1), mv = fmaxf(v0, v1);
                mu = fmaxf(mu, __shfl_xor_sync(0xffffffffu, mu, 1)); mv = fmaxf(mv, __shfl_xor_sync(0xffffffffu, mv, 1));
                mu = fmaxf(mu, __shfl_xor_sync(0xffffffffu, mu, 2)); mv = fmaxf(mv, __shfl_xor_sync(0xffffffffu, mv, 2));
                mu *= -cs; mv *= -cs;
                u0 = ex2(fmaf(u0, cs, mu)); u1 = ex2(fmaf(u1, cs, mu)); v0 = ex2(fmaf(v0, cs, mv)); v1 = ex2(fmaf(v1, cs, mv));
                float lu = u0 + u1, lv = v0 + v1;
                lu += __shfl_xor_sync(0xffffffffu, lu, 1); lv += __shfl_xor_sync(0xffffffffu, lv, 1);
                lu += __shfl_xor_sync(0xffffffffu, lu, 2); lv += __shfl_xor_sync(0xffffffffu, lv, 2);
                const float su = lg0 * rcp(lu), sv = lg1 * rcp(lv);
                const uint32_t pu = pack_bf16(u0 * su, u1 * su), pv = pack_bf16(v0 * sv, v1 * sv);
#pragma unroll
                for (int d = 0; d < 2; d++) {
                    const uint32_t (&vv)[4] = vo[h * 2 + d];
                    float oa[4] = {}, ob[4] = {};
                    mma_16816(oa, pk[48 + h * 4 + d * 2], pk[49 + h * 4 + d * 2], vv[0], vv[1], pu & mk, pu & ~mk);
                    mma_16816(ob, vv[0], vv[1], vv[2], vv[3], pv & mk, pv & ~mk);
                    qf[h * 8 + d * 4] = pack_bf16(oa[0], oa[1]); qf[h * 8 + d * 4 + 1] = pack_bf16(ob[0], ob[1]);
                    qf[h * 8 + d * 4 + 2] = pack_bf16(oa[2], oa[3]); qf[h * 8 + d * 4 + 3] = pack_bf16(ob[2], ob[3]);
                }
            }
#pragma unroll
            for (int i = 0; i < 32; i++) pk[i] = qf[i];
            named_sync(3 + w, 128);
        };
        auto pack_half = [&](const float (&acc)[64], const int OFF, float scale) INL {
#pragma unroll
            for (int i = 0; i < 32; i++) pk[OFF + i] = pack_bf16(acc[2 * i] * scale, acc[2 * i + 1] * scale);
        };
        auto gemm_run = [&]() INL {
                float acc0[64], acc1[64];
#pragma unroll
                for (int i = 0; i < 64; i++) pk[i] = 0;
#pragma unroll
                for (int j = 0; j < 4; j++) asm volatile("xor.b32 %0, %1, %2;" : "=r"(slot4[j]) : "r"(slot_a), "r"(j << 5));
                const uint32_t dA = desc_lo(base + w * 8192, 0), dB = desc_lo(base + 16384, 8192);
                auto wait_full = [&](int st) INL { mbar_wait_hot(gfull + st * 8, gph); };
                auto release = [&](int st) INL { arrive_pair(gempty + st * 8); };
                bool pend = false;
                auto kstep = [&](auto st_, const int Q, bool ending = false) INL {
                    constexpr int st = decltype(st_)::v, OA = st * (G_STAGE >> 4);
                    wait_full(st);
                    if (st == 2) named_sync_if(ending && w, 6, 256);
                    wg_fence();
                    wgmma_ss_n256<OA, OA>(acc0, acc1, dA, dB);
                    wg_commit();
                    wg_wait<1>();
                    release((st + 3) & 3);
                    wg_fence();
                    wgmma_ss_n256<OA + 2, OA + 128>(acc0, acc1, dA, dB);
                    wgmma_ss_n256<OA + 4, OA + 256>(acc0, acc1, dA, dB);
                    if (st == 3) named_arrive_if(ending && !w, 6, 256);
                    wgmma_ss_n256<OA + 6, OA + 384>(acc0, acc1, dA, dB);
                    wg_commit();
                    if (Q >= 0) { stage_quarter(Q); signal(Q); }
                    KTRACE(w);
                };
                wait_full(0);
                GTRACE(w);
                while (true) {
                    wg_fence();
                    wgmma_ss_n256_init(acc0, acc1, dA, dB);
                    wgmma_ss_n256<2, 128>(acc0, acc1, dA, dB);
                    wgmma_ss_n256<4, 256>(acc0, acc1, dA, dB);
                    wgmma_ss_n256<6, 384>(acc0, acc1, dA, dB);
                    wg_commit();
                    KTRACE(w);
                    const int cur = job;
                    const bool is_o = cur >= (T_O << 12), unit2 = (cur >> 6) == 3;
                    const int tail = o_tail(cur);
                    int lim = is_o ? o_head(cur) + tail : (cur < 256 ? 16 : 8);
                    int left = unit2 ? 11 : lim - (is_o ? O_STAGGER + 1 : 1);
                    bool imp = unit2;
                    next_job();
                    if (__builtin_expect(unit2, 0)) { if (tid == TRACE_TID) PTRACE(4); unit_export(cur); if (tid == TRACE_TID) PTRACE(5); }
                    if (pend) {
                        kstep(IC<1>{}, 0);
                        kstep(IC<2>{}, -1);
                        kstep(IC<3>{}, 1);
                        GTRACE(w);
                        gph ^= 1;
                        kstep(IC<0>{}, -1);
                        kstep(IC<1>{}, 2);
                        kstep(IC<2>{}, 3, left == 7);
                        kstep(IC<3>{}, -1, left == 7);
                        GTRACE(w);
                        gph ^= 1;
                        left -= 7;
                        if (left > 0) { kstep(IC<0>{}, -1); left--; }
                    }
                    int last_st = 3;
#pragma unroll 1
                    while (left > 0) {
                        auto ends = [&]() INL -> bool {
                            if (__builtin_expect(--left > 0, 1)) return false;
                            if (is_o) {
                                const uint32_t v = uniform(o_state(olim, lim - tail));
                                const int n = (v >> 1) + ((v & 1) ? 0 : tail);
                                left = n - lim; lim = n;
                            }
                            return left == 0;
                        };
                        kstep(IC<1>{}, -1);
                        if (ends()) { last_st = 1; break; }
                        kstep(IC<2>{}, -1, left == 2 && !is_o && !imp);
                        if (ends()) { last_st = 2; break; }
                        kstep(IC<3>{}, -1, left == 1 && !is_o && !imp);
                        GTRACE(w);
                        gph ^= 1;
                        if (ends()) {
                            if (!imp) break;
                            if (tid == TRACE_TID) PTRACE(6);
                            unit_import(cur);
                            if (tid == TRACE_TID) PTRACE(7);
                            imp = false; left = 4;
                        }
                        kstep(IC<0>{}, -1);
                        if (ends()) { last_st = 0; break; }
                    }
                    if (is_o) {
                        if (w) {
                            wg_wait<0>();
                            release(last_st);
                            named_sync(6, 256);
                        }
#pragma unroll 1
                        for (int i = 1; i <= O_STAGGER; i++) {
                            const int st = (last_st + i) & 3;
                            if (i > 1 && st == 0) gph ^= 1;
                            wait_full(st);
                            const uint32_t a = dA + st * (G_STAGE >> 4), b = dB + st * (G_STAGE >> 4);
                            wg_fence();
                            wgmma_ss_n256<0, 0>(acc0, acc1, a, b);
                            wgmma_ss_n256<2, 128>(acc0, acc1, a, b);
                            wgmma_ss_n256<4, 256>(acc0, acc1, a, b);
                            wgmma_ss_n256<6, 384>(acc0, acc1, a, b);
                            wg_commit();
                            named_arrive_if(!w && i == O_STAGGER, 6, 256);
                            wg_wait<1>();
                            arrive_pair(gempty + last_st * 8, i == 1 && !w);
                        }
                        slot_wait(1);
                        wg_wait<0>();
                        fence_regs(acc0);
                        fence_regs(acc1);
                        auto put = [&](const float (&acc)[64], const int Q, int off) INL {
#pragma unroll
                            for (int j = 0; j < 4; j++) {
                                const float* o = acc + Q * 32 + j * 8;
                                stmatrix_x4(slot4[j] + off, pack_bf16(o[0], o[1]), pack_bf16(o[2], o[3]), pack_bf16(o[4], o[5]), pack_bf16(o[6], o[7]));
                            }
                        };
                        put(acc0, 0, 0);
                        signal(0);
                        put(acc0, 1, 8192);
                        signal(1);
                        put(acc1, 0, -OFF_STG - w * 8192);
                        put(acc1, 1, G_STAGE - OFF_STG - w * 8192);
                        __syncwarp();
                        warp_arrive(tfull + w * 8);
#pragma unroll
                        for (int i = 1; i <= O_STAGGER; i++) release((last_st + i) & 3);
                        GTRACE(w);
#pragma unroll
                        for (int i = 0; i < 64; i++) O[i] = 0.f;
                        break;
                    }
                    if (tid == 128 && !is_o) PTRACE(12);
                    oscale1 = cur < 128 || unit2 ? Q_SCALE : 1.f;
                    ptrans = unit2;
                    if (tid == TRACE_TID && unit2) PTRACE(1);
                    named_arrive_if(w && job >= (T_A << 12), 1, TURN_THREADS);
                    wg_wait<0>();
                    fence_regs(acc0);
                    fence_regs(acc1);
                    release(3);
                    if (tid == TRACE_TID && unit2) PTRACE(2);
                    if (__builtin_expect(unit2, 0)) { unit_attend(acc0, cur); if (tid == TRACE_TID) PTRACE(3); }
                    else if (__builtin_expect((cur >> 6) == 2, 0)) pack_k(acc0);
                    else if (cur < 128) pack_half(acc0, 0, Q_SCALE);
                    else pack_half(acc0, 0, 1.f);
                    if (job >= (T_A << 12)) {
                        stage_pair();
                        signal_both();
#pragma unroll
                        for (int i = 0; i < 64; i++) asm volatile("mov.b32 %0, %1;" : "=f"(O[i]) : "f"(acc1[i]));
                        break;
                    }
                    if (cur < 128 || unit2) pack_half(acc1, 32, Q_SCALE);
                    else pack_half(acc1, 32, 1.f);
                    fence_regs(pk);
                    wait_full(0);
                    pend = (cur >> 6) != 2;
                }
        };
        setup_wait();
#pragma unroll 1
        while (true) {
        gemm_run();
        if (job < 0) break;
        if (tid == 128) PTRACE(11);
        GTRACE(w);
        {
            {
                sph ^= 1;
                code_pad<PAD_A>();
                uint32_t step = ~0u, ajob = ~0u;
                const int r0 = w * 64 + wwarp * 16 + (lane >> 2);
                float S[64];
                uint32_t P[32] = {};
                fence_regs(P);
                float m0 = 0.f, m1 = 0.f, l0 = 0.25f, l1 = 0.25f, g0 = oscale1, g1 = oscale1, e0 = 0.f, e1 = 0.f;
                constexpr float SUM_MAX = 1.1529215e18f;
                float sum_max = SUM_MAX;
                int rem = 0;
                int maskrem = 0;
                uint32_t starts = 1;
                auto issue_S = [&]() INL {
                    const uint32_t da = desc_lo(base + OFF_Q0 + w * 8192, 0) + (ajob & 1) * ((OFF_Q1 - OFF_Q0) >> 4);
                    const uint32_t db = desc_lo(base + OFF_K0, 0) + (step & 1) * ((OFF_K1 - OFF_K0) >> 4);
                    wg_fence();
                    wgmma_ss_n128_init<0, 0, 0>(S, da, db);
                    wgmma_ss_n128_tb0<2, 2>(S, da, db, 1);
                    wgmma_ss_n128_tb0<4, 4>(S, da, db, 1);
                    wgmma_ss_n128_tb0<6, 6>(S, da, db, 1);
                    wgmma_ss_n128_tb0<1024, 1024>(S, da, db, 1);
                    wgmma_ss_n128_tb0<1026, 1026>(S, da, db, 1);
                    wgmma_ss_n128_tb0<1028, 1028>(S, da, db, 1);
                    wgmma_ss_n128_tb0<1030, 1030>(S, da, db, 1);
                    wg_commit();
                };
                auto issue_PV = [&](uint32_t t, int pass) INL {
                    const uint32_t db = desc_lo(base + OFF_V0, 16384) + (t & 1) * ((OFF_V1 - OFF_V0) >> 4);
                    mbar_wait_hot(vfull + (t & 1) * 8, (t >> 1) & 1);
                    wg_fence();
                    wgmma_rs_n128_tb1<0>(O, P[0], P[1], P[2], P[3], db, !(starts & 2));
                    wgmma_rs_n128_tb1<128>(O, P[4], P[5], P[6], P[7], db, 1);
                    wgmma_rs_n128_tb1<256>(O, P[8], P[9], P[10], P[11], db, 1);
                    wgmma_rs_n128_tb1<384>(O, P[12], P[13], P[14], P[15], db, 1);
                    if (pass) named_arrive(pass, TURN_THREADS);
                    wgmma_rs_n128_tb1<512>(O, P[16], P[17], P[18], P[19], db, 1);
                    wgmma_rs_n128_tb1<640>(O, P[20], P[21], P[22], P[23], db, 1);
                    wgmma_rs_n128_tb1<768>(O, P[24], P[25], P[26], P[27], db, 1);
                    wgmma_rs_n128_tb1<896>(O, P[28], P[29], P[30], P[31], db, 1);
                    wg_commit();
                };
                auto pv_done = [&](uint32_t t) INL {
                    wg_wait<0>();
                    fence_regs(O);
                    arrive_pair(vempty + (t & 1) * 8, t != ~0u);
                };
                auto row_max = [&](float& a0, float& a1) INL {
                    a0 = fmaxf(S[0], S[1]); a1 = fmaxf(S[2], S[3]);
#pragma unroll
                    for (int j = 1; j < 16; j++) {
                        a0 = fmaxf(a0, fmaxf(S[j * 4], S[j * 4 + 1]));
                        a1 = fmaxf(a1, fmaxf(S[j * 4 + 2], S[j * 4 + 3]));
                    }
                    a0 = fmaxf(a0, __shfl_xor_sync(0xffffffffu, a0, 1));
                    a1 = fmaxf(a1, __shfl_xor_sync(0xffffffffu, a1, 1));
                    a0 = fmaxf(a0, __shfl_xor_sync(0xffffffffu, a0, 2));
                    a1 = fmaxf(a1, __shfl_xor_sync(0xffffffffu, a1, 2));
                };
                auto mask_diag = [&]() INL {
                    const int d = (r0 & 63) - (lane & 3) * 2;
                    auto mask_block = [&](const int J0) INL {
                        bool up0 = false, up1 = false;
#pragma unroll
                        for (int j = 0; j < 8; j++) {
                            const bool c0 = j * 8 > d, c1 = j * 8 + 1 > d;
                            if (c0) S[(J0 + j) * 4] = -INFINITY;
                            if (c1) S[(J0 + j) * 4 + 1] = -INFINITY;
                            if (up0) S[(J0 + j) * 4 + 2] = -INFINITY;
                            if (up1) S[(J0 + j) * 4 + 3] = -INFINITY;
                            up0 = c0; up1 = c1;
                        }
                    };
                    if (w) {
                        mask_block(8);
                    } else {
                        mask_block(0);
#pragma unroll
                        for (int i = 32; i < 64; i++) S[i] = -INFINITY;
                    }
                };
                auto exp_part = [&](float& t0, float& t1, const int J0, const int J1, const bool SUB) INL {
#pragma unroll
                    for (int j = J0; j < J1; j++) {
                        const float e0 = ex2(SUB ? S[j * 4] - m0 : S[j * 4]), e1 = ex2(SUB ? S[j * 4 + 1] - m0 : S[j * 4 + 1]);
                        const float e2 = ex2(SUB ? S[j * 4 + 2] - m1 : S[j * 4 + 2]), e3 = ex2(SUB ? S[j * 4 + 3] - m1 : S[j * 4 + 3]);
                        t0 = (j ? t0 : l0) + (e0 + e1);
                        t1 = (j ? t1 : l1) + (e2 + e3);
                        P[j * 2] = pack_bf16(e0, e1);
                        P[j * 2 + 1] = pack_bf16(e2, e3);
                    }
                };
                auto exp_head = [&](float& t0, float& t1, auto j1_) INL {
                    constexpr int J1 = decltype(j1_)::v;
                    float E[J1 * 4];
#pragma unroll
                    for (int j = 0; j < J1; j++) {
#pragma unroll
                        for (int e = 0; e < 4; e++) E[j * 4 + e] = ex2(S[j * 4 + e]);
                        t0 = (j ? t0 : l0) + (E[j * 4] + E[j * 4 + 1]);
                        t1 = (j ? t1 : l1) + (E[j * 4 + 2] + E[j * 4 + 3]);
                    }
                    order_after(t0 + t1, bars + 508);
                    pv_done(step - 1);
                    fence_regs(P);
                    fence_regs(S);
                    fence_regs(E);
#pragma unroll
                    for (int i = 0; i < J1 * 2; i++) P[i] = pack_bf16(E[i * 2], E[i * 2 + 1]);
                };
                auto close_job = [&]() INL {
                    l0 += __shfl_xor_sync(0xffffffffu, l0, 1); l1 += __shfl_xor_sync(0xffffffffu, l1, 1);
                    l0 += __shfl_xor_sync(0xffffffffu, l0, 2); l1 += __shfl_xor_sync(0xffffffffu, l1, 2);
                    e0 = g0 * rcp(l0); e1 = g1 * rcp(l1);
                };
                auto put_O = [&]() INL {
                    mbar_wait_hot(sempty + (w * 2 + 1) * 8, sph ^ 1);
                    uint32_t a[4];
#pragma unroll
                    for (int j = 0; j < 4; j++) asm volatile("xor.b32 %0, %1, %2;" : "=r"(a[j]) : "r"(slot_a), "r"(j << 5));
#pragma unroll
                    for (int q = 0; q < 8; q++) {
                        const float* o = O + q * 8;
                        stmatrix_x4(a[q & 3] + (q >> 2) * 8192, pack_bf16(o[0] * e0, o[1] * e0), pack_bf16(o[2] * e1, o[3] * e1),
                                    pack_bf16(o[4] * e0, o[5] * e0), pack_bf16(o[6] * e1, o[7] * e1));
                    }
                    sph ^= 1;
                    signal_both();
                };
                auto exp_plain = [&](float& t0, float& t1) INL {
                    exp_head(t0, t1, IC<5>{});
                    exp_part(t0, t1, 5, 16, false);
                    fence_regs(P);
                };
                auto exp_diag = [&](float& t0, float& t1) INL {
                    const int d = warp - 4, dd = (r0 & 7) - (int)(slot_a >> 6 & 6);
                    auto tri = [&](const int B) INL {
                        if (0 > dd) S[8 * B] = S[8 * B + 6] = -INFINITY;
                        if (1 > dd) S[8 * B + 1] = S[8 * B + 7] = -INFINITY;
                        S[8 * B + 4] = S[8 * B + 5] = -INFINITY;
                        asm volatile("" ::: "memory");
                    };
                    auto blocks = [&](const int B) INL {
                        auto zero = [&](const int B0) INL {
#pragma unroll
                            for (int i = 4 * B0; i < 4 * B + 12; i++) P[i] = 0;
                            asm volatile("" ::: "memory");
                        };
                        auto block = [&](const int B0) INL { exp_part(t0, t1, 2 * B0, 2 * B0 + 2, false); asm volatile("" ::: "memory"); };
                        if (d < B) zero(B);
                        else {
                            block(B);
                            if (d < B + 1) zero(B + 1);
                            else {
                                block(B + 1);
                                if (d < B + 2) zero(B + 2); else block(B + 2);
                            }
                        }
                    };
                    if (d > 3) {
                        if (d < 6) { if (d == 4) tri(4); else tri(5); } else { if (d == 6) tri(6); else tri(7); }
                        exp_head(t0, t1, IC<5>{});
                        exp_part(t0, t1, 5, 10, false);
                        blocks(5);
                    } else {
                        if (d < 2) { if (d == 0) tri(0); else tri(1); } else { if (d == 2) tri(2); else tri(3); }
                        exp_head(t0, t1, IC<2>{});
#pragma unroll
                        for (int i = 16; i < 32; i++) P[i] = 0;
                        blocks(1);
                    }
                    fence_regs(P);
                };
                auto unsafe_tile = [&](float t0, float t1, bool fresh) INL -> bool {
                    const bool unsafe = !(t0 + t1 <= sum_max) |
                                        (fresh & ((slot_a & 0x180) == 0) & !(fminf(t0, t1) >= 8.6736174e-19f));
                    return __any_sync(0xffffffffu, unsafe);
                };
                auto redo_tile = [&](float& t0, float& t1, bool fresh) INL {
                    wg_wait<0>();
                    fence_regs(O);
                    if (rem == maskrem) mask_diag();
                    float a0, a1;
                    row_max(a0, a1);
                    if (!fresh) { a0 = fmaxf(a0, m0); a1 = fmaxf(a1, m1); }
                    const float c0 = fresh ? 1.f : ex2(m0 - a0), c1 = fresh ? 1.f : ex2(m1 - a1);
                    m0 = a0; m1 = a1; sum_max = -1.f;
                    l0 *= c0; l1 *= c1;
#pragma unroll
                    for (int j = 0; j < 16; j++) { O[j * 4] *= c0; O[j * 4 + 1] *= c0; O[j * 4 + 2] *= c1; O[j * 4 + 3] *= c1; }
                    exp_part(t0, t1, 0, 16, true);
                };
                auto finish = [&]() INL {
                    if (starts & 2) put_O();
                    named_sync(1 + w, TURN_THREADS);
                    TRACE_MARK(0, w, step + 1);
                    issue_PV(step, w == 0 ? 2 : 0);
                    close_job();
                    pv_done(step);
                    put_O();
                };
                auto open_job = [&]() INL {
                    ajob++; rem = (job & 15) + 1; maskrem = (job & 512) ? 0 : job & 15;
                };
                auto do_step = [&]() INL -> bool {
                    float t0, t1;
                    const bool fresh = starts & 1, pending = starts & 2;
                    rem--; step++;
                    named_sync(1 + w, TURN_THREADS);
                    TRACE_MARK(0, w, step);
                    issue_S();
                    if (__builtin_expect(pending || fresh, 0)) {
                        if (pending) put_O();
                        if (fresh) {
                            code_pad<PAD_R>();
                            close_job();
                            g0 = __ldcg(g_gate + (job & 15) * 128 + r0); g1 = __ldcg(g_gate + (job & 15) * 128 + r0 + 8);
                            l0 = 0.f; l1 = 0.f; m0 = 0.f; m1 = 0.f; sum_max = SUM_MAX;
                            if (step == 0) {
                                wg_fence();
                                wg_commit();
                                named_arrive(2 - w, TURN_THREADS);
                                goto issued;
                            }
                        }
                    }
                    issue_PV(step - 1, 2 - w);
                issued:
                    starts = (starts << 1 & 2) | (rem == 0);
                    TRACE_MARK(1, w, step);
                    wg_wait<1>();
                    fence_regs(S);
                    arrive_pair(kempty + (step & 1) * 8);
                    TRACE_MARK(2, w, step);
                    if (__builtin_expect(rem != maskrem, 1)) {
                        exp_plain(t0, t1);
                        if (__builtin_expect(!unsafe_tile(t0, t1, false) && starts == 0, 1)) {
                            l0 = t0; l1 = t1;
                            TRACE_MARK(3, w, step);
                            return true;
                        }
                    } else {
                        exp_diag(t0, t1);
                    }
                    if (unsafe_tile(t0, t1, fresh)) redo_tile(t0, t1, fresh);
                    l0 = t0; l1 = t1;
                    TRACE_MARK(3, w, step);
                    if (rem == 0) {
                        warp_arrive(qempty + (ajob & 1) * 8);
                        next_job();
                        if ((job >> 12) != T_A) return false;
                        open_job();
                    }
                    return true;
                };
                open_job();
#pragma unroll 1
                while (do_step()) {}
                finish();
            }
        }
        GTRACE(w);
        jb = uniform(jb); job = uniform(job); sph = uniform(sph); gph = uniform(gph);
        if (job < 0) break;
        }
    } else {
        reg_dec<40>();
        if (base & 1023) __trap();
        setup_wait();
        if (warp == 0) STRACE(6);
        volatile uint32_t* epoch_word = reinterpret_cast<volatile uint32_t*>(smem_raw + OFF_BAR + 532);
        uint32_t epoch1 = 0;
        if (warp > 0) {
        if (warp == 3) { epoch1 = uniform(ld_acquire(g_flags + F_DONE)) / NUM_SMS + 1; if (lane == 0) *epoch_word = epoch1; }
        {
            if (warp == 1 && elect_one()) {
#pragma unroll
                for (int i = 0; i < 7; i++) prefetch_map(&p.amap[0] + i);
            }
            __syncwarp();
            if (warp < 3) __nanosleep(jobs[0] < 256 ? GATE_DELAY_LONG_NS : GATE_DELAY_SHORT_NS);
            if (tid == TRACE_GATE) PTRACE(10);
            float* gate_vals = reinterpret_cast<float*>(smem_raw + OFF_BAR + 576);
            if (warp == 3) {
                if (blockIdx.x == 0) g_flags[F_SPLIT + lane] = g_flags[F_TICKET + lane] = 0;
                named_sync(5, 96);
                if (lane < 16 && blockIdx.x + lane * NUM_SMS < SEQ) g_gate[blockIdx.x + lane * NUM_SMS] = 1.f / (1.f + __expf(-gate_vals[lane]));
                if (tid == TRACE_GATE) PTRACE(9);
                __threadfence();
                __syncwarp();
                if (lane == 0) red_release(g_flags + F_GATE);
            } else {
                const uint32_t bar = gatefull + (warp - 1) * 16;
                auto fetch = [&](int r) INL {
                    if (lane == 0) mbar_expect_tx(bar + (r & 2) * 4, 4096);
                    __syncwarp();
                    if (lane < 2) asm volatile("cp.async.bulk.shared::cluster.global.mbarrier::complete_tx::bytes [%0], [%1], 2048, [%2];"
                                               ::"r"(stg + ((warp - 1) * 8 + r + lane) * 2048), "l"(p.xp + (size_t)min((int)blockIdx.x + ((warp - 1) * 8 + r + lane) * NUM_SMS, SEQ - 1) * DM), "r"(bar + (r & 2) * 4) : "memory");
                };
                fetch(0); fetch(2);
                uint32_t gw[16];
#pragma unroll
                for (int i = 0; i < 4; i++) {
                    const uint4 t = __ldg(reinterpret_cast<const uint4*>(p.gate_w) + i * 32 + lane);
                    gw[i * 4] = t.x; gw[i * 4 + 1] = t.y; gw[i * 4 + 2] = t.z; gw[i * 4 + 3] = t.w;
                }
#pragma unroll 1
                for (int r = 0; r < 8; r += 2) {
                    mbar_wait(bar + (r & 2) * 4, r >> 2);
                    if (r < 4) fetch(r + 4);
                    fence_regs(gw);
                    float acc0 = 0.f, acc1 = 0.f;
                    uint32_t ln;
                    asm volatile("mov.u32 %0, %%laneid;" : "=r"(ln));
#pragma unroll
                    for (int i = 0; i < 4; i++) {
                        const uint4* xr = reinterpret_cast<const uint4*>(smem_raw + OFF_STG + ((warp - 1) * 8 + r) * 2048) + i * 32 + ln;
                        const uint4 a = xr[0], c = xr[128];
                        const uint32_t av[4] = {a.x, a.y, a.z, a.w}, cv[4] = {c.x, c.y, c.z, c.w};
#pragma unroll
                        for (int e = 0; e < 4; e++) {
                            const float lo = __uint_as_float(gw[i * 4 + e] << 16), hi = __uint_as_float(gw[i * 4 + e] & 0xffff0000u);
                            acc0 = fmaf(__uint_as_float(av[e] << 16), lo, acc0);
                            acc1 = fmaf(__uint_as_float(cv[e] << 16), lo, acc1);
                            acc0 = fmaf(__uint_as_float(av[e] & 0xffff0000u), hi, acc0);
                            acc1 = fmaf(__uint_as_float(cv[e] & 0xffff0000u), hi, acc1);
                        }
                    }
                    float t = (lane < 16 ? acc0 : acc1) + __shfl_xor_sync(0xffffffffu, lane < 16 ? acc1 : acc0, 16);
#pragma unroll
                    for (int o = 8; o > 0; o >>= 1) t += __shfl_xor_sync(0xffffffffu, t, o);
                    if ((lane & 15) == 0) gate_vals[(warp - 1) * 8 + r + (lane >> 4)] = t;
                }
                uint32_t t2;
                asm volatile("mov.u32 %0, %%tid.x;" : "=r"(t2));
                warp_arrive2(sempty - 16 + (t2 >> 5) * 16, sempty - 8 + (t2 >> 5) * 16);
                named_arrive(5, 96);
                if (tid == TRACE_GATE) PTRACE(9);
            }
            if (tid == TRACE_GATE) PTRACE(8);
        }
        if (warp < 3) {
            if (elect_one()) {
                const int w = warp - 1;
                uint32_t qn = 0, un = 0;
                prefetch_map(&p.qkv_st); prefetch_map(&p.st_par);
                for (int jb = 0; jb < MAX_JOBS; jb++) {
                    const int job = jobs[jb];
                    if (job < 0) break;
                    const int type = job >> 12, pl = type == T_O ? o_state(otile, 0) >> 1 : job & 0xFFF;
                    const CUtensorMap* map = &p.qkv_st;
                    int nq = 4, mt, ob0, ob1, flag, flag2 = -1;
                    bool par = false;
                    if (type <= T_O) {
                        const int n = pl >> 3;
                        mt = (pl & 7) * 2 + rank;
                        if (type == T_O)  {
                            map = &p.out_st; ob0 = (n & 3) * 4; ob1 = ob0 + 2; flag = -1;
                            for (uint32_t tries = 0; (int32_t)(ld_acquire(g_flags + F_OUT + pl * 2 + rank) - *epoch_word) < 0; tries++) {
                                __nanosleep(300);
                                if (tries > (1u << 22)) __trap();
                            }
                            fence_async_global();
                        }
                        else if (n < 16)  { ob0 = n * 4; ob1 = ob0 + 2; flag = F_Q + n * 32 + mt; flag2 = flag + 16; }
                        else if (n < 24)  {
                            mbar_wait(hout + w * 8, un++ & 1);
                            nq = ob0 = ob1 = 0; flag = F_H + mt * 8 + (n & 7);
                        } else if (n < 32) {
                            par = true; ob0 = 192 + (n & 7) * 2; ob1 = unit_head(n & 7) * 2;
                            flag = F_CTX + mt * 40 + 32 + (n & 7); flag2 = F_Q + ob1 * 8 + mt;
                        } else            { ob0 = n * 2; ob1 = ob0 + 64; flag = F_KV + (n - 32) * 16 + mt; }
                    } else {
                        nq = 2; mt = pl & 15; ob0 = ob1 = ((pl >> 4) & 31) * 2; flag = F_CTX + mt * 40 + ((pl >> 4) & 31);
                    }
                    for (int q = 0; q < nq; q++, qn++) {
                        const uint32_t slot = w * 2 + (qn & 1);
                        const int blk = (q < 2 ? ob0 : ob1) + (q & 1);
                        if (type == T_O && q == 2) {
                            mbar_wait(tfull + w * 8, 0);
                            fence_async_smem();
                            tma_reduce_add_3d(map, base + w * 8192, 0, mt * 128 + w * 64, ob1);
                            tma_reduce_add_3d(map, base + G_STAGE + w * 8192, 0, mt * 128 + w * 64, ob1 + 1);
                            bulk_commit();
                            break;
                        }
                        mbar_wait(sfull + slot * 8, (qn >> 1) & 1);
                        fence_async_smem();
                        if (type == T_O) {
                            tma_reduce_add_3d(map, stg + slot * 8192, 0, mt * 128 + w * 64, blk);
                        } else if (par) {
                            tma_store_par(&p.st_par, stg + slot * 8192, mt * 64, w, blk);
                        } else {
                            tma_store_3d(map, stg + slot * 8192, 0, mt * 128 + w * 64, blk, POL_STREAM);
                        }
                        bulk_commit();
                        if (type == T_O) continue;
                        if (!(q & 1)) continue;
                        bulk_wait_read<1>();
                        mbar_arrive(sempty + (slot ^ 1) * 8);
                        bulk_wait_read<0>();
                        mbar_arrive(sempty + slot * 8);
                    }
                    bulk_wait<0>();
                    END_MARK(jb);
                    if (flag >= 0) {
                        asm volatile("fence.release.gpu;" ::: "memory");
                        red_relaxed(g_flags + flag);
                        if (flag2 >= 0) red_relaxed(g_flags + flag2);
                    }
                }
            }
        } else {
            int jb = 0;
            for (int un = 0; (jobs[jb] >> 12) == T_P; jb++) {
                const int n = jobs[jb] >> 3, mt = (jobs[jb] & 7) * 2 + rank;
                if ((n >> 3) != 3) continue;
                wait_flags<200>(lane == 31 || (lane == 0 && mt > 0), lane == 31 ? F_GATE : F_H + max(mt - 1, 0) * 8 + (n & 7),
                                epoch1 * (lane == 31 ? GATE_COUNT : 2));
                if (lane == 0) mbar_arrive(lready + un * 8);
                un++;
            }
            if ((jobs[jb] >> 12) != T_A) {
                wait_flags<200>(lane == 0, F_GATE, epoch1 * GATE_COUNT);
                if (lane == 0) { mbar_arrive(aready); red_relaxed(g_flags + F_DONE); }
            } else {
                const int jh = jobs[jb] >> 4 & 31, jq = jobs[jb] & 15;
                wait_flags<100>(lane <= jq || lane >= 30, lane == 31 ? F_GATE : (lane == 30 ? F_Q + jh * 16 + jq : F_KV + jh * 16 + (lane & 15)),
                                epoch1 * (lane == 31 ? GATE_COUNT : 2));
                if (lane == 0) { mbar_arrive(aready); red_relaxed(g_flags + F_DONE); }
            int left = 0, nxt = jobs[jb];
            uint32_t ajob = 0;
#pragma unroll 1
            for (uint32_t astep = 0;; astep++) {
                if (left == 0) {
                    if ((nxt >> 12) != T_A) break;
                    left = (nxt & 15) + 1;
                    nxt = jobs[++jb];
                    mbar_wait(qfull + (ajob & 1) * 8, (ajob >> 1) & 1);
                    ajob++;
                }
                left--;
                mbar_wait(kfull + (astep & 1) * 8, (astep >> 1) & 1);
                named_sync(1, TURN_THREADS);
                named_sync(2, TURN_THREADS);
            }
            named_sync(1, TURN_THREADS);
            named_sync(2, TURN_THREADS);
            }
            if (jobs[jb] == (T_O << 12)) {
                mbar_wait(gatefull, 0);
                const int tile = o_state(otile, 0) >> 1;
                uint4* dst = reinterpret_cast<uint4*>(p.out) + ((tile & 7) * 256 + rank * 128) * (DM / 8) + (tile >> 3) * 32 + lane;
#pragma unroll 4
                for (int r = 0; r < 128; r++) {
                    dst[r * (DM / 8)] = make_uint4(0, 0, 0, 0);
                    if ((r & 3) == 3) __nanosleep(CLEAR_GAP_NS);
                }
                __threadfence();
                fence_async_global();
                __syncwarp();
                if (lane == 0) red_release(g_flags + F_OUT + tile * 2 + rank);
            }
        }
        } else {
            uint32_t gph = 1;
            int vrow = 0, vblk = 0;
            bool vsolo = false;
            auto load_kv = [&](uint32_t dst, uint32_t bar, int row, int blk, bool solo) INL {
                load_operand(dst, bar, &p.qkv_ld, &p.qkv_half, row, blk, rank, solo, POL_NORMAL);
            };
            auto load_v = [&](uint32_t t) INL {
                if (t == 0) mbar_wait(gempty + 24, gph);
                mbar_wait(vempty + (t & 1) * 8, ((t >> 1) & 1) ^ 1);
                load_kv(base + ((t & 1) ? OFF_V1 : OFF_V0), vfull + (t & 1) * 8, vrow, vblk, vsolo);
            };
            int jb = __ffs(__ballot_sync(0xffffffffu, lane <= MAX_JOBS && (jobs[min(lane, MAX_JOBS)] >> 12) != T_P)) - 1;
            int cur = uniform(jobs[jb]);
            auto announce = [&](uint32_t word, uint32_t v) INL {
                asm volatile("{\n.reg .pred p;\nsetp.lt.u32 p, %2, 2;\n@p red.relaxed.cluster.shared::cluster.max.u32 [%0], %1;\n}"
                             ::"r"(mapa(word, lane & 1)), "r"(v), "r"(lane) : "memory");
                __syncwarp();
            };
            uint32_t ticket = 0;
            auto draw_ticket = [&](int ojob) INL {
                asm volatile("{\n.reg .pred p;\nsetp.ne.u32 p, %2, 0;\n@p atom.relaxed.gpu.global.inc.u32 %0, [%1], 0x7fffffff;\n}"
                             : "+r"(ticket) : "l"(g_flags + F_TICKET + (ojob >> 5 & 1)), "r"((uint32_t)(rank == 0 && lane == 0)) : "memory");
                __syncwarp();
            };
            int pl = 0;
            uint32_t seen_a = 0, seen_b = 0;
            auto ask_ctx = [&]() INL {
                const uint32_t* f = g_flags + F_CTX + ((pl & 7) * 2 + rank) * 40;
                seen_a = ld_relaxed(f + lane); seen_b = ld_relaxed(f + 32 + (lane & 7));
            };
            auto open_tile = [&](int ojob) INL {
                if (rank == 0) {
                    const uint32_t t = uniform(ticket);
                    announce(otile, 2 * ((ojob & 32) ? 31 - t : t) + 1);
                }
                pl = (ojob & 32) | uniform(o_state(otile, 0) >> 1);
                ask_ctx();
            };
            const uint16_t* recs = reinterpret_cast<const uint16_t*>(rounds);
            uint32_t rec = uniform(recs[0]), nrec = uniform(recs[1]);
            STRACE(7);
            int st0 = SOLO_STAGES;
#pragma unroll 1
            for (int r = 2; rec != 0xFFFF; r++) {
                const uint32_t nnrec = recs[r];
                load_round(rec, st0, gph);
                if (r == 2) STRACE(8);
                gph ^= 1;
                st0 = 0;
                rec = nrec; nrec = uniform(nnrec);
                if (nrec == 0xFFFF || (rec & 8192)) {
                    if (nrec != 0xFFFF) {
                        prefetch_map(&p.qkv_ld); prefetch_map(&p.qkv_half);
                        if ((cur >> 12) == T_O) { prefetch_map(&p.wo_a); prefetch_map(&p.wo_b); prefetch_map(&p.out_st); }
                    } else if ((cur >> 12) == T_O) {
                        if (rec != 0xFFFF) {
                            mbar_wait(aready, 0);
                            draw_ticket(cur);
                        } else {
                            open_tile(cur);
                        }
                    }
                }
            }
            int nxt = cur;
            uint32_t astep = 0;
            if ((cur >> 12) == T_A) {
            {
                const int jh = cur >> 4 & 31, jq = cur & 15, j0 = (cur & 512) ? 0 : jq;
                mbar_wait(aready, 0);
                fence_async_global();
                mbar_wait(gempty, gph);
                load_operand(base + OFF_Q0, qfull, &p.qkv_ld, &p.qkv_ld, jq * 128, jh * 2, 0, true, POL_STREAM);
                PTRACE(17);
                mbar_wait(gempty + 8, gph);
                load_kv(base + OFF_K0, kfull, j0 * 128, 64 + jh * 2, j0 == jq && (jq & 1));
                PTRACE(16);
            }
            epoch1 = *epoch_word;
            jb++;
            nxt = uniform(jobs[jb]);
            int i = 0;
            uint32_t ajob = 1;
            bool q_issued = false;
#pragma unroll 1
            while (true) {
                const int qt = cur & 15;
                const bool last = i == qt;
                const int j = (cur & 512) ? i : qt - i, blk = (cur >> 4 & 31) * 2;
                const bool solo = j == qt && (qt & 1);
                {
                    const uint32_t sl = astep & 1;
                    if (astep == 0) {
                        mbar_wait(gempty + 16, gph);
                    } else {
                        mbar_wait(kempty + sl * 8, ((astep >> 1) & 1) ^ 1);
                        load_kv(base + (sl ? OFF_K1 : OFF_K0), kfull + sl * 8, j * 128, 64 + blk, solo);
                        if (astep == 1) PTRACE(14);
                        load_v(astep - 1);
                        if (astep == 1) PTRACE(15);
                    }
                }
                vrow = j * 128; vblk = 128 + blk; vsolo = solo;
                astep++;
                if ((nxt >> 12) != T_A) {
                    if (last) break;
                } else if (!q_issued && (last || i == 2 || (i > 2 && i >= qt - 2))) {
                    const int jh = nxt >> 4 & 31, jq = nxt & 15;
                    q_issued = wait_flags(lane <= jq || lane >= 30, lane == 31 ? F_GATE : (lane == 30 ? F_Q + jh * 16 + jq : F_KV + jh * 16 + (lane & 15)),
                                          epoch1 * (lane == 31 ? GATE_COUNT : 2), last);
                    if (q_issued) {
                        mbar_wait(qempty + (ajob & 1) * 8, ((ajob >> 1) & 1) ^ 1);
                        load_operand(base + ((ajob & 1) ? OFF_Q1 : OFF_Q0), qfull + (ajob & 1) * 8, &p.qkv_ld, &p.qkv_ld, jq * 128, jh * 2, 0, true, POL_STREAM);
                    }
                }
                i++;
                if (last) {
                    cur = nxt; jb++; nxt = uniform(jobs[jb]); i = 0; ajob++; q_issued = false;
                    if ((nxt >> 12) == T_O) { prefetch_map(&p.wo_a); prefetch_map(&p.wo_b); prefetch_map(&p.out_st); }
                }
            }
            if (nxt >= 0) draw_ticket(nxt);
            load_v(astep - 1);
            if (nxt >= 0) open_tile(nxt);
            }
            int nks = 0;
            if (nxt >= 0) {
                epoch1 = *epoch_word;
                const int m0 = (pl & 7) * 256 + rank * 128, nb = (pl >> 3 & 3) * 4 + rank * 2, part = pl >> 5 & 1;
                uint32_t ready_a = 0, ready_b = 0;
                uint32_t claim_even = 0, claim_odd = 0;
                const int head = o_head(pl), tail = o_tail(pl);
                int lim = head;
                bool known = false;
#pragma unroll 1
                for (int ks = 0;; ks++) {
                    const int st = ks & 3;
                    if (rank == 0) {
                        auto exchange = [&](uint32_t& claim) INL {
                            if (ks + 1 >= head) {
                                known = (uint32_t)uniform(claim) >= O_FLEX;
                                if (!known) lim = ks + 2;
                                announce(olim, known ? 2 * (lim + tail) + 1 : 2 * lim);
                            }
                            asm volatile("{\n.reg .pred p;\nsetp.ne.u32 p, %2, 0;\n@p atom.relaxed.gpu.global.inc.u32 %0, [%1], 0x7fffffff;\n}"
                                         : "+r"(claim) : "l"(g_flags + F_SPLIT + (pl & 31)), "r"((uint32_t)(!known && lane == 0)) : "memory");
                            __syncwarp();
                        };
                        if (!known && ks + 3 >= head) { if (ks & 1) exchange(claim_odd); else exchange(claim_even); }
                    } else if (!known && ks >= lim) {
                        const uint32_t v = uniform(o_state(olim, ks));
                        known = v & 1;
                        lim = (v >> 1) - (known ? tail : 0);
                    }
                    if (ks >= lim + tail) { nks = ks; break; }
                    if (ks == CLEAR_KS && !part) warp_arrive(gatefull);
                    int acol;
                    if (ks >= lim) acol = (part ? 64 - O_T1 : 200) + ks - lim;
                    else if (part) acol = ks < O_H1 ? O_F0 + ks : O_F0 + 2 * O_H1 + O_FLEX - 1 - ks;
                    else acol = ks < 8 ? 192 + ks : (ks < O_H0 ? ks - 8 : ks - 8 + O_H1);
                    for (uint32_t tries = 0; !(((acol < 192 ? ready_a : ready_b) >> (acol >> 1 & 31)) & 1); tries++) {
                        if (ks | tries) ask_ctx();
                        ready_a = __ballot_sync(0xffffffffu, (int32_t)(seen_a - epoch1 * 2) >= 0);
                        ready_b = __ballot_sync(0xffffffffu, (int32_t)(seen_b - epoch1 * 2) >= 0);
                        fence_acquire();
                        trap_if(tries > (1u << 22));
                    }
                    {
                        const uint32_t sa = base + st * G_STAGE;
                        if (ks < 4 && astep) mbar_wait((ks < 2 ? kempty : vempty) + ((astep - 1) & 1) * 8, ((astep - 1) >> 1) & 1);
                        else mbar_wait(gempty + st * 8, gph);
                        load_kstep(sa, sa + 16384 + rank * 16384, gfull + st * 8, G_STAGE, acol >= 192 ? &p.wo_b : &p.wo_a, acol & 63, nb,
                                   &p.qkv_half, m0, acol, 1);
                    }
                    if (st == 3) gph ^= 1;
                }
            }
            if (lane == 0) {
                if (nxt >= 0) for (int s = 0; s < 4; s++) mbar_wait(gempty + s * 8, gph ^ (s < (nks & 3)));
                else for (uint32_t t = astep; t < astep + 2; t++) {
                    mbar_wait(kempty + (t & 1) * 8, ((t >> 1) & 1) ^ 1);
                    mbar_wait(vempty + (t & 1) * 8, ((t >> 1) & 1) ^ 1);
                }
            }
        }
    }
}

typedef CUresult (*EncodeFn)(CUtensorMap*, CUtensorMapDataType, cuuint32_t, void*, const cuuint64_t*, const cuuint64_t*,
                             const cuuint32_t*, const cuuint32_t*, CUtensorMapInterleave, CUtensorMapSwizzle,
                             CUtensorMapL2promotion, CUtensorMapFloatOOBfill);

void make_map3(EncodeFn enc, CUtensorMap* m, const void* ptr, int rows, int cols, int box_rows, int box_blks, bool blocked = false) {
    cuuint64_t dims[3] = {64, (cuuint64_t)rows, (cuuint64_t)(cols / 64)};
    cuuint64_t strides[2] = {blocked ? 128 : (cuuint64_t)cols * 2, blocked ? (cuuint64_t)rows * 128 : 128};
    cuuint32_t box[3] = {64, (cuuint32_t)box_rows, (cuuint32_t)box_blks};
    cuuint32_t es[3] = {1, 1, 1};
    enc(m, CU_TENSOR_MAP_DATA_TYPE_BFLOAT16, 3, const_cast<void*>(ptr), dims, strides, box, es, CU_TENSOR_MAP_INTERLEAVE_NONE,
        CU_TENSOR_MAP_SWIZZLE_128B, CU_TENSOR_MAP_L2_PROMOTION_L2_256B, CU_TENSOR_MAP_FLOAT_OOB_FILL_NONE);
}

Params h_params;

const int16_t k_jobs[NUM_SMS][MAX_JOBS] = {
    {339,153,217,8890,8339,8802,8311,9042,8405,9008,8551,9134,8677,4128,-1,-1,-1,-1,-1,-1,-1,-1,-1,-1},
    {339,153,217,8891,8338,8803,8310,9043,8404,9009,8550,9135,8676,4128,-1,-1,-1,-1,-1,-1,-1,-1,-1,-1},
    {40,0,307,8888,8289,8720,8259,8854,8539,8898,8627,8998,8655,4128,-1,-1,-1,-1,-1,-1,-1,-1,-1,-1},
    {40,0,307,8889,8288,8721,8258,8855,8538,8899,8626,8999,8654,4128,-1,-1,-1,-1,-1,-1,-1,-1,-1,-1},
    {10,157,221,8706,8269,8820,8457,9006,8687,4128,-1,-1,-1,-1,-1,-1,-1,-1,-1,-1,-1,-1,-1,-1},
    {10,157,221,8707,8268,8821,8456,9007,8686,4128,-1,-1,-1,-1,-1,-1,-1,-1,-1,-1,-1,-1,-1,-1},
    {132,196,296,8730,8333,8940,8503,9082,8697,4128,-1,-1,-1,-1,-1,-1,-1,-1,-1,-1,-1,-1,-1,-1},
    {132,196,296,8731,8332,8941,8502,9083,8696,4128,-1,-1,-1,-1,-1,-1,-1,-1,-1,-1,-1,-1,-1,-1},
    {128,192,8758,8199,8774,8313,9026,8415,9130,8663,4128,-1,-1,-1,-1,-1,-1,-1,-1,-1,-1,-1,-1,-1},
    {128,192,8759,8198,8775,8312,9027,8414,9131,8662,4128,-1,-1,-1,-1,-1,-1,-1,-1,-1,-1,-1,-1,-1},
    {133,197,8742,8369,8704,8285,8768,8543,9022,8601,4128,-1,-1,-1,-1,-1,-1,-1,-1,-1,-1,-1,-1,-1},
    {133,197,8743,8368,8705,8284,8769,8542,9023,8600,4128,-1,-1,-1,-1,-1,-1,-1,-1,-1,-1,-1,-1,-1},
    {131,195,38,8708,8265,8932,8461,8896,8631,9076,8585,4128,-1,-1,-1,-1,-1,-1,-1,-1,-1,-1,-1,-1},
    {131,195,38,8709,8264,8933,8460,8897,8630,9077,8584,4128,-1,-1,-1,-1,-1,-1,-1,-1,-1,-1,-1,-1},
    {137,201,8750,8331,8816,8533,8912,8411,9078,8671,4128,-1,-1,-1,-1,-1,-1,-1,-1,-1,-1,-1,-1,-1},
    {137,201,8751,8330,8817,8532,8913,8410,9079,8670,4128,-1,-1,-1,-1,-1,-1,-1,-1,-1,-1,-1,-1,-1},
    {43,264,440,8744,8201,8858,8417,8954,8483,9016,8649,9152,8691,4128,-1,-1,-1,-1,-1,-1,-1,-1,-1,-1},
    {43,264,440,8745,8200,8859,8416,8955,8482,9017,8648,9153,8690,4128,-1,-1,-1,-1,-1,-1,-1,-1,-1,-1},
    {151,215,8876,8299,8964,8445,9146,8703,4128,-1,-1,-1,-1,-1,-1,-1,-1,-1,-1,-1,-1,-1,-1,-1},
    {151,215,8877,8298,8965,8444,9147,8702,4128,-1,-1,-1,-1,-1,-1,-1,-1,-1,-1,-1,-1,-1,-1,-1},
    {470,5,159,223,8772,8281,8936,8407,9066,8651,4128,-1,-1,-1,-1,-1,-1,-1,-1,-1,-1,-1,-1,-1},
    {470,5,159,223,8773,8280,8937,8406,9067,8650,4128,-1,-1,-1,-1,-1,-1,-1,-1,-1,-1,-1,-1,-1},
    {136,200,444,8760,8275,8848,8477,9040,8525,9148,8681,4128,-1,-1,-1,-1,-1,-1,-1,-1,-1,-1,-1,-1},
    {136,200,444,8761,8274,8849,8476,9041,8524,9149,8680,4128,-1,-1,-1,-1,-1,-1,-1,-1,-1,-1,-1,-1},
    {46,510,462,310,8764,8293,8862,8439,9064,8653,4128,-1,-1,-1,-1,-1,-1,-1,-1,-1,-1,-1,-1,-1},
    {46,510,462,310,8765,8292,8863,8438,9065,8652,4128,-1,-1,-1,-1,-1,-1,-1,-1,-1,-1,-1,-1,-1},
    {145,209,8894,8335,8942,8485,9098,8695,4128,-1,-1,-1,-1,-1,-1,-1,-1,-1,-1,-1,-1,-1,-1,-1},
    {145,209,8895,8334,8943,8484,9099,8694,4128,-1,-1,-1,-1,-1,-1,-1,-1,-1,-1,-1,-1,-1,-1,-1},
    {140,204,8878,8329,8934,8441,9070,8685,4128,-1,-1,-1,-1,-1,-1,-1,-1,-1,-1,-1,-1,-1,-1,-1},
    {140,204,8879,8328,8935,8440,9071,8684,4128,-1,-1,-1,-1,-1,-1,-1,-1,-1,-1,-1,-1,-1,-1,-1},
    {146,210,504,8884,8301,8966,8527,9128,8603,4128,-1,-1,-1,-1,-1,-1,-1,-1,-1,-1,-1,-1,-1,-1},
    {146,210,504,8885,8300,8967,8526,9129,8602,4128,-1,-1,-1,-1,-1,-1,-1,-1,-1,-1,-1,-1,-1,-1},
    {14,6,8868,8245,8806,8267,8938,8547,9000,8611,9108,8643,4128,-1,-1,-1,-1,-1,-1,-1,-1,-1,-1,-1},
    {14,6,8869,8244,8807,8266,8939,8546,9001,8610,9109,8642,4128,-1,-1,-1,-1,-1,-1,-1,-1,-1,-1,-1},
    {144,208,8748,8211,8836,8463,9004,8591,4128,-1,-1,-1,-1,-1,-1,-1,-1,-1,-1,-1,-1,-1,-1,-1},
    {144,208,8749,8210,8837,8462,9005,8590,4128,-1,-1,-1,-1,-1,-1,-1,-1,-1,-1,-1,-1,-1,-1,-1},
    {12,4,8740,8243,8724,8287,8930,8435,8900,8517,9086,8659,4128,-1,-1,-1,-1,-1,-1,-1,-1,-1,-1,-1},
    {12,4,8741,8242,8725,8286,8931,8434,8901,8516,9087,8658,4128,-1,-1,-1,-1,-1,-1,-1,-1,-1,-1,-1},
    {143,207,8866,8353,8752,8205,8830,8409,9056,8561,9140,8581,9104,8679,4128,-1,-1,-1,-1,-1,-1,-1,-1,-1},
    {143,207,8867,8352,8753,8204,8831,8408,9057,8560,9141,8580,9105,8678,4128,-1,-1,-1,-1,-1,-1,-1,-1,-1},
    {147,211,8872,8297,8834,8459,9030,8437,9100,8665,4128,-1,-1,-1,-1,-1,-1,-1,-1,-1,-1,-1,-1,-1},
    {147,211,8873,8296,8835,8458,9031,8436,9101,8664,4128,-1,-1,-1,-1,-1,-1,-1,-1,-1,-1,-1,-1,-1},
    {41,1,8766,8327,8828,8399,9126,8667,4128,-1,-1,-1,-1,-1,-1,-1,-1,-1,-1,-1,-1,-1,-1,-1},
    {41,1,8767,8326,8829,8398,9127,8666,4128,-1,-1,-1,-1,-1,-1,-1,-1,-1,-1,-1,-1,-1,-1,-1},
    {150,214,8882,8223,8832,8473,8980,8413,9094,8669,4128,-1,-1,-1,-1,-1,-1,-1,-1,-1,-1,-1,-1,-1},
    {150,214,8883,8222,8833,8472,8981,8412,9095,8668,4128,-1,-1,-1,-1,-1,-1,-1,-1,-1,-1,-1,-1,-1},
    {141,205,33,8726,8341,8976,8479,9024,8449,9136,8501,9144,8683,4128,-1,-1,-1,-1,-1,-1,-1,-1,-1,-1},
    {141,205,33,8727,8340,8977,8478,9025,8448,9137,8500,9145,8682,4128,-1,-1,-1,-1,-1,-1,-1,-1,-1,-1},
    {277,405,152,216,8718,8475,8902,8403,9150,8661,4128,-1,-1,-1,-1,-1,-1,-1,-1,-1,-1,-1,-1,-1},
    {277,405,152,216,8719,8474,8903,8402,9151,8660,4128,-1,-1,-1,-1,-1,-1,-1,-1,-1,-1,-1,-1,-1},
    {139,203,8886,8203,8856,8433,9032,8393,9080,8599,4128,-1,-1,-1,-1,-1,-1,-1,-1,-1,-1,-1,-1,-1},
    {139,203,8887,8202,8857,8432,9033,8392,9081,8598,4128,-1,-1,-1,-1,-1,-1,-1,-1,-1,-1,-1,-1,-1},
    {149,213,8746,8303,8982,8397,9084,8645,4128,-1,-1,-1,-1,-1,-1,-1,-1,-1,-1,-1,-1,-1,-1,-1},
    {149,213,8747,8302,8983,8396,9085,8644,4128,-1,-1,-1,-1,-1,-1,-1,-1,-1,-1,-1,-1,-1,-1,-1},
    {138,202,8870,8221,8860,8395,9060,8607,4128,-1,-1,-1,-1,-1,-1,-1,-1,-1,-1,-1,-1,-1,-1,-1},
    {138,202,8871,8220,8861,8394,9061,8606,4128,-1,-1,-1,-1,-1,-1,-1,-1,-1,-1,-1,-1,-1,-1,-1},
    {134,198,8738,8225,8728,8283,8962,8541,8992,8499,9074,8609,9124,8595,9184,8693,4128,-1,-1,-1,-1,-1,-1,-1},
    {134,198,8739,8224,8729,8282,8963,8540,8993,8498,9075,8608,9125,8594,9185,8692,4128,-1,-1,-1,-1,-1,-1,-1},
    {142,206,8874,8271,8818,8447,9068,8647,4128,-1,-1,-1,-1,-1,-1,-1,-1,-1,-1,-1,-1,-1,-1,-1},
    {142,206,8875,8270,8819,8446,9069,8646,4128,-1,-1,-1,-1,-1,-1,-1,-1,-1,-1,-1,-1,-1,-1,-1},
    {47,498,506,306,8892,8277,8784,8467,9048,8535,9020,8579,9088,8657,9186,8689,4128,-1,-1,-1,-1,-1,-1,-1},
    {47,498,506,306,8893,8276,8785,8466,9049,8534,9021,8578,9089,8656,9187,8688,4128,-1,-1,-1,-1,-1,-1,-1},
    {148,212,8762,8279,8826,8523,9002,8605,4128,-1,-1,-1,-1,-1,-1,-1,-1,-1,-1,-1,-1,-1,-1,-1},
    {148,212,8763,8278,8827,8522,9003,8604,4128,-1,-1,-1,-1,-1,-1,-1,-1,-1,-1,-1,-1,-1,-1,-1},
    {276,404,268,500,450,490,374,390,430,380,356,412,168,232,9018,8701,-1,-1,-1,-1,-1,-1,-1,-1},
    {276,404,268,500,450,490,374,390,430,380,356,412,168,232,9019,8700,-1,-1,-1,-1,-1,-1,-1,-1},
    {11,403,459,507,329,393,369,377,417,361,433,167,231,9132,8699,-1,-1,-1,-1,-1,-1,-1,-1,-1},
    {11,403,459,507,329,393,369,377,417,361,433,167,231,9133,8698,-1,-1,-1,-1,-1,-1,-1,-1,-1},
    {350,486,502,262,302,334,318,87,52,100,179,243,4096,-1,-1,-1,-1,-1,-1,-1,-1,-1,-1,-1},
    {350,486,502,262,302,334,318,87,52,100,179,243,4096,-1,-1,-1,-1,-1,-1,-1,-1,-1,-1,-1},
    {340,158,222,492,60,108,76,172,236,4096,-1,-1,-1,-1,-1,-1,-1,-1,-1,-1,-1,-1,-1,-1},
    {340,158,222,492,60,108,76,172,236,4096,-1,-1,-1,-1,-1,-1,-1,-1,-1,-1,-1,-1,-1,-1},
    {42,3,35,59,107,360,408,181,245,4096,-1,-1,-1,-1,-1,-1,-1,-1,-1,-1,-1,-1,-1,-1},
    {42,3,35,59,107,360,408,181,245,4096,-1,-1,-1,-1,-1,-1,-1,-1,-1,-1,-1,-1,-1,-1},
    {45,156,220,396,85,109,93,180,244,4096,-1,-1,-1,-1,-1,-1,-1,-1,-1,-1,-1,-1,-1,-1},
    {45,156,220,396,85,109,93,180,244,4096,-1,-1,-1,-1,-1,-1,-1,-1,-1,-1,-1,-1,-1,-1},
    {466,482,266,258,37,69,53,77,183,247,4096,-1,-1,-1,-1,-1,-1,-1,-1,-1,-1,-1,-1,-1},
    {466,482,266,258,37,69,53,77,183,247,4096,-1,-1,-1,-1,-1,-1,-1,-1,-1,-1,-1,-1,-1},
    {471,407,463,442,290,322,314,386,478,382,366,414,182,246,4096,-1,-1,-1,-1,-1,-1,-1,-1,-1},
    {471,407,463,442,290,322,314,386,478,382,366,414,182,246,4096,-1,-1,-1,-1,-1,-1,-1,-1,-1},
    {469,349,485,501,445,333,317,373,477,423,439,415,173,237,4096,-1,-1,-1,-1,-1,-1,-1,-1,-1},
    {469,349,485,501,445,333,317,373,477,423,439,415,173,237,4096,-1,-1,-1,-1,-1,-1,-1,-1,-1},
    {8,269,309,453,449,489,385,425,422,358,92,188,252,4096,-1,-1,-1,-1,-1,-1,-1,-1,-1,-1},
    {8,269,309,453,449,489,385,425,422,358,92,188,252,4096,-1,-1,-1,-1,-1,-1,-1,-1,-1,-1},
    {343,287,487,263,303,455,495,391,51,91,160,224,4096,-1,-1,-1,-1,-1,-1,-1,-1,-1,-1,-1},
    {343,287,487,263,303,455,495,391,51,91,160,224,4096,-1,-1,-1,-1,-1,-1,-1,-1,-1,-1,-1},
    {464,272,480,456,288,488,392,61,379,363,435,176,240,4096,-1,-1,-1,-1,-1,-1,-1,-1,-1,-1},
    {464,272,480,456,288,488,392,61,379,363,435,176,240,4096,-1,-1,-1,-1,-1,-1,-1,-1,-1,-1},
    {336,280,400,256,448,320,312,384,424,416,352,432,472,171,235,4096,-1,-1,-1,-1,-1,-1,-1,-1},
    {336,280,400,256,448,320,312,384,424,416,352,432,472,171,235,4096,-1,-1,-1,-1,-1,-1,-1,-1},
    {337,273,265,155,219,368,376,479,359,102,184,248,4096,-1,-1,-1,-1,-1,-1,-1,-1,-1,-1,-1},
    {337,273,265,155,219,368,376,479,359,102,184,248,4096,-1,-1,-1,-1,-1,-1,-1,-1,-1,-1,-1},
    {468,284,508,260,300,324,332,388,104,72,174,238,4096,-1,-1,-1,-1,-1,-1,-1,-1,-1,-1,-1},
    {468,284,508,260,300,324,332,388,104,72,174,238,4096,-1,-1,-1,-1,-1,-1,-1,-1,-1,-1,-1},
    {338,281,2,34,66,110,78,175,239,4096,-1,-1,-1,-1,-1,-1,-1,-1,-1,-1,-1,-1,-1,-1},
    {338,281,2,34,66,110,78,175,239,4096,-1,-1,-1,-1,-1,-1,-1,-1,-1,-1,-1,-1,-1,-1},
    {130,194,39,63,55,95,103,97,4096,-1,-1,-1,-1,-1,-1,-1,-1,-1,-1,-1,-1,-1,-1,-1},
    {130,194,39,63,55,95,103,97,4096,-1,-1,-1,-1,-1,-1,-1,-1,-1,-1,-1,-1,-1,-1,-1},
    {135,199,454,494,67,83,365,413,191,255,4096,-1,-1,-1,-1,-1,-1,-1,-1,-1,-1,-1,-1,-1},
    {135,199,454,494,67,83,365,413,191,255,4096,-1,-1,-1,-1,-1,-1,-1,-1,-1,-1,-1,-1,-1},
    {348,484,460,308,292,452,316,372,428,420,476,101,187,251,4096,-1,-1,-1,-1,-1,-1,-1,-1,-1},
    {348,484,460,308,292,452,316,372,428,420,476,101,187,251,4096,-1,-1,-1,-1,-1,-1,-1,-1,-1},
    {13,154,218,58,106,74,178,242,4096,-1,-1,-1,-1,-1,-1,-1,-1,-1,-1,-1,-1,-1,-1,-1},
    {13,154,218,58,106,74,178,242,4096,-1,-1,-1,-1,-1,-1,-1,-1,-1,-1,-1,-1,-1,-1,-1},
    {465,481,457,505,289,328,71,111,79,166,230,4096,-1,-1,-1,-1,-1,-1,-1,-1,-1,-1,-1,-1},
    {465,481,457,505,289,328,71,111,79,166,230,4096,-1,-1,-1,-1,-1,-1,-1,-1,-1,-1,-1,-1},
    {44,270,446,294,326,65,81,89,161,225,4096,-1,-1,-1,-1,-1,-1,-1,-1,-1,-1,-1,-1,-1},
    {44,270,446,294,326,65,81,89,161,225,4096,-1,-1,-1,-1,-1,-1,-1,-1,-1,-1,-1,-1,-1},
    {9,511,503,295,327,375,399,381,437,353,409,473,169,233,4096,-1,-1,-1,-1,-1,-1,-1,-1,-1},
    {9,511,503,295,327,375,399,381,437,353,409,473,169,233,4096,-1,-1,-1,-1,-1,-1,-1,-1,-1},
    {347,283,483,259,291,491,331,371,431,383,367,99,186,250,4096,-1,-1,-1,-1,-1,-1,-1,-1,-1},
    {347,283,483,259,291,491,331,371,431,383,367,99,186,250,4096,-1,-1,-1,-1,-1,-1,-1,-1,-1},
    {274,282,458,261,293,493,397,389,429,421,357,75,189,253,4096,-1,-1,-1,-1,-1,-1,-1,-1,-1},
    {274,282,458,261,293,493,397,389,429,421,357,75,189,253,4096,-1,-1,-1,-1,-1,-1,-1,-1,-1},
    {278,286,406,32,64,56,48,88,170,234,4096,-1,-1,-1,-1,-1,-1,-1,-1,-1,-1,-1,-1,-1},
    {278,286,406,32,64,56,48,88,170,234,4096,-1,-1,-1,-1,-1,-1,-1,-1,-1,-1,-1,-1,-1},
    {279,351,271,447,298,330,394,370,426,378,354,434,164,228,4096,-1,-1,-1,-1,-1,-1,-1,-1,-1},
    {279,351,271,447,298,330,394,370,426,378,354,434,164,228,4096,-1,-1,-1,-1,-1,-1,-1,-1,-1},
    {344,345,497,257,297,321,313,82,50,90,98,96,4096,-1,-1,-1,-1,-1,-1,-1,-1,-1,-1,-1},
    {344,345,497,257,297,321,313,82,50,90,98,96,4096,-1,-1,-1,-1,-1,-1,-1,-1,-1,-1,-1},
    {129,193,311,335,319,86,438,364,436,163,227,4096,-1,-1,-1,-1,-1,-1,-1,-1,-1,-1,-1,-1},
    {129,193,311,335,319,86,438,364,436,163,227,4096,-1,-1,-1,-1,-1,-1,-1,-1,-1,-1,-1,-1},
    {341,285,509,461,301,325,398,80,418,362,410,474,177,241,4096,-1,-1,-1,-1,-1,-1,-1,-1,-1},
    {341,285,509,461,301,325,398,80,418,362,410,474,177,241,4096,-1,-1,-1,-1,-1,-1,-1,-1,-1},
    {342,275,267,499,299,451,395,57,49,73,185,249,4096,-1,-1,-1,-1,-1,-1,-1,-1,-1,-1,-1},
    {342,275,267,499,299,451,395,57,49,73,185,249,4096,-1,-1,-1,-1,-1,-1,-1,-1,-1,-1,-1},
    {346,402,496,304,443,323,315,387,427,419,355,411,165,229,4096,-1,-1,-1,-1,-1,-1,-1,-1,-1},
    {346,402,496,304,443,323,315,387,427,419,355,411,165,229,4096,-1,-1,-1,-1,-1,-1,-1,-1,-1},
    {15,401,305,441,70,62,54,94,190,254,4096,-1,-1,-1,-1,-1,-1,-1,-1,-1,-1,-1,-1,-1},
    {15,401,305,441,70,62,54,94,190,254,4096,-1,-1,-1,-1,-1,-1,-1,-1,-1,-1,-1,-1,-1},
    {467,7,36,68,84,105,475,162,226,4096,-1,-1,-1,-1,-1,-1,-1,-1,-1,-1,-1,-1,-1,-1},
    {467,7,36,68,84,105,475,162,226,4096,-1,-1,-1,-1,-1,-1,-1,-1,-1,-1,-1,-1,-1,-1},
};

void build_rounds() {
    for (int c = 0; c < NUM_SMS / 2; c++) {
        const int16_t* jobs = h_params.jobs[2 * c];
        int nr = 0, prev_key = -1, last = 0;
        for (int j = 0; (jobs[j] >> 12) == T_P; j++) {
            const int n = jobs[j] >> 3, a = n >= 32, unit = n >= 16 && n < 32 ? (n >> 3) - 1 : 0, cnt = a ? 2 : 4;
            const int key = (jobs[j] & 7) | a << 3 | (unit > 0) << 4;
            const int wm = n < 16 ? 0 : (n < 32 ? 1 : n >> 4 & 1), col = n < 16 ? n : (n < 32 ? n & 7 : n & 15);
            const bool keep = key == prev_key, final_tile = (jobs[j + 1] >> 12) != T_P;
            const int k0 = keep ? last : 0;
            for (int r = 0; r < cnt; r++) {
                last = (k0 + r) % cnt;
                h_params.rounds[c][nr++] = (uint16_t)((key & 15) | wm << 4 | col << 6 | last << 10 | (keep && r == 0) << 12 | (final_tile && r == 0) << 13 | unit << 14);
            }
            prev_key = key;
        }
        while (nr < MAX_ROUNDS) h_params.rounds[c][nr++] = 0xFFFF;
        h_params.first[c] = h_params.rounds[c][0];
    }
}

void build_schedule() {
    for (int c = 0; c < NUM_SMS; c++) {
        for (int j = 0; j < MAX_JOBS; j++) h_params.jobs[c][j] = k_jobs[c][j];
    }
    build_rounds();
}

}

extern "C" void kernel_launch(void* const* d_in, const int* in_sizes, int n_in, void* d_out, int out_size) {
    (void)in_sizes; (void)n_in; (void)out_size;
    static EncodeFn enc = nullptr;
    if (!enc) {
        cudaDriverEntryPointQueryResult qr;
        void* fn = nullptr;
        cudaGetDriverEntryPoint("cuTensorMapEncodeTiled", &fn, cudaEnableDefault, &qr);
        enc = (EncodeFn)fn;
        cudaFuncSetAttribute(fused_kernel, cudaFuncAttributeMaxDynamicSharedMemorySize, SMEM_BYTES);
        build_schedule();
    }
    void* qkv;
    cudaGetSymbolAddress(&qkv, g_qkv);
    Params& p = h_params;
    make_map3(enc, &p.amap[0], d_in[0], SEQ, DM, 128, 1);
    make_map3(enc, &p.amap[1], d_in[1], SEQ, DC, 128, 1);
    make_map3(enc, &p.wmap[0], d_in[2], DM, 4096, 64, 2);
    make_map3(enc, &p.wmap[2], d_in[3], DC, 4096, 64, 2);
    make_map3(enc, &p.wmap[3], d_in[4], DC, 4096, 64, 2);
    make_map3(enc, &p.wmap[1], d_in[7], DM, 3072, 64, 2);
    make_map3(enc, &p.wo_a, d_in[5], 4096, DM, 64, 2);
    make_map3(enc, &p.wo_b, d_in[8], DM, DM, 64, 2);
    make_map3(enc, &p.qkv_st, qkv, SEQ, QKV_W, 64, 1, true);
    make_map3(enc, &p.qkv_ld, qkv, SEQ, QKV_W, 128, 2, true);
    make_map3(enc, &p.qkv_half, qkv, SEQ, QKV_W, 128, 1, true);
    {
        cuuint64_t dims[4] = {64, SEQ / 2, 2, QKV_W / 64}, strides[3] = {256, 128, (cuuint64_t)SEQ * 128};
        cuuint32_t box[4] = {64, 64, 1, 1}, es[4] = {1, 1, 1, 1};
        enc(&p.st_par, CU_TENSOR_MAP_DATA_TYPE_BFLOAT16, 4, qkv, dims, strides, box, es, CU_TENSOR_MAP_INTERLEAVE_NONE,
            CU_TENSOR_MAP_SWIZZLE_128B, CU_TENSOR_MAP_L2_PROMOTION_L2_256B, CU_TENSOR_MAP_FLOAT_OOB_FILL_NONE);
        dims[3] = DM / 64; strides[0] = DM * 4; strides[1] = DM * 2; strides[2] = 128; box[2] = 2;
        enc(&p.x_par, CU_TENSOR_MAP_DATA_TYPE_BFLOAT16, 4, d_in[0], dims, strides, box, es, CU_TENSOR_MAP_INTERLEAVE_NONE,
            CU_TENSOR_MAP_SWIZZLE_128B, CU_TENSOR_MAP_L2_PROMOTION_L2_256B, CU_TENSOR_MAP_FLOAT_OOB_FILL_NONE);
    }
    make_map3(enc, &p.out_st, d_out, SEQ, DM, 64, 1);
    p.xp = (const __nv_bfloat16*)d_in[0];
    p.gate_w = (const __nv_bfloat16*)d_in[9];
    p.out = (__nv_bfloat16*)d_out;
    fused_kernel<<<NUM_SMS, 384, SMEM_BYTES, cudaStreamPerThread>>>(p);
}
```

```cpp
#include <cuda_runtime.h>
#include <cuda_bf16.h>
#include <cuda.h>
#include <stdint.h>

#define INL __attribute__((always_inline))

namespace {

constexpr int SEQ = 2048;
constexpr int DM = 1024;
constexpr int DC = 512;
constexpr int QKV_W = 13312;
constexpr int NUM_SMS = 132;
constexpr int GATE_DELAY_SHORT_NS = 1000, GATE_DELAY_LONG_NS = 3000;
constexpr int CLEAR_KS = 30, CLEAR_GAP_NS = 100;
constexpr float Q_SCALE = 0.08838834764831845f * 1.4426950408889634f;

__device__ __align__(1024) __nv_bfloat16 g_qkv[(size_t)SEQ * QKV_W];
__device__ float g_gate[SEQ];
__device__ uint4 g_halo[16 * 8 * 2 * 5 * 4 * 32];

constexpr int F_Q = 0;
constexpr int F_KV = 1792;
constexpr int F_H = 768;
constexpr int F_CTX = 960;
constexpr int F_GATE = 1600;
constexpr int F_DONE = 1632;
constexpr int F_SPLIT = 1664;
constexpr int F_TICKET = 1696;
constexpr int F_OUT = 1728;
constexpr int GATE_COUNT = NUM_SMS;
__device__ uint32_t g_flags[2304];

#define END_MARK(slot)
#define TRACE_MARK(k, w, i)
#define GTRACE(w)
#define KTRACE(w)
#define PTRACE(i)
#define TRACE_GATE 32
#define TRACE_TID 128

__device__ __forceinline__ uint32_t smem_u32(const void* p) { return (uint32_t)__cvta_generic_to_shared(p); }
__device__ __forceinline__ void mbar_init(uint32_t bar, uint32_t cnt) {
    asm volatile("mbarrier.init.shared::cta.b64 [%0], %1;" ::"r"(bar), "r"(cnt));
}
__device__ __forceinline__ void mbar_arrive(uint32_t bar) {
    asm volatile("mbarrier.arrive.shared::cta.b64 _, [%0];" ::"r"(bar) : "memory");
}
__device__ __forceinline__ bool elect_one() {
    uint32_t r;
    asm volatile("{\n.reg .pred p;\nelect.sync _|p, 0xffffffff;\nselp.b32 %0, 1, 0, p;\n}" : "=r"(r));
    return r != 0;
}
__device__ __forceinline__ uint32_t mapa(uint32_t addr, uint32_t cta) {
    uint32_t r;
    asm("mapa.shared::cluster.u32 %0, %1, %2;" : "=r"(r) : "r"(addr), "r"(cta));
    return r;
}
__device__ __forceinline__ void warp_arrive(uint32_t bar, bool pred = true) {
    asm volatile("{\n.reg .pred p, q;\nsetp.ne.u32 q, %1, 0;\nelect.sync _|p, 0xffffffff;\nand.pred p, p, q;\n"
                 "@p mbarrier.arrive.shared::cta.b64 _, [%0];\n}" ::"r"(bar), "r"((uint32_t)pred) : "memory");
}
__device__ __forceinline__ void warp_arrive2(uint32_t bar0, uint32_t bar1) {
    asm volatile("{\n.reg .pred p;\nelect.sync _|p, 0xffffffff;\n@p mbarrier.arrive.shared::cta.b64 _, [%0];\n"
                 "@p mbarrier.arrive.shared::cta.b64 _, [%1];\n}" ::"r"(bar0), "r"(bar1) : "memory");
}
__device__ __forceinline__ void warp_arrive_pair(uint32_t bar, uint32_t peer_bar, bool pred = true) {
    asm volatile("{\n.reg .pred p, q;\nsetp.ne.u32 q, %2, 0;\nelect.sync _|p, 0xffffffff;\nand.pred p, p, q;\n"
                 "@p mbarrier.arrive.shared::cluster.b64 _, [%1];\n@p mbarrier.arrive.shared::cta.b64 _, [%0];\n}"
                 ::"r"(bar), "r"(peer_bar), "r"((uint32_t)pred) : "memory");
}
__device__ __forceinline__ void mbar_expect_tx(uint32_t bar, uint32_t bytes) {
    asm volatile("mbarrier.arrive.expect_tx.shared::cta.b64 _, [%0], %1;" ::"r"(bar), "r"(bytes) : "memory");
}
constexpr int WAIT_HINT_NS = 20000, WAIT_TRIES = 200000;
__device__ __forceinline__ void mbar_wait(uint32_t bar, uint32_t parity) {
    asm volatile("{\n.reg .pred p;\n.reg .u32 c;\n"
                 "mbarrier.try_wait.parity.shared::cta.b64 p, [%0], %1;\n@p bra DONE;\nmov.u32 c, 0;\n"
                 "SPIN:\nmbarrier.try_wait.parity.shared::cta.b64 p, [%0], %1, %2;\n@p bra DONE;\n"
                 "add.u32 c, c, 1;\nsetp.lt.u32 p, c, %3;\n@p bra SPIN;\ntrap;\nDONE:\n}"
                 ::"r"(bar), "r"(parity), "n"(WAIT_HINT_NS), "n"(WAIT_TRIES) : "memory");
}
__device__ __forceinline__ void mbar_wait_hot(uint32_t bar, uint32_t parity) {
    asm volatile("{\n.reg .pred p, q;\n.reg .u32 c;\n.reg .u64 z;\nmov.u32 c, 0;\nmov.u64 z, 0;\n"
                 "SPIN:\nmbarrier.try_wait.parity.shared::cta.b64 p, [%0], %1;\n"
                 "add.u32 c, c, 1;\nsetp.lt.and.u32 q, c, 4194304, !p;\n@q bra SPIN;\n@!p st.global.u32 [z], c;\n}"
                 ::"r"(bar), "r"(parity) : "memory");
}
constexpr uint64_t POL_STREAM = 0x12F0000000000000ull;
constexpr uint64_t POL_NORMAL = 0x1000000000000000ull;
__device__ __forceinline__ void tma_load_3d(uint32_t dst, const CUtensorMap* map, uint32_t bar, int c0, int c1, int c2, uint64_t pol = POL_NORMAL) {
    asm volatile("cp.async.bulk.tensor.3d.shared::cluster.global.mbarrier::complete_tx::bytes.L2::cache_hint [%0], [%1, {%3, %4, %5}], [%2], %6;"
                 ::"r"(dst), "l"(map), "r"(bar), "r"(c0), "r"(c1), "r"(c2), "l"(pol) : "memory");
}
__device__ __forceinline__ void load_kstep(uint32_t sa, uint32_t sw, uint32_t bar, uint32_t bytes, const CUtensorMap* wmap, int wk, int wblk,
                                           const CUtensorMap* amap, int arow, int kc, uint32_t amode) {
    asm volatile("{\n.reg .pred p, q, r;\n.reg .b32 k;\nelect.sync _|p, 0xffffffff;\nsetp.eq.and.u32 q, %9, 1, p;\nsetp.eq.and.u32 r, %9, 2, p;\nshl.b32 k, %12, 6;\n"
                 "@p mbarrier.arrive.expect_tx.shared::cta.b64 _, [%2], %3;\n"
                 "@p cp.async.bulk.tensor.3d.shared::cluster.global.mbarrier::complete_tx::bytes.multicast::cluster.L2::cache_hint [%1], [%4, {0, k, %5}], [%2], %10, %11;\n"
                 "@q cp.async.bulk.tensor.3d.shared::cluster.global.mbarrier::complete_tx::bytes.L2::cache_hint [%0], [%6, {0, %7, %8}], [%2], %11;\n"
                 "@r cp.async.bulk.tensor.4d.shared::cluster.global.mbarrier::complete_tx::bytes.L2::cache_hint [%0], [%6, {0, %7, 0, %8}], [%2], %11;\n}"
                 ::"r"(sa), "r"(sw), "r"(bar), "r"(bytes), "l"(wmap), "r"(wblk), "l"(amap), "r"(arow), "r"(kc), "r"(amode), "h"((uint16_t)3), "l"(POL_NORMAL), "r"(wk) : "memory");
}
__device__ __forceinline__ void load_operand(uint32_t dst, uint32_t bar, const CUtensorMap* full, const CUtensorMap* half, int row, int blk,
                                             uint32_t rank, bool solo, uint64_t pol) {
    asm volatile("{\n.reg .pred p, q, r;\n.reg .b32 d, b;\nelect.sync _|p, 0xffffffff;\nsetp.ne.and.u32 q, %7, 0, p;\nsetp.eq.and.u32 r, %7, 0, p;\n"
                 "mad.lo.u32 d, %6, 16384, %0;\nadd.u32 b, %5, %6;\n"
                 "@p mbarrier.arrive.expect_tx.shared::cta.b64 _, [%1], 32768;\n"
                 "@q cp.async.bulk.tensor.3d.shared::cluster.global.mbarrier::complete_tx::bytes.L2::cache_hint [%0], [%2, {0, %4, %5}], [%1], %9;\n"
                 "@r cp.async.bulk.tensor.3d.shared::cluster.global.mbarrier::complete_tx::bytes.multicast::cluster.L2::cache_hint [d], [%3, {0, %4, b}], [%1], %8, %9;\n}"
                 ::"r"(dst), "r"(bar), "l"(full), "l"(half), "r"(row), "r"(blk), "r"(rank), "r"((uint32_t)solo), "h"((uint16_t)3), "l"(pol) : "memory");
}
__device__ __forceinline__ void tma_store_par(const CUtensorMap* map, uint32_t src, int pair, int parity, int blk) {
    asm volatile("cp.async.bulk.tensor.4d.global.shared::cta.bulk_group.L2::cache_hint [%0, {0, %2, %3, %4}], [%1], %5;"
                 ::"l"(map), "r"(src), "r"(pair), "r"(parity), "r"(blk), "l"(POL_STREAM) : "memory");
}
__device__ __forceinline__ void tma_store_3d(const CUtensorMap* map, uint32_t src, int c0, int c1, int c2, uint64_t pol) {
    asm volatile("cp.async.bulk.tensor.3d.global.shared::cta.bulk_group.L2::cache_hint [%0, {%2, %3, %4}], [%1], %5;"
                 ::"l"(map), "r"(src), "r"(c0), "r"(c1), "r"(c2), "l"(pol) : "memory");
}
__device__ __forceinline__ void tma_reduce_add_3d(const CUtensorMap* map, uint32_t src, int c0, int c1, int c2) {
    asm volatile("cp.reduce.async.bulk.tensor.3d.global.shared::cta.add.tile.bulk_group [%0, {%2, %3, %4}], [%1];"
                 ::"l"(map), "r"(src), "r"(c0), "r"(c1), "r"(c2) : "memory");
}
__device__ __forceinline__ void bulk_commit() { asm volatile("cp.async.bulk.commit_group;" ::: "memory"); }
template <int N> __device__ __forceinline__ void bulk_wait_read() { asm volatile("cp.async.bulk.wait_group.read %0;" ::"n"(N) : "memory"); }
template <int N> __device__ __forceinline__ void bulk_wait() { asm volatile("cp.async.bulk.wait_group %0;" ::"n"(N) : "memory"); }
__device__ __forceinline__ void fence_async_smem() { asm volatile("fence.proxy.async.shared::cta;" ::: "memory"); }
__device__ __forceinline__ void fence_async_global() { asm volatile("fence.proxy.async.global;" ::: "memory"); }
__device__ __forceinline__ uint32_t ld_acquire(const uint32_t* p) {
    uint32_t v;
    asm volatile("ld.acquire.gpu.global.u32 %0, [%1];" : "=r"(v) : "l"(p) : "memory");
    return v;
}
__device__ __forceinline__ uint32_t ld_relaxed(const uint32_t* p) {
    uint32_t v;
    asm volatile("ld.relaxed.gpu.global.u32 %0, [%1];" : "=r"(v) : "l"(p) : "memory");
    return v;
}
__device__ __forceinline__ void fence_acquire() { asm volatile("fence.acquire.gpu;\nfence.proxy.async.global;" ::: "memory"); }
__device__ __forceinline__ void red_release(uint32_t* p) {
    asm volatile("red.release.gpu.global.add.u32 [%0], 1;" ::"l"(p) : "memory");
}
__device__ __forceinline__ void red_relaxed(uint32_t* p) {
    asm volatile("red.relaxed.gpu.global.add.u32 [%0], 1;" ::"l"(p) : "memory");
}
__device__ __forceinline__ void prefetch_map(const CUtensorMap* map) { asm volatile("prefetch.tensormap [%0];" ::"l"(map) : "memory"); }
__device__ __forceinline__ void trap_if(bool c) { asm volatile("{\n.reg .pred p;\nsetp.ne.u32 p, %0, 0;\n@p trap;\n}" ::"r"((uint32_t)c)); }
__device__ __forceinline__ void setup_arrive() { asm volatile("barrier.cluster.arrive.relaxed.aligned;" ::: "memory"); }
__device__ __forceinline__ void setup_wait() { asm volatile("barrier.cluster.wait.aligned;" ::: "memory"); }
__device__ __forceinline__ uint32_t cluster_rank() { uint32_t r; asm("mov.u32 %0, %%cluster_ctarank;" : "=r"(r)); return r; }
__device__ __forceinline__ void named_sync(int id, int n) { asm volatile("bar.sync %0, %1;" ::"r"(id), "r"(n) : "memory"); }
__device__ __forceinline__ void named_arrive(int id, int n) { asm volatile("bar.arrive %0, %1;" ::"r"(id), "r"(n) : "memory"); }
__device__ __forceinline__ void named_sync_if(bool c, int id, int n) {
    asm volatile("{\n.reg .pred p;\nsetp.ne.u32 p, %0, 0;\n@p bar.sync %1, %2;\n}" ::"r"((uint32_t)c), "r"(id), "r"(n) : "memory");
}
__device__ __forceinline__ void named_arrive_if(bool c, int id, int n) {
    asm volatile("{\n.reg .pred p;\nsetp.ne.u32 p, %0, 0;\n@p bar.arrive %1, %2;\n}" ::"r"((uint32_t)c), "r"(id), "r"(n) : "memory");
}
template <int V> struct IC { static constexpr int v = V; };
template <int N> __device__ __forceinline__ void reg_dec() { asm volatile("setmaxnreg.dec.sync.aligned.u32 %0;" ::"n"(N)); }
template <int N> __device__ __forceinline__ void reg_inc() { asm volatile("setmaxnreg.inc.sync.aligned.u32 %0;" ::"n"(N)); }

__device__ __forceinline__ void wg_fence() { asm volatile("wgmma.fence.sync.aligned;" ::: "memory"); }
__device__ __forceinline__ void wg_commit() { asm volatile("wgmma.commit_group.sync.aligned;" ::: "memory"); }
template <int N> __device__ __forceinline__ void wg_wait() { asm volatile("wgmma.wait_group.sync.aligned %0;" ::"n"(N) : "memory"); }
template <int N> __device__ __forceinline__ void fence_regs(float (&r)[N]) {
#pragma unroll
    for (int i = 0; i < N; i++) asm volatile("" : "+f"(r[i])::"memory");
}
template <int N> __device__ __forceinline__ void fence_regs(uint32_t (&r)[N]) {
#pragma unroll
    for (int i = 0; i < N; i++) asm volatile("" : "+r"(r[i])::"memory");
}
__device__ __forceinline__ uint32_t desc_lo(uint32_t addr, uint32_t lbo) { return ((addr & 0x3FFFF) >> 4) | ((lbo >> 4) << 16); }
__device__ __forceinline__ int uniform(int v) { return __shfl_sync(0xffffffffu, v, 0); }
__device__ __forceinline__ uint32_t pack_bf16(float lo, float hi) {
    uint32_t r;
    asm("cvt.rn.bf16x2.f32 %0, %1, %2;" : "=r"(r) : "f"(hi), "f"(lo));
    return r;
}
__device__ __forceinline__ void stmatrix_x4(uint32_t addr, uint32_t r0, uint32_t r1, uint32_t r2, uint32_t r3) {
    asm volatile("stmatrix.sync.aligned.m8n8.x4.shared.b16 [%0], {%1, %2, %3, %4};"
                 ::"r"(addr), "r"(r0), "r"(r1), "r"(r2), "r"(r3) : "memory");
}
__device__ __forceinline__ void stmatrix_x4(uint32_t addr, uint32_t r0, uint32_t r1, uint32_t r2, uint32_t r3, bool trans) {
    asm volatile("{\n.reg .pred p;\nsetp.ne.u32 p, %5, 0;\n@p stmatrix.sync.aligned.m8n8.x4.trans.shared.b16 [%0], {%1, %2, %3, %4};\n"
                 "@!p stmatrix.sync.aligned.m8n8.x4.shared.b16 [%0], {%1, %2, %3, %4};\n}"
                 ::"r"(addr), "r"(r0), "r"(r1), "r"(r2), "r"(r3), "r"((uint32_t)trans) : "memory");
}
__device__ __forceinline__ void ldmatrix_x4_t(uint32_t addr, uint32_t (&r)[4]) {
    asm volatile("ldmatrix.sync.aligned.m8n8.x4.trans.shared.b16 {%0, %1, %2, %3}, [%4];"
                 : "=r"(r[0]), "=r"(r[1]), "=r"(r[2]), "=r"(r[3]) : "r"(addr) : "memory");
}
__device__ __forceinline__ void mma_16816(float (&d)[4], uint32_t a0, uint32_t a1, uint32_t a2, uint32_t a3, uint32_t b0, uint32_t b1) {
    asm("mma.sync.aligned.m16n8k16.row.col.f32.bf16.bf16.f32 {%0, %1, %2, %3}, {%4, %5, %6, %7}, {%8, %9}, {%0, %1, %2, %3};"
        : "+f"(d[0]), "+f"(d[1]), "+f"(d[2]), "+f"(d[3]) : "r"(a0), "r"(a1), "r"(a2), "r"(a3), "r"(b0), "r"(b1));
}
__device__ __forceinline__ void order_after(float v, uint32_t scratch) {
    asm volatile("{\n.reg .pred p;\nsetp.gt.f32 p, %0, 0f70000000;\n@p st.shared.u32 [%1], 0;\n}" ::"f"(v), "r"(scratch) : "memory");
}
__device__ __forceinline__ float rcp(float x) { float y; asm("rcp.approx.ftz.f32 %0, %1;" : "=f"(y) : "f"(x)); return y; }
__device__ __forceinline__ float ex2(float x) { float y; asm("ex2.approx.ftz.f32 %0, %1;" : "=f"(y) : "f"(x)); return y; }

template <int OA, int OB>
__device__ __forceinline__ void wgmma_ss_n256(float (&d0)[64], float (&d1)[64], uint32_t da, uint32_t db) {
    asm volatile("{\n.reg .b32 ta, tb;\n.reg .b64 da, db;\nadd.u32 ta, %128, %130;\nadd.u32 tb, %129, %131;\n"
        "mov.b64 da, {ta, 0x40000040};\nmov.b64 db, {tb, 0x40000040};\n"
        "wgmma.mma_async.sync.aligned.m64n256k16.f32.bf16.bf16 {%0, %1, %2, %3, %4, %5, %6, %7, %8, %9, %10, %11, %12, %13, %14, %15, %16, %17, %18, %19, %20, %21, %22, %23, %24, %25, %26, %27, %28, %29, %30, %31, %32, %33, %34, %35, %36, %37, %38, %39, %40, %41, %42, %43, %44, %45, %46, %47, %48, %49, %50, %51, %52, %53, %54, %55, %56, %57, %58, %59, %60, %61, %62, %63, %64, %65, %66, %67, %68, %69, %70, %71, %72, %73, %74, %75, %76, %77, %78, %79, %80, %81, %82, %83, %84, %85, %86, %87, %88, %89, %90, %91, %92, %93, %94, %95, %96, %97, %98, %99, %100, %101, %102, %103, %104, %105, %106, %107, %108, %109, %110, %111, %112, %113, %114, %115, %116, %117, %118, %119, %120, %121, %122, %123, %124, %125, %126, %127}, da, db, 1, 1, 1, 0, 1;\n}\n"
        : "+f"(d0[0]), "+f"(d0[1]), "+f"(d0[2]), "+f"(d0[3]), "+f"(d0[4]), "+f"(d0[5]), "+f"(d0[6]), "+f"(d0[7]), "+f"(d0[8]), "+f"(d0[9]), "+f"(d0[10]), "+f"(d0[11]), "+f"(d0[12]), "+f"(d0[13]), "+f"(d0[14]), "+f"(d0[15]), "+f"(d0[16]), "+f"(d0[17]), "+f"(d0[18]), "+f"(d0[19]), "+f"(d0[20]), "+f"(d0[21]), "+f"(d0[22]), "+f"(d0[23]), "+f"(d0[24]), "+f"(d0[25]), "+f"(d0[26]), "+f"(d0[27]), "+f"(d0[28]), "+f"(d0[29]), "+f"(d0[30]), "+f"(d0[31]), "+f"(d0[32]), "+f"(d0[33]), "+f"(d0[34]), "+f"(d0[35]), "+f"(d0[36]), "+f"(d0[37]), "+f"(d0[38]), "+f"(d0[39]), "+f"(d0[40]), "+f"(d0[41]), "+f"(d0[42]), "+f"(d0[43]), "+f"(d0[44]), "+f"(d0[45]), "+f"(d0[46]), "+f"(d0[47]), "+f"(d0[48]), "+f"(d0[49]), "+f"(d0[50]), "+f"(d0[51]), "+f"(d0[52]), "+f"(d0[53]), "+f"(d0[54]), "+f"(d0[55]), "+f"(d0[56]), "+f"(d0[57]), "+f"(d0[58]), "+f"(d0[59]), "+f"(d0[60]), "+f"(d0[61]), "+f"(d0[62]), "+f"(d0[63]), "+f"(d1[0]), "+f"(d1[1]), "+f"(d1[2]), "+f"(d1[3]), "+f"(d1[4]), "+f"(d1[5]), "+f"(d1[6]), "+f"(d1[7]), "+f"(d1[8]), "+f"(d1[9]), "+f"(d1[10]), "+f"(d1[11]), "+f"(d1[12]), "+f"(d1[13]), "+f"(d1[14]), "+f"(d1[15]), "+f"(d1[16]), "+f"(d1[17]), "+f"(d1[18]), "+f"(d1[19]), "+f"(d1[20]), "+f"(d1[21]), "+f"(d1[22]), "+f"(d1[23]), "+f"(d1[24]), "+f"(d1[25]), "+f"(d1[26]), "+f"(d1[27]), "+f"(d1[28]), "+f"(d1[29]), "+f"(d1[30]), "+f"(d1[31]), "+f"(d1[32]), "+f"(d1[33]), "+f"(d1[34]), "+f"(d1[35]), "+f"(d1[36]), "+f"(d1[37]), "+f"(d1[38]), "+f"(d1[39]), "+f"(d1[40]), "+f"(d1[41]), "+f"(d1[42]), "+f"(d1[43]), "+f"(d1[44]), "+f"(d1[45]), "+f"(d1[46]), "+f"(d1[47]), "+f"(d1[48]), "+f"(d1[49]), "+f"(d1[50]), "+f"(d1[51]), "+f"(d1[52]), "+f"(d1[53]), "+f"(d1[54]), "+f"(d1[55]), "+f"(d1[56]), "+f"(d1[57]), "+f"(d1[58]), "+f"(d1[59]), "+f"(d1[60]), "+f"(d1[61]), "+f"(d1[62]), "+f"(d1[63])
        : "r"(da), "r"(db), "n"(OA), "n"(OB));
}

__device__ __forceinline__ void wgmma_ss_n256_init(float (&d0)[64], float (&d1)[64], uint32_t da, uint32_t db) {
    asm volatile("{\n.reg .b64 da, db;\n"
        "mov.b64 da, {%128, 0x40000040};\nmov.b64 db, {%129, 0x40000040};\n"
        "wgmma.mma_async.sync.aligned.m64n256k16.f32.bf16.bf16 {%0, %1, %2, %3, %4, %5, %6, %7, %8, %9, %10, %11, %12, %13, %14, %15, %16, %17, %18, %19, %20, %21, %22, %23, %24, %25, %26, %27, %28, %29, %30, %31, %32, %33, %34, %35, %36, %37, %38, %39, %40, %41, %42, %43, %44, %45, %46, %47, %48, %49, %50, %51, %52, %53, %54, %55, %56, %57, %58, %59, %60, %61, %62, %63, %64, %65, %66, %67, %68, %69, %70, %71, %72, %73, %74, %75, %76, %77, %78, %79, %80, %81, %82, %83, %84, %85, %86, %87, %88, %89, %90, %91, %92, %93, %94, %95, %96, %97, %98, %99, %100, %101, %102, %103, %104, %105, %106, %107, %108, %109, %110, %111, %112, %113, %114, %115, %116, %117, %118, %119, %120, %121, %122, %123, %124, %125, %126, %127}, da, db, 0, 1, 1, 0, 1;\n}\n"
        : "=f"(d0[0]), "=f"(d0[1]), "=f"(d0[2]), "=f"(d0[3]), "=f"(d0[4]), "=f"(d0[5]), "=f"(d0[6]), "=f"(d0[7]), "=f"(d0[8]), "=f"(d0[9]), "=f"(d0[10]), "=f"(d0[11]), "=f"(d0[12]), "=f"(d0[13]), "=f"(d0[14]), "=f"(d0[15]), "=f"(d0[16]), "=f"(d0[17]), "=f"(d0[18]), "=f"(d0[19]), "=f"(d0[20]), "=f"(d0[21]), "=f"(d0[22]), "=f"(d0[23]), "=f"(d0[24]), "=f"(d0[25]), "=f"(d0[26]), "=f"(d0[27]), "=f"(d0[28]), "=f"(d0[29]), "=f"(d0[30]), "=f"(d0[31]), "=f"(d0[32]), "=f"(d0[33]), "=f"(d0[34]), "=f"(d0[35]), "=f"(d0[36]), "=f"(d0[37]), "=f"(d0[38]), "=f"(d0[39]), "=f"(d0[40]), "=f"(d0[41]), "=f"(d0[42]), "=f"(d0[43]), "=f"(d0[44]), "=f"(d0[45]), "=f"(d0[46]), "=f"(d0[47]), "=f"(d0[48]), "=f"(d0[49]), "=f"(d0[50]), "=f"(d0[51]), "=f"(d0[52]), "=f"(d0[53]), "=f"(d0[54]), "=f"(d0[55]), "=f"(d0[56]), "=f"(d0[57]), "=f"(d0[58]), "=f"(d0[59]), "=f"(d0[60]), "=f"(d0[61]), "=f"(d0[62]), "=f"(d0[63]), "=f"(d1[0]), "=f"(d1[1]), "=f"(d1[2]), "=f"(d1[3]), "=f"(d1[4]), "=f"(d1[5]), "=f"(d1[6]), "=f"(d1[7]), "=f"(d1[8]), "=f"(d1[9]), "=f"(d1[10]), "=f"(d1[11]), "=f"(d1[12]), "=f"(d1[13]), "=f"(d1[14]), "=f"(d1[15]), "=f"(d1[16]), "=f"(d1[17]), "=f"(d1[18]), "=f"(d1[19]), "=f"(d1[20]), "=f"(d1[21]), "=f"(d1[22]), "=f"(d1[23]), "=f"(d1[24]), "=f"(d1[25]), "=f"(d1[26]), "=f"(d1[27]), "=f"(d1[28]), "=f"(d1[29]), "=f"(d1[30]), "=f"(d1[31]), "=f"(d1[32]), "=f"(d1[33]), "=f"(d1[34]), "=f"(d1[35]), "=f"(d1[36]), "=f"(d1[37]), "=f"(d1[38]), "=f"(d1[39]), "=f"(d1[40]), "=f"(d1[41]), "=f"(d1[42]), "=f"(d1[43]), "=f"(d1[44]), "=f"(d1[45]), "=f"(d1[46]), "=f"(d1[47]), "=f"(d1[48]), "=f"(d1[49]), "=f"(d1[50]), "=f"(d1[51]), "=f"(d1[52]), "=f"(d1[53]), "=f"(d1[54]), "=f"(d1[55]), "=f"(d1[56]), "=f"(d1[57]), "=f"(d1[58]), "=f"(d1[59]), "=f"(d1[60]), "=f"(d1[61]), "=f"(d1[62]), "=f"(d1[63])
        : "r"(da), "r"(db));
}

template <int TB, int OA, int OB>
__device__ __forceinline__ void wgmma_ss_n128_init(float (&d)[64], uint32_t da, uint32_t db) {
    asm volatile("{\n.reg .b32 ta, tb;\n.reg .b64 da, db;\nadd.u32 ta, %64, %66;\nadd.u32 tb, %65, %67;\n"
        "mov.b64 da, {ta, 0x40000040};\nmov.b64 db, {tb, 0x40000040};\n"
        "wgmma.mma_async.sync.aligned.m64n128k16.f32.bf16.bf16 {%0, %1, %2, %3, %4, %5, %6, %7, %8, %9, %10, %11, %12, %13, %14, %15, %16, %17, %18, %19, %20, %21, %22, %23, %24, %25, %26, %27, %28, %29, %30, %31, %32, %33, %34, %35, %36, %37, %38, %39, %40, %41, %42, %43, %44, %45, %46, %47, %48, %49, %50, %51, %52, %53, %54, %55, %56, %57, %58, %59, %60, %61, %62, %63}, da, db, 0, 1, 1, 0, %68;\n}\n"
        : "=f"(d[0]), "=f"(d[1]), "=f"(d[2]), "=f"(d[3]), "=f"(d[4]), "=f"(d[5]), "=f"(d[6]), "=f"(d[7]), "=f"(d[8]), "=f"(d[9]), "=f"(d[10]), "=f"(d[11]), "=f"(d[12]), "=f"(d[13]), "=f"(d[14]), "=f"(d[15]), "=f"(d[16]), "=f"(d[17]), "=f"(d[18]), "=f"(d[19]), "=f"(d[20]), "=f"(d[21]), "=f"(d[22]), "=f"(d[23]), "=f"(d[24]), "=f"(d[25]), "=f"(d[26]), "=f"(d[27]), "=f"(d[28]), "=f"(d[29]), "=f"(d[30]), "=f"(d[31]), "=f"(d[32]), "=f"(d[33]), "=f"(d[34]), "=f"(d[35]), "=f"(d[36]), "=f"(d[37]), "=f"(d[38]), "=f"(d[39]), "=f"(d[40]), "=f"(d[41]), "=f"(d[42]), "=f"(d[43]), "=f"(d[44]), "=f"(d[45]), "=f"(d[46]), "=f"(d[47]), "=f"(d[48]), "=f"(d[49]), "=f"(d[50]), "=f"(d[51]), "=f"(d[52]), "=f"(d[53]), "=f"(d[54]), "=f"(d[55]), "=f"(d[56]), "=f"(d[57]), "=f"(d[58]), "=f"(d[59]), "=f"(d[60]), "=f"(d[61]), "=f"(d[62]), "=f"(d[63])
        : "r"(da), "r"(db), "n"(OA), "n"(OB), "n"(TB));
}

template <int OA, int OB>
__device__ __forceinline__ void wgmma_ss_n128_tb0(float (&d)[64], uint32_t da, uint32_t db, int scale_d) {
    asm volatile("{\n.reg .pred p;\n.reg .b32 ta, tb;\n.reg .b64 da, db;\nsetp.ne.b32 p, %66, 0;\nadd.u32 ta, %64, %67;\nadd.u32 tb, %65, %68;\n"
        "mov.b64 da, {ta, 0x40000040};\nmov.b64 db, {tb, 0x40000040};\n"
        "wgmma.mma_async.sync.aligned.m64n128k16.f32.bf16.bf16 "
        "{%0, %1, %2, %3, %4, %5, %6, %7, %8, %9, %10, %11, %12, %13, %14, %15, %16, %17, %18, %19, %20, %21, %22, %23, %24, %25, %26, %27, %28, %29, %30, %31, %32, %33, %34, %35, %36, %37, %38, %39, %40, %41, %42, %43, %44, %45, %46, %47, %48, %49, %50, %51, %52, %53, %54, %55, %56, %57, %58, %59, %60, %61, %62, %63}, da, db, p, 1, 1, 0, 0;\n}\n"
        : "+f"(d[0]), "+f"(d[1]), "+f"(d[2]), "+f"(d[3]), "+f"(d[4]), "+f"(d[5]), "+f"(d[6]), "+f"(d[7]), "+f"(d[8]), "+f"(d[9]), "+f"(d[10]), "+f"(d[11]), "+f"(d[12]), "+f"(d[13]), "+f"(d[14]), "+f"(d[15]), "+f"(d[16]), "+f"(d[17]), "+f"(d[18]), "+f"(d[19]), "+f"(d[20]), "+f"(d[21]), "+f"(d[22]), "+f"(d[23]), "+f"(d[24]), "+f"(d[25]), "+f"(d[26]), "+f"(d[27]), "+f"(d[28]), "+f"(d[29]), "+f"(d[30]), "+f"(d[31]), "+f"(d[32]), "+f"(d[33]), "+f"(d[34]), "+f"(d[35]), "+f"(d[36]), "+f"(d[37]), "+f"(d[38]), "+f"(d[39]), "+f"(d[40]), "+f"(d[41]), "+f"(d[42]), "+f"(d[43]), "+f"(d[44]), "+f"(d[45]), "+f"(d[46]), "+f"(d[47]), "+f"(d[48]), "+f"(d[49]), "+f"(d[50]), "+f"(d[51]), "+f"(d[52]), "+f"(d[53]), "+f"(d[54]), "+f"(d[55]), "+f"(d[56]), "+f"(d[57]), "+f"(d[58]), "+f"(d[59]), "+f"(d[60]), "+f"(d[61]), "+f"(d[62]), "+f"(d[63])
        : "r"(da), "r"(db), "r"(scale_d), "n"(OA), "n"(OB));
}

template <int OB>
__device__ __forceinline__ void wgmma_rs_n128_tb1(float (&d)[64], uint32_t a0, uint32_t a1, uint32_t a2, uint32_t a3, uint32_t db, int scale_d) {
    asm volatile("{\n.reg .pred p;\n.reg .b32 tb;\n.reg .b64 db;\nsetp.ne.b32 p, %69, 0;\nadd.u32 tb, %68, %70;\n"
        "mov.b64 db, {tb, 0x40000040};\n"
        "wgmma.mma_async.sync.aligned.m64n128k16.f32.bf16.bf16 "
        "{%0, %1, %2, %3, %4, %5, %6, %7, %8, %9, %10, %11, %12, %13, %14, %15, %16, %17, %18, %19, %20, %21, %22, %23, %24, %25, %26, %27, %28, %29, %30, %31, %32, %33, %34, %35, %36, %37, %38, %39, %40, %41, %42, %43, %44, %45, %46, %47, %48, %49, %50, %51, %52, %53, %54, %55, %56, %57, %58, %59, %60, %61, %62, %63}, {%64, %65, %66, %67}, db, p, 1, 1, 1;\n}\n"
        : "+f"(d[0]), "+f"(d[1]), "+f"(d[2]), "+f"(d[3]), "+f"(d[4]), "+f"(d[5]), "+f"(d[6]), "+f"(d[7]), "+f"(d[8]), "+f"(d[9]), "+f"(d[10]), "+f"(d[11]), "+f"(d[12]), "+f"(d[13]), "+f"(d[14]), "+f"(d[15]), "+f"(d[16]), "+f"(d[17]), "+f"(d[18]), "+f"(d[19]), "+f"(d[20]), "+f"(d[21]), "+f"(d[22]), "+f"(d[23]), "+f"(d[24]), "+f"(d[25]), "+f"(d[26]), "+f"(d[27]), "+f"(d[28]), "+f"(d[29]), "+f"(d[30]), "+f"(d[31]), "+f"(d[32]), "+f"(d[33]), "+f"(d[34]), "+f"(d[35]), "+f"(d[36]), "+f"(d[37]), "+f"(d[38]), "+f"(d[39]), "+f"(d[40]), "+f"(d[41]), "+f"(d[42]), "+f"(d[43]), "+f"(d[44]), "+f"(d[45]), "+f"(d[46]), "+f"(d[47]), "+f"(d[48]), "+f"(d[49]), "+f"(d[50]), "+f"(d[51]), "+f"(d[52]), "+f"(d[53]), "+f"(d[54]), "+f"(d[55]), "+f"(d[56]), "+f"(d[57]), "+f"(d[58]), "+f"(d[59]), "+f"(d[60]), "+f"(d[61]), "+f"(d[62]), "+f"(d[63])
        : "r"(a0), "r"(a1), "r"(a2), "r"(a3), "r"(db), "r"(scale_d), "n"(OB));
}

__device__ __forceinline__ uint32_t stage_addr(uint32_t block, int warp, int lane) {
    return block + (warp * 16 + (lane & 7) + ((lane >> 3) & 1) * 8) * 128 + (((lane >> 4) ^ (lane & 7)) << 4);
}
template <int OFF, int N>
__device__ __forceinline__ void stage_packed_64x64(uint32_t a0, int off, const uint32_t (&v)[N]) {
#pragma unroll
    for (int j = 0; j < 8; j += 2) {
        uint32_t a = a0;
        if (j) asm volatile("xor.b32 %0, %1, %2;" : "=r"(a) : "r"(a0), "r"(j << 4));
        stmatrix_x4(a + off, v[OFF + j * 2], v[OFF + j * 2 + 1], v[OFF + j * 2 + 2], v[OFF + j * 2 + 3]);
    }
}

template <int OFF, int N>
__device__ __forceinline__ void stage_packed_64x64(const uint32_t (&a)[4], int off, const uint32_t (&v)[N]) {
#pragma unroll
    for (int j = 0; j < 4; j++) stmatrix_x4(a[j] + off, v[OFF + j * 4], v[OFF + j * 4 + 1], v[OFF + j * 4 + 2], v[OFF + j * 4 + 3]);
}

template <int OFF, int N>
__device__ __forceinline__ void stage_packed_64x64(const uint32_t (&a)[4], int off, const uint32_t (&v)[N], bool trans) {
#pragma unroll
    for (int j = 0; j < 4; j++) stmatrix_x4(a[j] + off, v[OFF + j * 4], v[OFF + j * 4 + 1], v[OFF + j * 4 + 2], v[OFF + j * 4 + 3], trans);
}

constexpr int MAX_JOBS = 24;
constexpr int MAX_ROUNDS = 44;
constexpr int T_P = 0, T_O = 1, T_A = 2;
constexpr int HQ_A = 4, HQ_B = 28;
__host__ __device__ constexpr int unit_head(int g) { return g + (g < 4 ? HQ_A : HQ_B - 4); }
constexpr int G_STAGE = 49152;
constexpr int OFF_Q0 = 0, OFF_K0 = 32768, OFF_Q1 = 65536, OFF_K1 = 98304, OFF_V0 = 131072, OFF_V1 = 163840;
constexpr int OFF_STG = 196608;
constexpr int OFF_BAR = 229376;
constexpr int SMEM_BYTES = OFF_BAR + 640;
constexpr int TURN_THREADS = 288;

struct Params {
    CUtensorMap amap[2];
    CUtensorMap wmap[4];
    CUtensorMap x_par, wo_a, wo_b, qkv_st, qkv_ld, qkv_half, st_par, out_st;
    const __nv_bfloat16* xp;
    const __nv_bfloat16* gate_w;
    __nv_bfloat16* out;
    uint2 first[NUM_SMS];
    int16_t jobs[NUM_SMS][MAX_JOBS];
    uint16_t rounds[NUM_SMS / 2][MAX_ROUNDS];
};

constexpr int O_STAGGER = 4;
constexpr int O_F0 = 35, O_H1 = 5;
constexpr int O_FLEX = 16, O_H0 = O_F0 + 8, O_T0 = 8, O_T1 = 64 - O_F0 - O_FLEX - O_H1;
__device__ __forceinline__ int o_head(int job) { return (job & 32) ? O_H1 : O_H0; }
__device__ __forceinline__ int o_tail(int job) { return (job & 32) ? O_T1 : O_T0; }
__device__ __forceinline__ uint32_t o_state(uint32_t word, int have) {
    uint32_t v;
    asm volatile("{\n.reg .pred p, q;\n.reg .u32 c, t;\nmov.u32 c, 0;\n"
                 "SPIN:\nld.volatile.shared.u32 %0, [%1];\nand.b32 t, %0, 1;\nsetp.ne.u32 q, t, 0;\nsetp.gt.or.u32 p, %0, %2, q;\n@p bra DONE;\n"
                 "add.u32 c, c, 1;\nsetp.lt.u32 q, c, 16777216;\n@q bra SPIN;\ntrap;\nDONE:\n}"
                 : "=r"(v) : "r"(word), "r"(2 * have + 1) : "memory");
    return v;
}

template <class T> __device__ __forceinline__ T* page_ptr(int off) {
    extern __shared__ __align__(1024) uint8_t smem_raw[];
    return *reinterpret_cast<T* volatile*>(smem_raw + OFF_BAR + off);
}
template <int SLEEP_NS = 0>
__device__ __forceinline__ bool wait_flags(bool active, int idx, uint32_t target, bool block = true) {
    for (uint32_t tries = 0;; tries++) {
        const bool ok = !active | ((int32_t)(ld_acquire(g_flags + idx) - target) >= 0);
        if (__all_sync(0xffffffffu, ok)) break;
        if (!block) return false;
        if (SLEEP_NS) __nanosleep(SLEEP_NS);
        trap_if(tries > (1u << 22));
    }
    fence_async_global();
    return true;
}

__global__ void __cluster_dims__(2, 1, 1) __launch_bounds__(384, 1)
fused_kernel(const __grid_constant__ Params p) {
    extern __shared__ __align__(1024) uint8_t smem_raw[];
    const uint32_t base = smem_u32(smem_raw);
    const uint32_t bars = base + OFF_BAR;
    const uint32_t gfull = bars, gempty = bars + 32, sfull = bars + 64, sempty = bars + 96;
    const uint32_t qfull = bars + 128, qempty = bars + 144, kfull = bars + 160, kempty = bars + 176;
    const uint32_t vfull = bars + 192, vempty = bars + 208, lready = bars + 224, hout = bars + 240;
    const uint32_t tfull = bars + 256, aready = bars + 272, gatefull = bars + 280;
    const uint32_t otile = bars + 528;
    const uint32_t olim = bars + 504;
    const uint32_t stg = base + OFF_STG;
    uint32_t* rounds = reinterpret_cast<uint32_t*>(smem_raw + OFF_BAR + 416);
    const uint32_t rank = cluster_rank();
    int* jobs = reinterpret_cast<int*>(smem_raw + OFF_BAR + 312);
    auto w_map = [&](uint32_t rec, uint32_t half) INL { return &p.wmap[(rec & 8) ? 2 + half : ((rec >> 15) && half ? 0 : rec >> 4 & 1)]; };
    auto w_blk = [&](uint32_t rec, uint32_t half) INL -> int {
        const int col = rec >> 6 & 15;
        if (rec & 8) return (col + (rec & 16)) * 2;
        return rec >> 14 == 0 ? col * 4 + half * 2 : (rec >> 14 == 1 ? 16 + half * 16 + col * 2 : (half ? unit_head(col) : col) * 2);
    };
    auto load_round = [&](uint32_t rec, int st0, uint32_t parity) INL {
        const CUtensorMap* wm = w_map(rec, rank);
        const CUtensorMap* am = rec >> 14 ? &p.x_par : &p.amap[rec >> 3 & 1];
        const int wb = w_blk(rec, rank), kc0 = (rec >> 10 & 3) * 4, arow = ((rec & 7) * 256 + rank * 128) >> (rec >> 14 ? 1 : 0);
        const uint32_t bytes = (rec & 4096) ? G_STAGE - 16384 : G_STAGE, amode = (rec & 4096) ? 0 : (rec >> 14 ? 2 : 1);
#pragma unroll 1
        for (int st = st0; st < 4; st++) {
            const uint32_t sa = base + st * G_STAGE;
            mbar_wait(gempty + st * 8, parity);
            load_kstep(sa, sa + 16384 + rank * 16384, gfull + st * 8, bytes, wm, kc0 + st, wb, am, arow, kc0 + st, amode);
        }
    };
    if (threadIdx.x < 32) {
        if (elect_one()) {
            const uint2 r = p.first[blockIdx.x];
            mbar_init(gfull, 1);
            fence_async_smem();
            const char* maps;
            asm("mov.b64 %0, %1;" : "=l"(maps) : "l"(&p.amap[0]));
            asm volatile("{\n.reg .pred q;\nsetp.eq.u32 q, %8, 0;\n"
                         "mbarrier.arrive.expect_tx.shared::cta.b64 _, [%1], 49152;\n"
                         "cp.async.bulk.tensor.3d.shared::cluster.global.mbarrier::complete_tx::bytes.L2::cache_hint [%9], [%3, {0, 0, %6}], [%1], %11;\n"
                         "cp.async.bulk.tensor.3d.shared::cluster.global.mbarrier::complete_tx::bytes.L2::cache_hint [%10], [%4, {0, 0, %7}], [%1], %11;\n"
                         "@q cp.async.bulk.tensor.3d.shared::cluster.global.mbarrier::complete_tx::bytes.L2::cache_hint [%0], [%2, {0, %5, 0}], [%1], %11;\n"
                         "@!q cp.async.bulk.tensor.4d.shared::cluster.global.mbarrier::complete_tx::bytes.L2::cache_hint [%0], [%2, {0, %5, 0, 0}], [%1], %11;\n}"
                         ::"r"(base), "r"(gfull), "l"(maps + (r.x & 0x780)), "l"(maps + (r.x >> 4 & 0x780)), "l"(maps + (r.x >> 8 & 0x780)),
                           "r"(r.x >> 20), "r"(r.y & 0xffff), "r"(r.y >> 16), "r"(r.x & 1), "r"(base + 16384), "r"(base + 32768), "l"(POL_NORMAL) : "memory");
            asm volatile("fence.mbarrier_init.release.cluster;" ::: "memory");
        }
        __syncwarp();
    }
    const int tid = threadIdx.x, warp = uniform(tid >> 5), lane = tid & 31, wg = warp >> 2;
    if (warp == 1) {
        if (elect_one()) {
#pragma unroll
            for (int i = 1; i < 39; i++)
                mbar_init(bars + i * 8, (0x0CC000F0ull >> i & 1) ? 16 : ((0x300000F00ull >> i & 1) ? 4 : ((0xC0000ull >> i & 1) ? 8 : 1)));
            asm volatile("fence.mbarrier_init.release.cluster;" ::: "memory");
            fence_async_smem();
        }
        __syncwarp();
    }
    setup_arrive();
    if (warp > 3) {
        reg_inc<232>();
        named_sync(0, 352);
        const int w = wg - 1, wwarp = warp & 3;
        const uint32_t slot_a = stage_addr(stg + w * 16384, wwarp, lane);
        const uint32_t bars_peer = uniform(mapa(bars, rank ^ 1));
        auto arrive_pair = [&](uint32_t bar, bool pred = true) INL { warp_arrive_pair(bar, bars_peer + (bar - bars), pred); };
        uint32_t gph = 0;
        uint32_t sph = 1;
        int jb = 0;
        int job = uniform(jobs[0]);
        auto next_job = [&]() INL { jb++; job = uniform(jobs[jb]); };
        auto slot_wait = [&](int q) INL { mbar_wait(sempty + (w * 2 + (q & 1)) * 8, (q >> 1) ^ sph ^ 1); };
        auto signal = [&](int q) INL {
            __syncwarp();
            warp_arrive(sfull + (w * 2 + (q & 1)) * 8);
        };
        uint32_t pk[64];
        float O[64];
        float oscale1 = 1.f;
        uint32_t slot4[4];
        bool ptrans = false;
        auto stage_quarter = [&](const int Q) INL {
            slot_wait(Q);
            if (Q == 0) stage_packed_64x64<0>(slot4, 0, pk, ptrans);
            if (Q == 1) stage_packed_64x64<16>(slot4, 8192, pk, ptrans);
            if (Q == 2) stage_packed_64x64<32>(slot4, 0, pk);
            if (Q == 3) stage_packed_64x64<48>(slot4, 8192, pk);
        };
        auto stage_pair = [&]() INL {
            slot_wait(1);
            stage_packed_64x64<0>(slot4, 0, pk, ptrans);
            stage_packed_64x64<16>(slot4, 8192, pk, ptrans);
        };
        auto signal_both = [&]() INL {
            __syncwarp();
            warp_arrive2(sfull + w * 16, sfull + w * 16 + 8);
        };
        uint32_t un = 0;
        auto lane_id = [&]() INL { uint32_t ln; asm volatile("mov.u32 %0, %%laneid;" : "=r"(ln)); return ln; };
        auto v_addr = [&](uint32_t ln) INL { return stg + w * 16384 + (wwarp * 16 + (ln & 7)) * 128 + (((ln >> 3) ^ (ln & 7)) << 4); };
        auto v_off = [&](uint32_t a, const int h) INL { return (a ^ ((h & 1) * 64)) + (h >> 1) * 8192; };
        auto halo_ptr = [&](int mt, int g, int slot, uint32_t ln) INL { return page_ptr<uint4>(512) + (((mt * 8 + g) * 2 + w) * 5 + slot) * 128 + ln; };
        auto pack_k = [&](const float (&acc)[64]) INL {
#pragma unroll
            for (int j = 0; j < 16; j++) { pk[j] = pack_bf16(acc[4 * j], acc[4 * j + 1]); pk[16 + j] = pack_bf16(acc[4 * j + 2], acc[4 * j + 3]); }
        };
        auto unit_export = [&](int cur) INL {
            const uint32_t ln = lane_id();
            uint4* dst = halo_ptr((cur & 7) * 2 + rank, cur >> 3 & 7, wwarp, ln);
            slot_wait(1);
            stage_packed_64x64<32>(slot4, 0, pk);
            stage_packed_64x64<48>(slot4, 8192, pk);
#pragma unroll
            for (int h = 0; h < 4; h++) __stcg(dst + h * 32, make_uint4(pk[16 + h * 4], pk[17 + h * 4], pk[18 + h * 4], pk[19 + h * 4]));
            __syncwarp();
            if (wwarp == 3) {
                const uint32_t va = v_addr(ln) + 1024;
#pragma unroll
                for (int h = 0; h < 4; h++) {
                    uint32_t t[4];
                    ldmatrix_x4_t(v_off(va, h), t);
                    pk[32 + h * 4] = t[0]; pk[33 + h * 4] = t[1]; pk[34 + h * 4] = t[2]; pk[35 + h * 4] = t[3];
                }
#pragma unroll
                for (int h = 0; h < 4; h++) __stcg(dst + 128 + h * 32, make_uint4(pk[32 + h * 4], pk[33 + h * 4], pk[34 + h * 4], pk[35 + h * 4]));
                __syncwarp();
                warp_arrive(hout + w * 8);
            }
        };
        auto unit_import = [&](int cur) INL {
            const uint32_t ln = lane_id();
            const int mt = (cur & 7) * 2 + rank;
            mbar_wait(lready + un * 8, 0);
            un++;
            const uint4* src = halo_ptr(wwarp ? mt : max(mt - 1, 0), cur >> 3 & 7, (wwarp + 3) & 3, ln);
#pragma unroll
            for (int h = 0; h < 4; h++) {
                const uint4 t = __ldcg(src + h * 32);
                pk[32 + h * 4] = t.x; pk[33 + h * 4] = t.y; pk[34 + h * 4] = t.z; pk[35 + h * 4] = t.w;
            }
            if (wwarp) {
                const uint32_t va = v_addr(ln) - 1024;
#pragma unroll
                for (int h = 0; h < 4; h++) {
                    uint32_t t[4];
                    ldmatrix_x4_t(v_off(va, h), t);
                    pk[48 + h * 4] = t[0]; pk[49 + h * 4] = t[1]; pk[50 + h * 4] = t[2]; pk[51 + h * 4] = t[3];
                }
            } else {
#pragma unroll
                for (int h = 0; h < 4; h++) {
                    const uint4 t = __ldcg(src + 128 + h * 32);
                    pk[48 + h * 4] = t.x; pk[49 + h * 4] = t.y; pk[50 + h * 4] = t.z; pk[51 + h * 4] = t.w;
                }
            }
        };
        auto unit_attend = [&](const float (&q)[64], int cur) INL {
            const float cs = 0.17677669529663687f * 1.4426950408889634f;
            const uint32_t ln = lane_id();
            const int g = ln >> 2, c2 = (ln & 3) * 2, mt = (cur & 7) * 2 + rank;
            uint32_t qf[32], vo[8][4];
#pragma unroll
            for (int i = 0; i < 32; i++) qf[i] = pack_bf16(q[2 * i], q[2 * i + 1]);
            fence_regs(qf);
            const float* gp = page_ptr<float>(520) + mt * 128 + wwarp * 32 + g * 2 + w;
            const float lg0 = 1.f - __ldcg(gp), lg1 = 1.f - __ldcg(gp + 16);
            const uint32_t va = stg + w * 16384 + (wwarp * 16 + (ln & 7) + (ln >> 4) * 8) * 128 + ((((ln >> 3) & 1) ^ (ln & 7)) << 4);
#pragma unroll
            for (int i = 0; i < 8; i++) ldmatrix_x4_t((va ^ ((i & 3) * 32)) + (i >> 2) * 8192, vo[i]);
            const bool m0 = c2 > g, m1 = c2 + 1 > g, first = mt + wwarp == 0;
            const uint32_t mk = (m0 ? 0xffffu : 0u) | (m1 ? 0xffff0000u : 0u);
#pragma unroll
            for (int h = 0; h < 4; h++) {
                float s[3][4] = {};
#pragma unroll
                for (int k = 0; k < 2; k++) {
                    const int i = h * 8 + k * 4, j = h * 4 + k * 2;
                    mma_16816(s[0], qf[i], qf[i + 1], qf[i + 2], qf[i + 3], pk[32 + j], pk[33 + j]);
                    mma_16816(s[1], qf[i], qf[i + 1], qf[i + 2], qf[i + 3], pk[j], pk[j + 1]);
                    mma_16816(s[2], qf[i], qf[i + 1], qf[i + 2], qf[i + 3], pk[16 + j], pk[17 + j]);
                }
                if (first) s[0][0] = s[0][1] = -INFINITY;
                float u0 = m0 ? s[0][0] : s[1][0], u1 = m1 ? s[0][1] : s[1][1], v0 = m0 ? s[1][2] : s[2][2], v1 = m1 ? s[1][3] : s[2][3];
                float mu = fmaxf(u0, u1), mv = fmaxf(v0, v1);
                mu = fmaxf(mu, __shfl_xor_sync(0xffffffffu, mu, 1)); mv = fmaxf(mv, __shfl_xor_sync(0xffffffffu, mv, 1));
                mu = fmaxf(mu, __shfl_xor_sync(0xffffffffu, mu, 2)); mv = fmaxf(mv, __shfl_xor_sync(0xffffffffu, mv, 2));
                mu *= -cs; mv *= -cs;
                u0 = ex2(fmaf(u0, cs, mu)); u1 = ex2(fmaf(u1, cs, mu)); v0 = ex2(fmaf(v0, cs, mv)); v1 = ex2(fmaf(v1, cs, mv));
                float lu = u0 + u1, lv = v0 + v1;
                lu += __shfl_xor_sync(0xffffffffu, lu, 1); lv += __shfl_xor_sync(0xffffffffu, lv, 1);
                lu += __shfl_xor_sync(0xffffffffu, lu, 2); lv += __shfl_xor_sync(0xffffffffu, lv, 2);
                const float su = lg0 * rcp(lu), sv = lg1 * rcp(lv);
                const uint32_t pu = pack_bf16(u0 * su, u1 * su), pv = pack_bf16(v0 * sv, v1 * sv);
#pragma unroll
                for (int d = 0; d < 2; d++) {
                    const uint32_t (&vv)[4] = vo[h * 2 + d];
                    float oa[4] = {}, ob[4] = {};
                    mma_16816(oa, pk[48 + h * 4 + d * 2], pk[49 + h * 4 + d * 2], vv[0], vv[1], pu & mk, pu & ~mk);
                    mma_16816(ob, vv[0], vv[1], vv[2], vv[3], pv & mk, pv & ~mk);
                    qf[h * 8 + d * 4] = pack_bf16(oa[0], oa[1]); qf[h * 8 + d * 4 + 1] = pack_bf16(ob[0], ob[1]);
                    qf[h * 8 + d * 4 + 2] = pack_bf16(oa[2], oa[3]); qf[h * 8 + d * 4 + 3] = pack_bf16(ob[2], ob[3]);
                }
            }
#pragma unroll
            for (int i = 0; i < 32; i++) pk[i] = qf[i];
            named_sync(3 + w, 128);
        };
        auto pack_half = [&](const float (&acc)[64], const int OFF, float scale) INL {
#pragma unroll
            for (int i = 0; i < 32; i++) pk[OFF + i] = pack_bf16(acc[2 * i] * scale, acc[2 * i + 1] * scale);
        };
        auto gemm_run = [&]() INL {
                float acc0[64], acc1[64];
#pragma unroll
                for (int i = 0; i < 64; i++) pk[i] = 0;
#pragma unroll
                for (int j = 0; j < 4; j++) asm volatile("xor.b32 %0, %1, %2;" : "=r"(slot4[j]) : "r"(slot_a), "r"(j << 5));
                const uint32_t dA = desc_lo(base + w * 8192, 0), dB = desc_lo(base + 16384, 8192);
                auto wait_full = [&](int st) INL { mbar_wait_hot(gfull + st * 8, gph); };
                auto release = [&](int st) INL { arrive_pair(gempty + st * 8); };
                bool pend = false;
                auto kstep = [&](auto st_, const int Q, bool ending = false) INL {
                    constexpr int st = decltype(st_)::v, OA = st * (G_STAGE >> 4);
                    wait_full(st);
                    if (st == 2) named_sync_if(ending && w, 6, 256);
                    wg_fence();
                    wgmma_ss_n256<OA, OA>(acc0, acc1, dA, dB);
                    wg_commit();
                    wg_wait<1>();
                    release((st + 3) & 3);
                    wg_fence();
                    wgmma_ss_n256<OA + 2, OA + 128>(acc0, acc1, dA, dB);
                    wgmma_ss_n256<OA + 4, OA + 256>(acc0, acc1, dA, dB);
                    if (st == 3) named_arrive_if(ending && !w, 6, 256);
                    wgmma_ss_n256<OA + 6, OA + 384>(acc0, acc1, dA, dB);
                    wg_commit();
                    if (Q >= 0) { stage_quarter(Q); signal(Q); }
                    KTRACE(w);
                };
                wait_full(0);
                GTRACE(w);
                while (true) {
                    wg_fence();
                    wgmma_ss_n256_init(acc0, acc1, dA, dB);
                    wgmma_ss_n256<2, 128>(acc0, acc1, dA, dB);
                    wgmma_ss_n256<4, 256>(acc0, acc1, dA, dB);
                    wgmma_ss_n256<6, 384>(acc0, acc1, dA, dB);
                    wg_commit();
                    KTRACE(w);
                    const int cur = job;
                    const bool is_o = cur >= (T_O << 12), unit2 = (cur >> 6) == 3;
                    const int tail = o_tail(cur);
                    int lim = is_o ? o_head(cur) + tail : (cur < 256 ? 16 : 8);
                    int left = unit2 ? 11 : lim - (is_o ? O_STAGGER + 1 : 1);
                    bool imp = unit2;
                    next_job();
                    if (__builtin_expect(unit2, 0)) { if (tid == TRACE_TID) PTRACE(4); unit_export(cur); if (tid == TRACE_TID) PTRACE(5); }
                    if (pend) {
                        kstep(IC<1>{}, 0);
                        kstep(IC<2>{}, -1);
                        kstep(IC<3>{}, 1);
                        GTRACE(w);
                        gph ^= 1;
                        kstep(IC<0>{}, -1);
                        kstep(IC<1>{}, 2);
                        kstep(IC<2>{}, 3, left == 7);
                        kstep(IC<3>{}, -1, left == 7);
                        GTRACE(w);
                        gph ^= 1;
                        left -= 7;
                        if (left > 0) { kstep(IC<0>{}, -1); left--; }
                    }
                    int last_st = 3;
#pragma unroll 1
                    while (left > 0) {
                        auto ends = [&]() INL -> bool {
                            if (__builtin_expect(--left > 0, 1)) return false;
                            if (is_o) {
                                const uint32_t v = uniform(o_state(olim, lim - tail));
                                const int n = (v >> 1) + ((v & 1) ? 0 : tail);
                                left = n - lim; lim = n;
                            }
                            return left == 0;
                        };
                        kstep(IC<1>{}, -1);
                        if (ends()) { last_st = 1; break; }
                        kstep(IC<2>{}, -1, left == 2 && !is_o && !imp);
                        if (ends()) { last_st = 2; break; }
                        kstep(IC<3>{}, -1, left == 1 && !is_o && !imp);
                        GTRACE(w);
                        gph ^= 1;
                        if (ends()) {
                            if (!imp) break;
                            if (tid == TRACE_TID) PTRACE(6);
                            unit_import(cur);
                            if (tid == TRACE_TID) PTRACE(7);
                            imp = false; left = 4;
                        }
                        kstep(IC<0>{}, -1);
                        if (ends()) { last_st = 0; break; }
                    }
                    if (is_o) {
                        if (w) {
                            wg_wait<0>();
                            release(last_st);
                            named_sync(6, 256);
                        }
#pragma unroll 1
                        for (int i = 1; i <= O_STAGGER; i++) {
                            const int st = (last_st + i) & 3;
                            if (i > 1 && st == 0) gph ^= 1;
                            wait_full(st);
                            const uint32_t a = dA + st * (G_STAGE >> 4), b = dB + st * (G_STAGE >> 4);
                            wg_fence();
                            wgmma_ss_n256<0, 0>(acc0, acc1, a, b);
                            wgmma_ss_n256<2, 128>(acc0, acc1, a, b);
                            wgmma_ss_n256<4, 256>(acc0, acc1, a, b);
                            wgmma_ss_n256<6, 384>(acc0, acc1, a, b);
                            wg_commit();
                            named_arrive_if(!w && i == O_STAGGER, 6, 256);
                            wg_wait<1>();
                            arrive_pair(gempty + last_st * 8, i == 1 && !w);
                        }
                        slot_wait(1);
                        wg_wait<0>();
                        fence_regs(acc0);
                        fence_regs(acc1);
                        auto put = [&](const float (&acc)[64], const int Q, int off) INL {
#pragma unroll
                            for (int j = 0; j < 4; j++) {
                                const float* o = acc + Q * 32 + j * 8;
                                stmatrix_x4(slot4[j] + off, pack_bf16(o[0], o[1]), pack_bf16(o[2], o[3]), pack_bf16(o[4], o[5]), pack_bf16(o[6], o[7]));
                            }
                        };
                        put(acc0, 0, 0);
                        signal(0);
                        put(acc0, 1, 8192);
                        signal(1);
                        put(acc1, 0, -OFF_STG - w * 8192);
                        put(acc1, 1, G_STAGE - OFF_STG - w * 8192);
                        __syncwarp();
                        warp_arrive(tfull + w * 8);
#pragma unroll
                        for (int i = 1; i <= O_STAGGER; i++) release((last_st + i) & 3);
                        GTRACE(w);
#pragma unroll
                        for (int i = 0; i < 64; i++) O[i] = 0.f;
                        break;
                    }
                    if (tid == 128 && !is_o) PTRACE(12);
                    oscale1 = cur < 128 || unit2 ? Q_SCALE : 1.f;
                    ptrans = unit2;
                    if (tid == TRACE_TID && unit2) PTRACE(1);
                    named_arrive_if(w && job >= (T_A << 12), 1, TURN_THREADS);
                    wg_wait<0>();
                    fence_regs(acc0);
                    fence_regs(acc1);
                    release(3);
                    if (tid == TRACE_TID && unit2) PTRACE(2);
                    if (__builtin_expect(unit2, 0)) { unit_attend(acc0, cur); if (tid == TRACE_TID) PTRACE(3); }
                    else if (__builtin_expect((cur >> 6) == 2, 0)) pack_k(acc0);
                    else if (cur < 128) pack_half(acc0, 0, Q_SCALE);
                    else pack_half(acc0, 0, 1.f);
                    if (job >= (T_A << 12)) {
                        stage_pair();
                        signal_both();
#pragma unroll
                        for (int i = 0; i < 64; i++) asm volatile("mov.b32 %0, %1;" : "=f"(O[i]) : "f"(acc1[i]));
                        break;
                    }
                    if (cur < 128 || unit2) pack_half(acc1, 32, Q_SCALE);
                    else pack_half(acc1, 32, 1.f);
                    fence_regs(pk);
                    wait_full(0);
                    pend = (cur >> 6) != 2;
                }
        };
        setup_wait();
#pragma unroll 1
        while (true) {
        gemm_run();
        if (job < 0) break;
        if (tid == 128) PTRACE(11);
        GTRACE(w);
        {
            {
                sph ^= 1;
                uint32_t step = ~0u, ajob = ~0u;
                const int r0 = w * 64 + wwarp * 16 + (lane >> 2);
                float S[64];
                uint32_t P[32] = {};
                fence_regs(P);
                float m0 = 0.f, m1 = 0.f, l0 = 0.25f, l1 = 0.25f, g0 = oscale1, g1 = oscale1, e0 = 0.f, e1 = 0.f;
                constexpr float SUM_MAX = 1.1529215e18f;
                float sum_max = SUM_MAX;
                int rem = 0;
                int maskrem = 0;
                uint32_t starts = 1;
                auto issue_S = [&]() INL {
                    const uint32_t da = desc_lo(base + OFF_Q0 + w * 8192, 0) + (ajob & 1) * ((OFF_Q1 - OFF_Q0) >> 4);
                    const uint32_t db = desc_lo(base + OFF_K0, 0) + (step & 1) * ((OFF_K1 - OFF_K0) >> 4);
                    wg_fence();
                    wgmma_ss_n128_init<0, 0, 0>(S, da, db);
                    wgmma_ss_n128_tb0<2, 2>(S, da, db, 1);
                    wgmma_ss_n128_tb0<4, 4>(S, da, db, 1);
                    wgmma_ss_n128_tb0<6, 6>(S, da, db, 1);
                    wgmma_ss_n128_tb0<1024, 1024>(S, da, db, 1);
                    wgmma_ss_n128_tb0<1026, 1026>(S, da, db, 1);
                    wgmma_ss_n128_tb0<1028, 1028>(S, da, db, 1);
                    wgmma_ss_n128_tb0<1030, 1030>(S, da, db, 1);
                    wg_commit();
                };
                auto issue_PV = [&](uint32_t t, int pass) INL {
                    const uint32_t db = desc_lo(base + OFF_V0, 16384) + (t & 1) * ((OFF_V1 - OFF_V0) >> 4);
                    mbar_wait_hot(vfull + (t & 1) * 8, (t >> 1) & 1);
                    wg_fence();
                    wgmma_rs_n128_tb1<0>(O, P[0], P[1], P[2], P[3], db, !(starts & 2));
                    wgmma_rs_n128_tb1<128>(O, P[4], P[5], P[6], P[7], db, 1);
                    wgmma_rs_n128_tb1<256>(O, P[8], P[9], P[10], P[11], db, 1);
                    wgmma_rs_n128_tb1<384>(O, P[12], P[13], P[14], P[15], db, 1);
                    if (pass) named_arrive(pass, TURN_THREADS);
                    wgmma_rs_n128_tb1<512>(O, P[16], P[17], P[18], P[19], db, 1);
                    wgmma_rs_n128_tb1<640>(O, P[20], P[21], P[22], P[23], db, 1);
                    wgmma_rs_n128_tb1<768>(O, P[24], P[25], P[26], P[27], db, 1);
                    wgmma_rs_n128_tb1<896>(O, P[28], P[29], P[30], P[31], db, 1);
                    wg_commit();
                };
                auto pv_done = [&](uint32_t t) INL {
                    wg_wait<0>();
                    fence_regs(O);
                    arrive_pair(vempty + (t & 1) * 8, t != ~0u);
                };
                auto row_max = [&](float& a0, float& a1) INL {
                    a0 = fmaxf(S[0], S[1]); a1 = fmaxf(S[2], S[3]);
#pragma unroll
                    for (int j = 1; j < 16; j++) {
                        a0 = fmaxf(a0, fmaxf(S[j * 4], S[j * 4 + 1]));
                        a1 = fmaxf(a1, fmaxf(S[j * 4 + 2], S[j * 4 + 3]));
                    }
                    a0 = fmaxf(a0, __shfl_xor_sync(0xffffffffu, a0, 1));
                    a1 = fmaxf(a1, __shfl_xor_sync(0xffffffffu, a1, 1));
                    a0 = fmaxf(a0, __shfl_xor_sync(0xffffffffu, a0, 2));
                    a1 = fmaxf(a1, __shfl_xor_sync(0xffffffffu, a1, 2));
                };
                auto mask_diag = [&]() INL {
                    const int d = (r0 & 63) - (lane & 3) * 2;
                    auto mask_block = [&](const int J0) INL {
                        bool up0 = false, up1 = false;
#pragma unroll
                        for (int j = 0; j < 8; j++) {
                            const bool c0 = j * 8 > d, c1 = j * 8 + 1 > d;
                            if (c0) S[(J0 + j) * 4] = -INFINITY;
                            if (c1) S[(J0 + j) * 4 + 1] = -INFINITY;
                            if (up0) S[(J0 + j) * 4 + 2] = -INFINITY;
                            if (up1) S[(J0 + j) * 4 + 3] = -INFINITY;
                            up0 = c0; up1 = c1;
                        }
                    };
                    if (w) {
                        mask_block(8);
                    } else {
                        mask_block(0);
#pragma unroll
                        for (int i = 32; i < 64; i++) S[i] = -INFINITY;
                    }
                };
                auto exp_part = [&](float& t0, float& t1, const int J0, const int J1, const bool SUB) INL {
#pragma unroll
                    for (int j = J0; j < J1; j++) {
                        const float e0 = ex2(SUB ? S[j * 4] - m0 : S[j * 4]), e1 = ex2(SUB ? S[j * 4 + 1] - m0 : S[j * 4 + 1]);
                        const float e2 = ex2(SUB ? S[j * 4 + 2] - m1 : S[j * 4 + 2]), e3 = ex2(SUB ? S[j * 4 + 3] - m1 : S[j * 4 + 3]);
                        t0 = (j ? t0 : l0) + (e0 + e1);
                        t1 = (j ? t1 : l1) + (e2 + e3);
                        P[j * 2] = pack_bf16(e0, e1);
                        P[j * 2 + 1] = pack_bf16(e2, e3);
                    }
                };
                auto exp_head = [&](float& t0, float& t1, auto j1_) INL {
                    constexpr int J1 = decltype(j1_)::v;
                    float E[J1 * 4];
#pragma unroll
                    for (int j = 0; j < J1; j++) {
#pragma unroll
                        for (int e = 0; e < 4; e++) E[j * 4 + e] = ex2(S[j * 4 + e]);
                        t0 = (j ? t0 : l0) + (E[j * 4] + E[j * 4 + 1]);
                        t1 = (j ? t1 : l1) + (E[j * 4 + 2] + E[j * 4 + 3]);
                    }
                    order_after(t0 + t1, bars + 508);
                    pv_done(step - 1);
                    fence_regs(P);
                    fence_regs(S);
                    fence_regs(E);
#pragma unroll
                    for (int i = 0; i < J1 * 2; i++) P[i] = pack_bf16(E[i * 2], E[i * 2 + 1]);
                };
                auto close_job = [&]() INL {
                    l0 += __shfl_xor_sync(0xffffffffu, l0, 1); l1 += __shfl_xor_sync(0xffffffffu, l1, 1);
                    l0 += __shfl_xor_sync(0xffffffffu, l0, 2); l1 += __shfl_xor_sync(0xffffffffu, l1, 2);
                    e0 = g0 * rcp(l0); e1 = g1 * rcp(l1);
                };
                auto put_O = [&]() INL {
                    mbar_wait_hot(sempty + (w * 2 + 1) * 8, sph ^ 1);
                    uint32_t a[4];
#pragma unroll
                    for (int j = 0; j < 4; j++) asm volatile("xor.b32 %0, %1, %2;" : "=r"(a[j]) : "r"(slot_a), "r"(j << 5));
#pragma unroll
                    for (int q = 0; q < 8; q++) {
                        const float* o = O + q * 8;
                        stmatrix_x4(a[q & 3] + (q >> 2) * 8192, pack_bf16(o[0] * e0, o[1] * e0), pack_bf16(o[2] * e1, o[3] * e1),
                                    pack_bf16(o[4] * e0, o[5] * e0), pack_bf16(o[6] * e1, o[7] * e1));
                    }
                    sph ^= 1;
                    signal_both();
                };
                auto exp_plain = [&](float& t0, float& t1) INL {
                    exp_head(t0, t1, IC<5>{});
                    exp_part(t0, t1, 5, 16, false);
                    fence_regs(P);
                };
                auto exp_diag = [&](float& t0, float& t1) INL {
                    const int d = warp - 4, dd = (r0 & 7) - (int)(slot_a >> 6 & 6);
                    auto tri = [&](const int B) INL {
                        if (0 > dd) S[8 * B] = S[8 * B + 6] = -INFINITY;
                        if (1 > dd) S[8 * B + 1] = S[8 * B + 7] = -INFINITY;
                        S[8 * B + 4] = S[8 * B + 5] = -INFINITY;
                        asm volatile("" ::: "memory");
                    };
                    auto blocks = [&](const int B) INL {
                        auto zero = [&](const int B0) INL {
#pragma unroll
                            for (int i = 4 * B0; i < 4 * B + 12; i++) P[i] = 0;
                            asm volatile("" ::: "memory");
                        };
                        auto block = [&](const int B0) INL { exp_part(t0, t1, 2 * B0, 2 * B0 + 2, false); asm volatile("" ::: "memory"); };
                        if (d < B) zero(B);
                        else {
                            block(B);
                            if (d < B + 1) zero(B + 1);
                            else {
                                block(B + 1);
                                if (d < B + 2) zero(B + 2); else block(B + 2);
                            }
                        }
                    };
                    if (d > 3) {
                        if (d < 6) { if (d == 4) tri(4); else tri(5); } else { if (d == 6) tri(6); else tri(7); }
                        exp_head(t0, t1, IC<5>{});
                        exp_part(t0, t1, 5, 10, false);
                        blocks(5);
                    } else {
                        if (d < 2) { if (d == 0) tri(0); else tri(1); } else { if (d == 2) tri(2); else tri(3); }
                        exp_head(t0, t1, IC<2>{});
#pragma unroll
                        for (int i = 16; i < 32; i++) P[i] = 0;
                        blocks(1);
                    }
                    fence_regs(P);
                };
                auto unsafe_tile = [&](float t0, float t1, bool fresh) INL -> bool {
                    const bool unsafe = !(t0 + t1 <= sum_max) |
                                        (fresh & ((slot_a & 0x180) == 0) & !(fminf(t0, t1) >= 8.6736174e-19f));
                    return __any_sync(0xffffffffu, unsafe);
                };
                auto redo_tile = [&](float& t0, float& t1, bool fresh) INL {
                    wg_wait<0>();
                    fence_regs(O);
                    if (rem == maskrem) mask_diag();
                    float a0, a1;
                    row_max(a0, a1);
                    if (!fresh) { a0 = fmaxf(a0, m0); a1 = fmaxf(a1, m1); }
                    const float c0 = fresh ? 1.f : ex2(m0 - a0), c1 = fresh ? 1.f : ex2(m1 - a1);
                    m0 = a0; m1 = a1; sum_max = -1.f;
                    l0 *= c0; l1 *= c1;
#pragma unroll
                    for (int j = 0; j < 16; j++) { O[j * 4] *= c0; O[j * 4 + 1] *= c0; O[j * 4 + 2] *= c1; O[j * 4 + 3] *= c1; }
                    exp_part(t0, t1, 0, 16, true);
                };
                auto finish = [&]() INL {
                    if (starts & 2) put_O();
                    named_sync(1 + w, TURN_THREADS);
                    TRACE_MARK(0, w, step + 1);
                    issue_PV(step, w == 0 ? 2 : 0);
                    close_job();
                    pv_done(step);
                    put_O();
                };
                auto open_job = [&]() INL {
                    ajob++; rem = (job & 15) + 1; maskrem = (job & 512) ? 0 : job & 15;
                };
                auto do_step = [&]() INL -> bool {
                    float t0, t1;
                    const bool fresh = starts & 1, pending = starts & 2;
                    rem--; step++;
                    named_sync(1 + w, TURN_THREADS);
                    TRACE_MARK(0, w, step);
                    issue_S();
                    if (__builtin_expect(pending || fresh, 0)) {
                        if (pending) put_O();
                        if (fresh) {
                            close_job();
                            g0 = __ldcg(g_gate + (job & 15) * 128 + r0); g1 = __ldcg(g_gate + (job & 15) * 128 + r0 + 8);
                            l0 = 0.f; l1 = 0.f; m0 = 0.f; m1 = 0.f; sum_max = SUM_MAX;
                            if (step == 0) {
                                wg_fence();
                                wg_commit();
                                named_arrive(2 - w, TURN_THREADS);
                                goto issued;
                            }
                        }
                    }
                    issue_PV(step - 1, 2 - w);
                issued:
                    starts = (starts << 1 & 2) | (rem == 0);
                    TRACE_MARK(1, w, step);
                    wg_wait<1>();
                    fence_regs(S);
                    arrive_pair(kempty + (step & 1) * 8);
                    TRACE_MARK(2, w, step);
                    if (__builtin_expect(rem != maskrem, 1)) {
                        exp_plain(t0, t1);
                        if (__builtin_expect(!unsafe_tile(t0, t1, false) && starts == 0, 1)) {
                            l0 = t0; l1 = t1;
                            TRACE_MARK(3, w, step);
                            return true;
                        }
                    } else {
                        exp_diag(t0, t1);
                    }
                    if (unsafe_tile(t0, t1, fresh)) redo_tile(t0, t1, fresh);
                    l0 = t0; l1 = t1;
                    TRACE_MARK(3, w, step);
                    if (rem == 0) {
                        warp_arrive(qempty + (ajob & 1) * 8);
                        next_job();
                        if ((job >> 12) != T_A) return false;
                        open_job();
                    }
                    return true;
                };
                open_job();
#pragma unroll 1
                while (do_step()) {}
                finish();
            }
        }
        GTRACE(w);
        jb = uniform(jb); job = uniform(job); sph = uniform(sph); gph = uniform(gph);
        if (job < 0) break;
        }
    } else {
        reg_dec<40>();
        if (base & 1023) __trap();
        if (warp == 0) {
            const uint2 r = p.first[blockIdx.x];
            const char* maps = reinterpret_cast<const char*>(&p.amap[0]);
            const CUtensorMap* wm = reinterpret_cast<const CUtensorMap*>(maps + (r.x >> (rank ? 8 : 4) & 0x780));
            const CUtensorMap* am = reinterpret_cast<const CUtensorMap*>(maps + (r.x & 0x780));
            const int wb = rank ? r.y >> 16 : r.y & 0xffff;
            setup_wait();
#pragma unroll 1
            for (int st = 1; st < 4; st++) {
                const uint32_t sa = base + st * G_STAGE;
                load_kstep(sa, sa + 16384 + rank * 16384, gfull + st * 8, G_STAGE, wm, st, wb, am, r.x >> 20, st, 1 + (r.x & 1));
            }
            named_sync(7, 96);
        } else {
            if (warp == 2) {
                const int jl = lane < MAX_JOBS ? p.jobs[blockIdx.x][lane] : -1;
                if (lane <= MAX_JOBS) jobs[lane] = jl;
                if ((jl >> 12) == T_O) *reinterpret_cast<volatile uint32_t*>(smem_raw + OFF_BAR + 504) = 2 * o_head(jl);
                if (lane == 31) *reinterpret_cast<volatile uint32_t*>(smem_raw + OFF_BAR + 528) = 0;
            } else if (warp == 3) {
                if (lane == 31) *reinterpret_cast<ulonglong2*>(smem_raw + OFF_BAR + 512) = make_ulonglong2((uint64_t)g_halo, (uint64_t)g_gate);
                if (lane < MAX_ROUNDS / 2) rounds[lane] = reinterpret_cast<const uint32_t*>(p.rounds[blockIdx.x >> 1])[lane];
            }
            named_arrive_if(warp > 1, 7, 96);
            named_sync(0, 352);
            setup_wait();
        }
        volatile uint32_t* epoch_word = reinterpret_cast<volatile uint32_t*>(smem_raw + OFF_BAR + 532);
        uint32_t epoch1 = 0;
        if (warp > 0) {
        if (warp == 3) { epoch1 = uniform(ld_acquire(g_flags + F_DONE)) / NUM_SMS + 1; if (lane == 0) *epoch_word = epoch1; }
        {
            if (warp == 1 && elect_one()) {
#pragma unroll
                for (int i = 0; i < 7; i++) prefetch_map(&p.amap[0] + i);
            }
            __syncwarp();
            if (warp < 3) __nanosleep(jobs[0] < 256 ? GATE_DELAY_LONG_NS : GATE_DELAY_SHORT_NS);
            if (tid == TRACE_GATE) PTRACE(10);
            float* gate_vals = reinterpret_cast<float*>(smem_raw + OFF_BAR + 576);
            if (warp == 3) {
                if (blockIdx.x == 0) g_flags[F_SPLIT + lane] = g_flags[F_TICKET + lane] = 0;
                named_sync(5, 96);
                if (lane < 16 && blockIdx.x + lane * NUM_SMS < SEQ) g_gate[blockIdx.x + lane * NUM_SMS] = 1.f / (1.f + __expf(-gate_vals[lane]));
                if (tid == TRACE_GATE) PTRACE(9);
                __threadfence();
                __syncwarp();
                if (lane == 0) red_release(g_flags + F_GATE);
            } else {
                const uint32_t bar = gatefull + (warp - 1) * 16;
                auto fetch = [&](int r) INL {
                    if (lane == 0) mbar_expect_tx(bar + (r & 2) * 4, 4096);
                    __syncwarp();
                    if (lane < 2) asm volatile("cp.async.bulk.shared::cluster.global.mbarrier::complete_tx::bytes [%0], [%1], 2048, [%2];"
                                               ::"r"(stg + ((warp - 1) * 8 + r + lane) * 2048), "l"(p.xp + (size_t)min((int)blockIdx.x + ((warp - 1) * 8 + r + lane) * NUM_SMS, SEQ - 1) * DM), "r"(bar + (r & 2) * 4) : "memory");
                };
                fetch(0); fetch(2);
                uint32_t gw[16];
#pragma unroll
                for (int i = 0; i < 4; i++) {
                    const uint4 t = __ldg(reinterpret_cast<const uint4*>(p.gate_w) + i * 32 + lane);
                    gw[i * 4] = t.x; gw[i * 4 + 1] = t.y; gw[i * 4 + 2] = t.z; gw[i * 4 + 3] = t.w;
                }
#pragma unroll 1
                for (int r = 0; r < 8; r += 2) {
                    mbar_wait(bar + (r & 2) * 4, r >> 2);
                    if (r < 4) fetch(r + 4);
                    fence_regs(gw);
                    float acc0 = 0.f, acc1 = 0.f;
                    uint32_t ln;
                    asm volatile("mov.u32 %0, %%laneid;" : "=r"(ln));
#pragma unroll
                    for (int i = 0; i < 4; i++) {
                        const uint4* xr = reinterpret_cast<const uint4*>(smem_raw + OFF_STG + ((warp - 1) * 8 + r) * 2048) + i * 32 + ln;
                        const uint4 a = xr[0], c = xr[128];
                        const uint32_t av[4] = {a.x, a.y, a.z, a.w}, cv[4] = {c.x, c.y, c.z, c.w};
#pragma unroll
                        for (int e = 0; e < 4; e++) {
                            const float lo = __uint_as_float(gw[i * 4 + e] << 16), hi = __uint_as_float(gw[i * 4 + e] & 0xffff0000u);
                            acc0 = fmaf(__uint_as_float(av[e] << 16), lo, acc0);
                            acc1 = fmaf(__uint_as_float(cv[e] << 16), lo, acc1);
                            acc0 = fmaf(__uint_as_float(av[e] & 0xffff0000u), hi, acc0);
                            acc1 = fmaf(__uint_as_float(cv[e] & 0xffff0000u), hi, acc1);
                        }
                    }
                    float t = (lane < 16 ? acc0 : acc1) + __shfl_xor_sync(0xffffffffu, lane < 16 ? acc1 : acc0, 16);
#pragma unroll
                    for (int o = 8; o > 0; o >>= 1) t += __shfl_xor_sync(0xffffffffu, t, o);
                    if ((lane & 15) == 0) gate_vals[(warp - 1) * 8 + r + (lane >> 4)] = t;
                }
                uint32_t t2;
                asm volatile("mov.u32 %0, %%tid.x;" : "=r"(t2));
                warp_arrive2(sempty - 16 + (t2 >> 5) * 16, sempty - 8 + (t2 >> 5) * 16);
                named_arrive(5, 96);
                if (tid == TRACE_GATE) PTRACE(9);
            }
            if (tid == TRACE_GATE) PTRACE(8);
        }
        if (warp < 3) {
            if (elect_one()) {
                const int w = warp - 1;
                uint32_t qn = 0, un = 0;
                prefetch_map(&p.qkv_st); prefetch_map(&p.st_par);
                for (int jb = 0; jb < MAX_JOBS; jb++) {
                    const int job = jobs[jb];
                    if (job < 0) break;
                    const int type = job >> 12, pl = type == T_O ? o_state(otile, 0) >> 1 : job & 0xFFF;
                    const CUtensorMap* map = &p.qkv_st;
                    int nq = 4, mt, ob0, ob1, flag, flag2 = -1;
                    bool par = false;
                    if (type <= T_O) {
                        const int n = pl >> 3;
                        mt = (pl & 7) * 2 + rank;
                        if (type == T_O)  {
                            map = &p.out_st; ob0 = (n & 3) * 4; ob1 = ob0 + 2; flag = -1;
                            for (uint32_t tries = 0; (int32_t)(ld_acquire(g_flags + F_OUT + pl * 2 + rank) - *epoch_word) < 0; tries++) {
                                __nanosleep(300);
                                if (tries > (1u << 22)) __trap();
                            }
                            fence_async_global();
                        }
                        else if (n < 16)  { ob0 = n * 4; ob1 = ob0 + 2; flag = F_Q + n * 32 + mt; flag2 = flag + 16; }
                        else if (n < 24)  {
                            mbar_wait(hout + w * 8, un++ & 1);
                            nq = ob0 = ob1 = 0; flag = F_H + mt * 8 + (n & 7);
                        } else if (n < 32) {
                            par = true; ob0 = 192 + (n & 7) * 2; ob1 = unit_head(n & 7) * 2;
                            flag = F_CTX + mt * 40 + 32 + (n & 7); flag2 = F_Q + ob1 * 8 + mt;
                        } else            { ob0 = n * 2; ob1 = ob0 + 64; flag = F_KV + (n - 32) * 16 + mt; }
                    } else {
                        nq = 2; mt = pl & 15; ob0 = ob1 = ((pl >> 4) & 31) * 2; flag = F_CTX + mt * 40 + ((pl >> 4) & 31);
                    }
                    for (int q = 0; q < nq; q++, qn++) {
                        const uint32_t slot = w * 2 + (qn & 1);
                        const int blk = (q < 2 ? ob0 : ob1) + (q & 1);
                        if (type == T_O && q == 2) {
                            mbar_wait(tfull + w * 8, 0);
                            fence_async_smem();
                            tma_reduce_add_3d(map, base + w * 8192, 0, mt * 128 + w * 64, ob1);
                            tma_reduce_add_3d(map, base + G_STAGE + w * 8192, 0, mt * 128 + w * 64, ob1 + 1);
                            bulk_commit();
                            break;
                        }
                        mbar_wait(sfull + slot * 8, (qn >> 1) & 1);
                        fence_async_smem();
                        if (type == T_O) {
                            tma_reduce_add_3d(map, stg + slot * 8192, 0, mt * 128 + w * 64, blk);
                        } else if (par) {
                            tma_store_par(&p.st_par, stg + slot * 8192, mt * 64, w, blk);
                        } else {
                            tma_store_3d(map, stg + slot * 8192, 0, mt * 128 + w * 64, blk, POL_STREAM);
                        }
                        bulk_commit();
                        if (type == T_O) continue;
                        if (!(q & 1)) continue;
                        bulk_wait_read<1>();
                        mbar_arrive(sempty + (slot ^ 1) * 8);
                        bulk_wait_read<0>();
                        mbar_arrive(sempty + slot * 8);
                    }
                    bulk_wait<0>();
                    END_MARK(jb);
                    if (flag >= 0) {
                        asm volatile("fence.release.gpu;" ::: "memory");
                        red_relaxed(g_flags + flag);
                        if (flag2 >= 0) red_relaxed(g_flags + flag2);
                    }
                }
            }
        } else {
            int jb = 0;
            for (int un = 0; (jobs[jb] >> 12) == T_P; jb++) {
                const int n = jobs[jb] >> 3, mt = (jobs[jb] & 7) * 2 + rank;
                if ((n >> 3) != 3) continue;
                wait_flags<200>(lane == 31 || (lane == 0 && mt > 0), lane == 31 ? F_GATE : F_H + max(mt - 1, 0) * 8 + (n & 7),
                                epoch1 * (lane == 31 ? GATE_COUNT : 2));
                if (lane == 0) mbar_arrive(lready + un * 8);
                un++;
            }
            if ((jobs[jb] >> 12) != T_A) {
                wait_flags<200>(lane == 0, F_GATE, epoch1 * GATE_COUNT);
                if (lane == 0) { mbar_arrive(aready); red_relaxed(g_flags + F_DONE); }
            } else {
                const int jh = jobs[jb] >> 4 & 31, jq = jobs[jb] & 15;
                wait_flags<100>(lane <= jq || lane >= 30, lane == 31 ? F_GATE : (lane == 30 ? F_Q + jh * 16 + jq : F_KV + jh * 16 + (lane & 15)),
                                epoch1 * (lane == 31 ? GATE_COUNT : 2));
                if (lane == 0) { mbar_arrive(aready); red_relaxed(g_flags + F_DONE); }
            int left = 0, nxt = jobs[jb];
            uint32_t ajob = 0;
#pragma unroll 1
            for (uint32_t astep = 0;; astep++) {
                if (left == 0) {
                    if ((nxt >> 12) != T_A) break;
                    left = (nxt & 15) + 1;
                    nxt = jobs[++jb];
                    mbar_wait(qfull + (ajob & 1) * 8, (ajob >> 1) & 1);
                    ajob++;
                }
                left--;
                mbar_wait(kfull + (astep & 1) * 8, (astep >> 1) & 1);
                named_sync(1, TURN_THREADS);
                named_sync(2, TURN_THREADS);
            }
            named_sync(1, TURN_THREADS);
            named_sync(2, TURN_THREADS);
            }
            if (jobs[jb] == (T_O << 12)) {
                mbar_wait(gatefull, 0);
                const int tile = o_state(otile, 0) >> 1;
                uint4* dst = reinterpret_cast<uint4*>(p.out) + ((tile & 7) * 256 + rank * 128) * (DM / 8) + (tile >> 3) * 32 + lane;
#pragma unroll 4
                for (int r = 0; r < 128; r++) {
                    dst[r * (DM / 8)] = make_uint4(0, 0, 0, 0);
                    if ((r & 3) == 3) __nanosleep(CLEAR_GAP_NS);
                }
                __threadfence();
                fence_async_global();
                __syncwarp();
                if (lane == 0) red_release(g_flags + F_OUT + tile * 2 + rank);
            }
        }
        } else {
            uint32_t gph = 1;
            int vrow = 0, vblk = 0;
            bool vsolo = false;
            auto load_kv = [&](uint32_t dst, uint32_t bar, int row, int blk, bool solo) INL {
                load_operand(dst, bar, &p.qkv_ld, &p.qkv_half, row, blk, rank, solo, POL_NORMAL);
            };
            auto load_v = [&](uint32_t t) INL {
                if (t == 0) mbar_wait(gempty + 24, gph);
                mbar_wait(vempty + (t & 1) * 8, ((t >> 1) & 1) ^ 1);
                load_kv(base + ((t & 1) ? OFF_V1 : OFF_V0), vfull + (t & 1) * 8, vrow, vblk, vsolo);
            };
            int jb = __ffs(__ballot_sync(0xffffffffu, lane <= MAX_JOBS && (jobs[min(lane, MAX_JOBS)] >> 12) != T_P)) - 1;
            int cur = uniform(jobs[jb]);
            auto announce = [&](uint32_t word, uint32_t v) INL {
                asm volatile("{\n.reg .pred p;\nsetp.lt.u32 p, %2, 2;\n@p red.relaxed.cluster.shared::cluster.max.u32 [%0], %1;\n}"
                             ::"r"(mapa(word, lane & 1)), "r"(v), "r"(lane) : "memory");
                __syncwarp();
            };
            uint32_t ticket = 0;
            auto draw_ticket = [&](int ojob) INL {
                asm volatile("{\n.reg .pred p;\nsetp.ne.u32 p, %2, 0;\n@p atom.relaxed.gpu.global.inc.u32 %0, [%1], 0x7fffffff;\n}"
                             : "+r"(ticket) : "l"(g_flags + F_TICKET + (ojob >> 5 & 1)), "r"((uint32_t)(rank == 0 && lane == 0)) : "memory");
                __syncwarp();
            };
            int pl = 0;
            uint32_t seen_a = 0, seen_b = 0;
            auto ask_ctx = [&]() INL {
                const uint32_t* f = g_flags + F_CTX + ((pl & 7) * 2 + rank) * 40;
                seen_a = ld_relaxed(f + lane); seen_b = ld_relaxed(f + 32 + (lane & 7));
            };
            auto open_tile = [&](int ojob) INL {
                if (rank == 0) {
                    const uint32_t t = uniform(ticket);
                    announce(otile, 2 * ((ojob & 32) ? 31 - t : t) + 1);
                }
                pl = (ojob & 32) | uniform(o_state(otile, 0) >> 1);
                ask_ctx();
            };
            const uint16_t* recs = reinterpret_cast<const uint16_t*>(rounds);
            uint32_t rec = uniform(recs[0]), nrec = uniform(recs[1]);
            int st0 = 4;
#pragma unroll 1
            for (int r = 2; rec != 0xFFFF; r++) {
                const uint32_t nnrec = recs[r];
                load_round(rec, st0, gph);
                gph ^= 1;
                st0 = 0;
                rec = nrec; nrec = uniform(nnrec);
                if (nrec == 0xFFFF || (rec & 8192)) {
                    if (nrec != 0xFFFF) {
                        prefetch_map(&p.qkv_ld); prefetch_map(&p.qkv_half);
                        if ((cur >> 12) == T_O) { prefetch_map(&p.wo_a); prefetch_map(&p.wo_b); prefetch_map(&p.out_st); }
                    } else if ((cur >> 12) == T_O) {
                        if (rec != 0xFFFF) {
                            mbar_wait(aready, 0);
                            draw_ticket(cur);
                        } else {
                            open_tile(cur);
                        }
                    }
                }
            }
            int nxt = cur;
            uint32_t astep = 0;
            if ((cur >> 12) == T_A) {
            {
                const int jh = cur >> 4 & 31, jq = cur & 15, j0 = (cur & 512) ? 0 : jq;
                mbar_wait(aready, 0);
                fence_async_global();
                mbar_wait(gempty, gph);
                load_operand(base + OFF_Q0, qfull, &p.qkv_ld, &p.qkv_ld, jq * 128, jh * 2, 0, true, POL_STREAM);
                PTRACE(17);
                mbar_wait(gempty + 8, gph);
                load_kv(base + OFF_K0, kfull, j0 * 128, 64 + jh * 2, j0 == jq && (jq & 1));
                PTRACE(16);
            }
            epoch1 = *epoch_word;
            jb++;
            nxt = uniform(jobs[jb]);
            int i = 0;
            uint32_t ajob = 1;
            bool q_issued = false;
#pragma unroll 1
            while (true) {
                const int qt = cur & 15;
                const bool last = i == qt;
                const int j = (cur & 512) ? i : qt - i, blk = (cur >> 4 & 31) * 2;
                const bool solo = j == qt && (qt & 1);
                {
                    const uint32_t sl = astep & 1;
                    if (astep == 0) {
                        mbar_wait(gempty + 16, gph);
                    } else {
                        mbar_wait(kempty + sl * 8, ((astep >> 1) & 1) ^ 1);
                        load_kv(base + (sl ? OFF_K1 : OFF_K0), kfull + sl * 8, j * 128, 64 + blk, solo);
                        if (astep == 1) PTRACE(14);
                        load_v(astep - 1);
                        if (astep == 1) PTRACE(15);
                    }
                }
                vrow = j * 128; vblk = 128 + blk; vsolo = solo;
                astep++;
                if ((nxt >> 12) != T_A) {
                    if (last) break;
                } else if (!q_issued && (last || i == 2 || (i > 2 && i >= qt - 2))) {
                    const int jh = nxt >> 4 & 31, jq = nxt & 15;
                    q_issued = wait_flags(lane <= jq || lane >= 30, lane == 31 ? F_GATE : (lane == 30 ? F_Q + jh * 16 + jq : F_KV + jh * 16 + (lane & 15)),
                                          epoch1 * (lane == 31 ? GATE_COUNT : 2), last);
                    if (q_issued) {
                        mbar_wait(qempty + (ajob & 1) * 8, ((ajob >> 1) & 1) ^ 1);
                        load_operand(base + ((ajob & 1) ? OFF_Q1 : OFF_Q0), qfull + (ajob & 1) * 8, &p.qkv_ld, &p.qkv_ld, jq * 128, jh * 2, 0, true, POL_STREAM);
                    }
                }
                i++;
                if (last) {
                    cur = nxt; jb++; nxt = uniform(jobs[jb]); i = 0; ajob++; q_issued = false;
                    if ((nxt >> 12) == T_O) { prefetch_map(&p.wo_a); prefetch_map(&p.wo_b); prefetch_map(&p.out_st); }
                }
            }
            if (nxt >= 0) draw_ticket(nxt);
            load_v(astep - 1);
            if (nxt >= 0) open_tile(nxt);
            }
            int nks = 0;
            if (nxt >= 0) {
                epoch1 = *epoch_word;
                const int m0 = (pl & 7) * 256 + rank * 128, nb = (pl >> 3 & 3) * 4 + rank * 2, part = pl >> 5 & 1;
                uint32_t ready_a = 0, ready_b = 0;
                uint32_t claim_even = 0, claim_odd = 0;
                const int head = o_head(pl), tail = o_tail(pl);
                int lim = head;
                bool known = false;
#pragma unroll 1
                for (int ks = 0;; ks++) {
                    const int st = ks & 3;
                    if (rank == 0) {
                        auto exchange = [&](uint32_t& claim) INL {
                            if (ks + 1 >= head) {
                                known = (uint32_t)uniform(claim) >= O_FLEX;
                                if (!known) lim = ks + 2;
                                announce(olim, known ? 2 * (lim + tail) + 1 : 2 * lim);
                            }
                            asm volatile("{\n.reg .pred p;\nsetp.ne.u32 p, %2, 0;\n@p atom.relaxed.gpu.global.inc.u32 %0, [%1], 0x7fffffff;\n}"
                                         : "+r"(claim) : "l"(g_flags + F_SPLIT + (pl & 31)), "r"((uint32_t)(!known && lane == 0)) : "memory");
                            __syncwarp();
                        };
                        if (!known && ks + 3 >= head) { if (ks & 1) exchange(claim_odd); else exchange(claim_even); }
                    } else if (!known && ks >= lim) {
                        const uint32_t v = uniform(o_state(olim, ks));
                        known = v & 1;
                        lim = (v >> 1) - (known ? tail : 0);
                    }
                    if (ks >= lim + tail) { nks = ks; break; }
                    if (ks == CLEAR_KS && !part) warp_arrive(gatefull);
                    int acol;
                    if (ks >= lim) acol = (part ? 64 - O_T1 : 200) + ks - lim;
                    else if (part) acol = ks < O_H1 ? O_F0 + ks : O_F0 + 2 * O_H1 + O_FLEX - 1 - ks;
                    else acol = ks < 8 ? 192 + ks : (ks < O_H0 ? ks - 8 : ks - 8 + O_H1);
                    for (uint32_t tries = 0; !(((acol < 192 ? ready_a : ready_b) >> (acol >> 1 & 31)) & 1); tries++) {
                        if (ks | tries) ask_ctx();
                        ready_a = __ballot_sync(0xffffffffu, (int32_t)(seen_a - epoch1 * 2) >= 0);
                        ready_b = __ballot_sync(0xffffffffu, (int32_t)(seen_b - epoch1 * 2) >= 0);
                        fence_acquire();
                        trap_if(tries > (1u << 22));
                    }
                    {
                        const uint32_t sa = base + st * G_STAGE;
                        if (ks < 4 && astep) mbar_wait((ks < 2 ? kempty : vempty) + ((astep - 1) & 1) * 8, ((astep - 1) >> 1) & 1);
                        else mbar_wait(gempty + st * 8, gph);
                        load_kstep(sa, sa + 16384 + rank * 16384, gfull + st * 8, G_STAGE, acol >= 192 ? &p.wo_b : &p.wo_a, acol & 63, nb,
                                   &p.qkv_half, m0, acol, 1);
                    }
                    if (st == 3) gph ^= 1;
                }
            }
            if (lane == 0) {
                if (nxt >= 0) for (int s = 0; s < 4; s++) mbar_wait(gempty + s * 8, gph ^ (s < (nks & 3)));
                else for (uint32_t t = astep; t < astep + 2; t++) {
                    mbar_wait(kempty + (t & 1) * 8, ((t >> 1) & 1) ^ 1);
                    mbar_wait(vempty + (t & 1) * 8, ((t >> 1) & 1) ^ 1);
                }
            }
        }
    }
}

typedef CUresult (*EncodeFn)(CUtensorMap*, CUtensorMapDataType, cuuint32_t, void*, const cuuint64_t*, const cuuint64_t*,
                             const cuuint32_t*, const cuuint32_t*, CUtensorMapInterleave, CUtensorMapSwizzle,
                             CUtensorMapL2promotion, CUtensorMapFloatOOBfill);

void make_map3(EncodeFn enc, CUtensorMap* m, const void* ptr, int rows, int cols, int box_rows, int box_blks, bool blocked = false) {
    cuuint64_t dims[3] = {64, (cuuint64_t)rows, (cuuint64_t)(cols / 64)};
    cuuint64_t strides[2] = {blocked ? 128 : (cuuint64_t)cols * 2, blocked ? (cuuint64_t)rows * 128 : 128};
    cuuint32_t box[3] = {64, (cuuint32_t)box_rows, (cuuint32_t)box_blks};
    cuuint32_t es[3] = {1, 1, 1};
    enc(m, CU_TENSOR_MAP_DATA_TYPE_BFLOAT16, 3, const_cast<void*>(ptr), dims, strides, box, es, CU_TENSOR_MAP_INTERLEAVE_NONE,
        CU_TENSOR_MAP_SWIZZLE_128B, CU_TENSOR_MAP_L2_PROMOTION_L2_256B, CU_TENSOR_MAP_FLOAT_OOB_FILL_NONE);
}

Params h_params;

const int16_t k_jobs[NUM_SMS][MAX_JOBS] = {
    {339,153,217,8890,8339,8802,8311,9042,8405,9008,8551,9134,8677,4128,-1,-1,-1,-1,-1,-1,-1,-1,-1,-1},
    {339,153,217,8891,8338,8803,8310,9043,8404,9009,8550,9135,8676,4128,-1,-1,-1,-1,-1,-1,-1,-1,-1,-1},
    {40,0,307,8888,8289,8720,8259,8854,8539,8898,8627,8998,8655,4128,-1,-1,-1,-1,-1,-1,-1,-1,-1,-1},
    {40,0,307,8889,8288,8721,8258,8855,8538,8899,8626,8999,8654,4128,-1,-1,-1,-1,-1,-1,-1,-1,-1,-1},
    {10,157,221,8706,8269,8820,8457,9006,8687,4128,-1,-1,-1,-1,-1,-1,-1,-1,-1,-1,-1,-1,-1,-1},
    {10,157,221,8707,8268,8821,8456,9007,8686,4128,-1,-1,-1,-1,-1,-1,-1,-1,-1,-1,-1,-1,-1,-1},
    {132,196,296,8730,8333,8940,8503,9082,8697,4128,-1,-1,-1,-1,-1,-1,-1,-1,-1,-1,-1,-1,-1,-1},
    {132,196,296,8731,8332,8941,8502,9083,8696,4128,-1,-1,-1,-1,-1,-1,-1,-1,-1,-1,-1,-1,-1,-1},
    {128,192,8758,8199,8774,8313,9026,8415,9130,8663,4128,-1,-1,-1,-1,-1,-1,-1,-1,-1,-1,-1,-1,-1},
    {128,192,8759,8198,8775,8312,9027,8414,9131,8662,4128,-1,-1,-1,-1,-1,-1,-1,-1,-1,-1,-1,-1,-1},
    {133,197,8742,8369,8704,8285,8768,8543,9022,8601,4128,-1,-1,-1,-1,-1,-1,-1,-1,-1,-1,-1,-1,-1},
    {133,197,8743,8368,8705,8284,8769,8542,9023,8600,4128,-1,-1,-1,-1,-1,-1,-1,-1,-1,-1,-1,-1,-1},
    {131,195,38,8708,8265,8932,8461,8896,8631,9076,8585,4128,-1,-1,-1,-1,-1,-1,-1,-1,-1,-1,-1,-1},
    {131,195,38,8709,8264,8933,8460,8897,8630,9077,8584,4128,-1,-1,-1,-1,-1,-1,-1,-1,-1,-1,-1,-1},
    {137,201,8750,8331,8816,8533,8912,8411,9078,8671,4128,-1,-1,-1,-1,-1,-1,-1,-1,-1,-1,-1,-1,-1},
    {137,201,8751,8330,8817,8532,8913,8410,9079,8670,4128,-1,-1,-1,-1,-1,-1,-1,-1,-1,-1,-1,-1,-1},
    {43,264,440,8744,8201,8858,8417,8954,8483,9016,8649,9152,8691,4128,-1,-1,-1,-1,-1,-1,-1,-1,-1,-1},
    {43,264,440,8745,8200,8859,8416,8955,8482,9017,8648,9153,8690,4128,-1,-1,-1,-1,-1,-1,-1,-1,-1,-1},
    {151,215,8876,8299,8964,8445,9146,8703,4128,-1,-1,-1,-1,-1,-1,-1,-1,-1,-1,-1,-1,-1,-1,-1},
    {151,215,8877,8298,8965,8444,9147,8702,4128,-1,-1,-1,-1,-1,-1,-1,-1,-1,-1,-1,-1,-1,-1,-1},
    {470,5,159,223,8772,8281,8936,8407,9066,8651,4128,-1,-1,-1,-1,-1,-1,-1,-1,-1,-1,-1,-1,-1},
    {470,5,159,223,8773,8280,8937,8406,9067,8650,4128,-1,-1,-1,-1,-1,-1,-1,-1,-1,-1,-1,-1,-1},
    {136,200,444,8760,8275,8848,8477,9040,8525,9148,8681,4128,-1,-1,-1,-1,-1,-1,-1,-1,-1,-1,-1,-1},
    {136,200,444,8761,8274,8849,8476,9041,8524,9149,8680,4128,-1,-1,-1,-1,-1,-1,-1,-1,-1,-1,-1,-1},
    {46,510,462,310,8764,8293,8862,8439,9064,8653,4128,-1,-1,-1,-1,-1,-1,-1,-1,-1,-1,-1,-1,-1},
    {46,510,462,310,8765,8292,8863,8438,9065,8652,4128,-1,-1,-1,-1,-1,-1,-1,-1,-1,-1,-1,-1,-1},
    {145,209,8894,8335,8942,8485,9098,8695,4128,-1,-1,-1,-1,-1,-1,-1,-1,-1,-1,-1,-1,-1,-1,-1},
    {145,209,8895,8334,8943,8484,9099,8694,4128,-1,-1,-1,-1,-1,-1,-1,-1,-1,-1,-1,-1,-1,-1,-1},
    {140,204,8878,8329,8934,8441,9070,8685,4128,-1,-1,-1,-1,-1,-1,-1,-1,-1,-1,-1,-1,-1,-1,-1},
    {140,204,8879,8328,8935,8440,9071,8684,4128,-1,-1,-1,-1,-1,-1,-1,-1,-1,-1,-1,-1,-1,-1,-1},
    {146,210,504,8884,8301,8966,8527,9128,8603,4128,-1,-1,-1,-1,-1,-1,-1,-1,-1,-1,-1,-1,-1,-1},
    {146,210,504,8885,8300,8967,8526,9129,8602,4128,-1,-1,-1,-1,-1,-1,-1,-1,-1,-1,-1,-1,-1,-1},
    {14,6,8868,8245,8806,8267,8938,8547,9000,8611,9108,8643,4128,-1,-1,-1,-1,-1,-1,-1,-1,-1,-1,-1},
    {14,6,8869,8244,8807,8266,8939,8546,9001,8610,9109,8642,4128,-1,-1,-1,-1,-1,-1,-1,-1,-1,-1,-1},
    {144,208,8748,8211,8836,8463,9004,8591,4128,-1,-1,-1,-1,-1,-1,-1,-1,-1,-1,-1,-1,-1,-1,-1},
    {144,208,8749,8210,8837,8462,9005,8590,4128,-1,-1,-1,-1,-1,-1,-1,-1,-1,-1,-1,-1,-1,-1,-1},
    {12,4,8740,8243,8724,8287,8930,8435,8900,8517,9086,8659,4128,-1,-1,-1,-1,-1,-1,-1,-1,-1,-1,-1},
    {12,4,8741,8242,8725,8286,8931,8434,8901,8516,9087,8658,4128,-1,-1,-1,-1,-1,-1,-1,-1,-1,-1,-1},
    {143,207,8866,8353,8752,8205,8830,8409,9056,8561,9140,8581,9104,8679,4128,-1,-1,-1,-1,-1,-1,-1,-1,-1},
    {143,207,8867,8352,8753,8204,8831,8408,9057,8560,9141,8580,9105,8678,4128,-1,-1,-1,-1,-1,-1,-1,-1,-1},
    {147,211,8872,8297,8834,8459,9030,8437,9100,8665,4128,-1,-1,-1,-1,-1,-1,-1,-1,-1,-1,-1,-1,-1},
    {147,211,8873,8296,8835,8458,9031,8436,9101,8664,4128,-1,-1,-1,-1,-1,-1,-1,-1,-1,-1,-1,-1,-1},
    {41,1,8766,8327,8828,8399,9126,8667,4128,-1,-1,-1,-1,-1,-1,-1,-1,-1,-1,-1,-1,-1,-1,-1},
    {41,1,8767,8326,8829,8398,9127,8666,4128,-1,-1,-1,-1,-1,-1,-1,-1,-1,-1,-1,-1,-1,-1,-1},
    {150,214,8882,8223,8832,8473,8980,8413,9094,8669,4128,-1,-1,-1,-1,-1,-1,-1,-1,-1,-1,-1,-1,-1},
    {150,214,8883,8222,8833,8472,8981,8412,9095,8668,4128,-1,-1,-1,-1,-1,-1,-1,-1,-1,-1,-1,-1,-1},
    {141,205,33,8726,8341,8976,8479,9024,8449,9136,8501,9144,8683,4128,-1,-1,-1,-1,-1,-1,-1,-1,-1,-1},
    {141,205,33,8727,8340,8977,8478,9025,8448,9137,8500,9145,8682,4128,-1,-1,-1,-1,-1,-1,-1,-1,-1,-1},
    {277,405,152,216,8718,8475,8902,8403,9150,8661,4128,-1,-1,-1,-1,-1,-1,-1,-1,-1,-1,-1,-1,-1},
    {277,405,152,216,8719,8474,8903,8402,9151,8660,4128,-1,-1,-1,-1,-1,-1,-1,-1,-1,-1,-1,-1,-1},
    {139,203,8886,8203,8856,8433,9032,8393,9080,8599,4128,-1,-1,-1,-1,-1,-1,-1,-1,-1,-1,-1,-1,-1},
    {139,203,8887,8202,8857,8432,9033,8392,9081,8598,4128,-1,-1,-1,-1,-1,-1,-1,-1,-1,-1,-1,-1,-1},
    {149,213,8746,8303,8982,8397,9084,8645,4128,-1,-1,-1,-1,-1,-1,-1,-1,-1,-1,-1,-1,-1,-1,-1},
    {149,213,8747,8302,8983,8396,9085,8644,4128,-1,-1,-1,-1,-1,-1,-1,-1,-1,-1,-1,-1,-1,-1,-1},
    {138,202,8870,8221,8860,8395,9060,8607,4128,-1,-1,-1,-1,-1,-1,-1,-1,-1,-1,-1,-1,-1,-1,-1},
    {138,202,8871,8220,8861,8394,9061,8606,4128,-1,-1,-1,-1,-1,-1,-1,-1,-1,-1,-1,-1,-1,-1,-1},
    {134,198,8738,8225,8728,8283,8962,8541,8992,8499,9074,8609,9124,8595,9184,8693,4128,-1,-1,-1,-1,-1,-1,-1},
    {134,198,8739,8224,8729,8282,8963,8540,8993,8498,9075,8608,9125,8594,9185,8692,4128,-1,-1,-1,-1,-1,-1,-1},
    {142,206,8874,8271,8818,8447,9068,8647,4128,-1,-1,-1,-1,-1,-1,-1,-1,-1,-1,-1,-1,-1,-1,-1},
    {142,206,8875,8270,8819,8446,9069,8646,4128,-1,-1,-1,-1,-1,-1,-1,-1,-1,-1,-1,-1,-1,-1,-1},
    {47,498,506,306,8892,8277,8784,8467,9048,8535,9020,8579,9088,8657,9186,8689,4128,-1,-1,-1,-1,-1,-1,-1},
    {47,498,506,306,8893,8276,8785,8466,9049,8534,9021,8578,9089,8656,9187,8688,4128,-1,-1,-1,-1,-1,-1,-1},
    {148,212,8762,8279,8826,8523,9002,8605,4128,-1,-1,-1,-1,-1,-1,-1,-1,-1,-1,-1,-1,-1,-1,-1},
    {148,212,8763,8278,8827,8522,9003,8604,4128,-1,-1,-1,-1,-1,-1,-1,-1,-1,-1,-1,-1,-1,-1,-1},
    {276,404,268,500,450,490,374,390,430,380,356,412,168,232,9018,8701,-1,-1,-1,-1,-1,-1,-1,-1},
    {276,404,268,500,450,490,374,390,430,380,356,412,168,232,9019,8700,-1,-1,-1,-1,-1,-1,-1,-1},
    {11,403,459,507,329,393,369,377,417,361,433,167,231,9132,8699,-1,-1,-1,-1,-1,-1,-1,-1,-1},
    {11,403,459,507,329,393,369,377,417,361,433,167,231,9133,8698,-1,-1,-1,-1,-1,-1,-1,-1,-1},
    {350,486,502,262,302,334,318,87,52,100,179,243,4096,-1,-1,-1,-1,-1,-1,-1,-1,-1,-1,-1},
    {350,486,502,262,302,334,318,87,52,100,179,243,4096,-1,-1,-1,-1,-1,-1,-1,-1,-1,-1,-1},
    {340,158,222,492,60,108,76,172,236,4096,-1,-1,-1,-1,-1,-1,-1,-1,-1,-1,-1,-1,-1,-1},
    {340,158,222,492,60,108,76,172,236,4096,-1,-1,-1,-1,-1,-1,-1,-1,-1,-1,-1,-1,-1,-1},
    {42,3,35,59,107,360,408,181,245,4096,-1,-1,-1,-1,-1,-1,-1,-1,-1,-1,-1,-1,-1,-1},
    {42,3,35,59,107,360,408,181,245,4096,-1,-1,-1,-1,-1,-1,-1,-1,-1,-1,-1,-1,-1,-1},
    {45,156,220,396,85,109,93,180,244,4096,-1,-1,-1,-1,-1,-1,-1,-1,-1,-1,-1,-1,-1,-1},
    {45,156,220,396,85,109,93,180,244,4096,-1,-1,-1,-1,-1,-1,-1,-1,-1,-1,-1,-1,-1,-1},
    {466,482,266,258,37,69,53,77,183,247,4096,-1,-1,-1,-1,-1,-1,-1,-1,-1,-1,-1,-1,-1},
    {466,482,266,258,37,69,53,77,183,247,4096,-1,-1,-1,-1,-1,-1,-1,-1,-1,-1,-1,-1,-1},
    {471,407,463,442,290,322,314,386,478,382,366,414,182,246,4096,-1,-1,-1,-1,-1,-1,-1,-1,-1},
    {471,407,463,442,290,322,314,386,478,382,366,414,182,246,4096,-1,-1,-1,-1,-1,-1,-1,-1,-1},
    {469,349,485,501,445,333,317,373,477,423,439,415,173,237,4096,-1,-1,-1,-1,-1,-1,-1,-1,-1},
    {469,349,485,501,445,333,317,373,477,423,439,415,173,237,4096,-1,-1,-1,-1,-1,-1,-1,-1,-1},
    {8,269,309,453,449,489,385,425,422,358,92,188,252,4096,-1,-1,-1,-1,-1,-1,-1,-1,-1,-1},
    {8,269,309,453,449,489,385,425,422,358,92,188,252,4096,-1,-1,-1,-1,-1,-1,-1,-1,-1,-1},
    {343,287,487,263,303,455,495,391,51,91,160,224,4096,-1,-1,-1,-1,-1,-1,-1,-1,-1,-1,-1},
    {343,287,487,263,303,455,495,391,51,91,160,224,4096,-1,-1,-1,-1,-1,-1,-1,-1,-1,-1,-1},
    {464,272,480,456,288,488,392,61,379,363,435,176,240,4096,-1,-1,-1,-1,-1,-1,-1,-1,-1,-1},
    {464,272,480,456,288,488,392,61,379,363,435,176,240,4096,-1,-1,-1,-1,-1,-1,-1,-1,-1,-1},
    {336,280,400,256,448,320,312,384,424,416,352,432,472,171,235,4096,-1,-1,-1,-1,-1,-1,-1,-1},
    {336,280,400,256,448,320,312,384,424,416,352,432,472,171,235,4096,-1,-1,-1,-1,-1,-1,-1,-1},
    {337,273,265,155,219,368,376,479,359,102,184,248,4096,-1,-1,-1,-1,-1,-1,-1,-1,-1,-1,-1},
    {337,273,265,155,219,368,376,479,359,102,184,248,4096,-1,-1,-1,-1,-1,-1,-1,-1,-1,-1,-1},
    {468,284,508,260,300,324,332,388,104,72,174,238,4096,-1,-1,-1,-1,-1,-1,-1,-1,-1,-1,-1},
    {468,284,508,260,300,324,332,388,104,72,174,238,4096,-1,-1,-1,-1,-1,-1,-1,-1,-1,-1,-1},
    {338,281,2,34,66,110,78,175,239,4096,-1,-1,-1,-1,-1,-1,-1,-1,-1,-1,-1,-1,-1,-1},
    {338,281,2,34,66,110,78,175,239,4096,-1,-1,-1,-1,-1,-1,-1,-1,-1,-1,-1,-1,-1,-1},
    {130,194,39,63,55,95,103,97,4096,-1,-1,-1,-1,-1,-1,-1,-1,-1,-1,-1,-1,-1,-1,-1},
    {130,194,39,63,55,95,103,97,4096,-1,-1,-1,-1,-1,-1,-1,-1,-1,-1,-1,-1,-1,-1,-1},
    {135,199,454,494,67,83,365,413,191,255,4096,-1,-1,-1,-1,-1,-1,-1,-1,-1,-1,-1,-1,-1},
    {135,199,454,494,67,83,365,413,191,255,4096,-1,-1,-1,-1,-1,-1,-1,-1,-1,-1,-1,-1,-1},
    {348,484,460,308,292,452,316,372,428,420,476,101,187,251,4096,-1,-1,-1,-1,-1,-1,-1,-1,-1},
    {348,484,460,308,292,452,316,372,428,420,476,101,187,251,4096,-1,-1,-1,-1,-1,-1,-1,-1,-1},
    {13,154,218,58,106,74,178,242,4096,-1,-1,-1,-1,-1,-1,-1,-1,-1,-1,-1,-1,-1,-1,-1},
    {13,154,218,58,106,74,178,242,4096,-1,-1,-1,-1,-1,-1,-1,-1,-1,-1,-1,-1,-1,-1,-1},
    {465,481,457,505,289,328,71,111,79,166,230,4096,-1,-1,-1,-1,-1,-1,-1,-1,-1,-1,-1,-1},
    {465,481,457,505,289,328,71,111,79,166,230,4096,-1,-1,-1,-1,-1,-1,-1,-1,-1,-1,-1,-1},
    {44,270,446,294,326,65,81,89,161,225,4096,-1,-1,-1,-1,-1,-1,-1,-1,-1,-1,-1,-1,-1},
    {44,270,446,294,326,65,81,89,161,225,4096,-1,-1,-1,-1,-1,-1,-1,-1,-1,-1,-1,-1,-1},
    {9,511,503,295,327,375,399,381,437,353,409,473,169,233,4096,-1,-1,-1,-1,-1,-1,-1,-1,-1},
    {9,511,503,295,327,375,399,381,437,353,409,473,169,233,4096,-1,-1,-1,-1,-1,-1,-1,-1,-1},
    {347,283,483,259,291,491,331,371,431,383,367,99,186,250,4096,-1,-1,-1,-1,-1,-1,-1,-1,-1},
    {347,283,483,259,291,491,331,371,431,383,367,99,186,250,4096,-1,-1,-1,-1,-1,-1,-1,-1,-1},
    {274,282,458,261,293,493,397,389,429,421,357,75,189,253,4096,-1,-1,-1,-1,-1,-1,-1,-1,-1},
    {274,282,458,261,293,493,397,389,429,421,357,75,189,253,4096,-1,-1,-1,-1,-1,-1,-1,-1,-1},
    {278,286,406,32,64,56,48,88,170,234,4096,-1,-1,-1,-1,-1,-1,-1,-1,-1,-1,-1,-1,-1},
    {278,286,406,32,64,56,48,88,170,234,4096,-1,-1,-1,-1,-1,-1,-1,-1,-1,-1,-1,-1,-1},
    {279,351,271,447,298,330,394,370,426,378,354,434,164,228,4096,-1,-1,-1,-1,-1,-1,-1,-1,-1},
    {279,351,271,447,298,330,394,370,426,378,354,434,164,228,4096,-1,-1,-1,-1,-1,-1,-1,-1,-1},
    {344,345,497,257,297,321,313,82,50,90,98,96,4096,-1,-1,-1,-1,-1,-1,-1,-1,-1,-1,-1},
    {344,345,497,257,297,321,313,82,50,90,98,96,4096,-1,-1,-1,-1,-1,-1,-1,-1,-1,-1,-1},
    {129,193,311,335,319,86,438,364,436,163,227,4096,-1,-1,-1,-1,-1,-1,-1,-1,-1,-1,-1,-1},
    {129,193,311,335,319,86,438,364,436,163,227,4096,-1,-1,-1,-1,-1,-1,-1,-1,-1,-1,-1,-1},
    {341,285,509,461,301,325,398,80,418,362,410,474,177,241,4096,-1,-1,-1,-1,-1,-1,-1,-1,-1},
    {341,285,509,461,301,325,398,80,418,362,410,474,177,241,4096,-1,-1,-1,-1,-1,-1,-1,-1,-1},
    {342,275,267,499,299,451,395,57,49,73,185,249,4096,-1,-1,-1,-1,-1,-1,-1,-1,-1,-1,-1},
    {342,275,267,499,299,451,395,57,49,73,185,249,4096,-1,-1,-1,-1,-1,-1,-1,-1,-1,-1,-1},
    {346,402,496,304,443,323,315,387,427,419,355,411,165,229,4096,-1,-1,-1,-1,-1,-1,-1,-1,-1},
    {346,402,496,304,443,323,315,387,427,419,355,411,165,229,4096,-1,-1,-1,-1,-1,-1,-1,-1,-1},
    {15,401,305,441,70,62,54,94,190,254,4096,-1,-1,-1,-1,-1,-1,-1,-1,-1,-1,-1,-1,-1},
    {15,401,305,441,70,62,54,94,190,254,4096,-1,-1,-1,-1,-1,-1,-1,-1,-1,-1,-1,-1,-1},
    {467,7,36,68,84,105,475,162,226,4096,-1,-1,-1,-1,-1,-1,-1,-1,-1,-1,-1,-1,-1,-1},
    {467,7,36,68,84,105,475,162,226,4096,-1,-1,-1,-1,-1,-1,-1,-1,-1,-1,-1,-1,-1,-1},
};

void build_rounds() {
    for (int c = 0; c < NUM_SMS / 2; c++) {
        const int16_t* jobs = h_params.jobs[2 * c];
        int nr = 0, prev_key = -1, last = 0;
        for (int j = 0; (jobs[j] >> 12) == T_P; j++) {
            const int n = jobs[j] >> 3, a = n >= 32, unit = n >= 16 && n < 32 ? (n >> 3) - 1 : 0, cnt = a ? 2 : 4;
            const int key = (jobs[j] & 7) | a << 3 | (unit > 0) << 4;
            const int wm = n < 16 ? 0 : (n < 32 ? 1 : n >> 4 & 1), col = n < 16 ? n : (n < 32 ? n & 7 : n & 15);
            const bool keep = key == prev_key, final_tile = (jobs[j + 1] >> 12) != T_P;
            const int k0 = keep ? last : 0;
            for (int r = 0; r < cnt; r++) {
                last = (k0 + r) % cnt;
                h_params.rounds[c][nr++] = (uint16_t)((key & 15) | wm << 4 | col << 6 | last << 10 | (keep && r == 0) << 12 | (final_tile && r == 0) << 13 | unit << 14);
            }
            prev_key = key;
        }
        while (nr < MAX_ROUNDS) h_params.rounds[c][nr++] = 0xFFFF;
        {
            const uint32_t rec = h_params.rounds[c][0], col = rec >> 6 & 15, unit = rec >> 14;
            for (uint32_t r = 0; r < 2; r++) {
                uint32_t wm[2], wb[2];
                for (uint32_t h = 0; h < 2; h++) {
                    wm[h] = 2 + ((rec & 8) ? 2 + h : ((rec >> 15) && h ? 0 : rec >> 4 & 1));
                    wb[h] = (rec & 8) ? (col + (rec & 16)) * 2
                                      : (unit == 0 ? col * 4 + h * 2 : (unit == 1 ? 16 + h * 16 + col * 2 : (h ? unit_head(col) : col) * 2));
                }
                const uint32_t am = unit ? 6 : (rec >> 3 & 1), arow = unit ? (rec & 7) * 128 + r * 64 : (rec & 7) * 256 + r * 128;
                h_params.first[2 * c + r] = make_uint2((unit ? 1 : 0) | am << 7 | wm[0] << 11 | wm[1] << 15 | arow << 20, wb[0] | wb[1] << 16);
            }
        }
    }
}

void build_schedule() {
    for (int c = 0; c < NUM_SMS; c++) {
        for (int j = 0; j < MAX_JOBS; j++) h_params.jobs[c][j] = k_jobs[c][j];
    }
    build_rounds();
}

}

extern "C" void kernel_launch(void* const* d_in, const int* in_sizes, int n_in, void* d_out, int out_size) {
    (void)in_sizes; (void)n_in; (void)out_size;
    static EncodeFn enc = nullptr;
    if (!enc) {
        cudaDriverEntryPointQueryResult qr;
        void* fn = nullptr;
        cudaGetDriverEntryPoint("cuTensorMapEncodeTiled", &fn, cudaEnableDefault, &qr);
        enc = (EncodeFn)fn;
        cudaFuncSetAttribute(fused_kernel, cudaFuncAttributeMaxDynamicSharedMemorySize, SMEM_BYTES);
        build_schedule();
    }
    void* qkv;
    cudaGetSymbolAddress(&qkv, g_qkv);
    Params& p = h_params;
    make_map3(enc, &p.amap[0], d_in[0], SEQ, DM, 128, 1);
    make_map3(enc, &p.amap[1], d_in[1], SEQ, DC, 128, 1);
    make_map3(enc, &p.wmap[0], d_in[2], DM, 4096, 64, 2);
    make_map3(enc, &p.wmap[2], d_in[3], DC, 4096, 64, 2);
    make_map3(enc, &p.wmap[3], d_in[4], DC, 4096, 64, 2);
    make_map3(enc, &p.wmap[1], d_in[7], DM, 3072, 64, 2);
    make_map3(enc, &p.wo_a, d_in[5], 4096, DM, 64, 2);
    make_map3(enc, &p.wo_b, d_in[8], DM, DM, 64, 2);
    make_map3(enc, &p.qkv_st, qkv, SEQ, QKV_W, 64, 1, true);
    make_map3(enc, &p.qkv_ld, qkv, SEQ, QKV_W, 128, 2, true);
    make_map3(enc, &p.qkv_half, qkv, SEQ, QKV_W, 128, 1, true);
    {
        cuuint64_t dims[4] = {64, SEQ / 2, 2, QKV_W / 64}, strides[3] = {256, 128, (cuuint64_t)SEQ * 128};
        cuuint32_t box[4] = {64, 64, 1, 1}, es[4] = {1, 1, 1, 1};
        enc(&p.st_par, CU_TENSOR_MAP_DATA_TYPE_BFLOAT16, 4, qkv, dims, strides, box, es, CU_TENSOR_MAP_INTERLEAVE_NONE,
            CU_TENSOR_MAP_SWIZZLE_128B, CU_TENSOR_MAP_L2_PROMOTION_L2_256B, CU_TENSOR_MAP_FLOAT_OOB_FILL_NONE);
        dims[3] = DM / 64; strides[0] = DM * 4; strides[1] = DM * 2; strides[2] = 128; box[2] = 2;
        enc(&p.x_par, CU_TENSOR_MAP_DATA_TYPE_BFLOAT16, 4, d_in[0], dims, strides, box, es, CU_TENSOR_MAP_INTERLEAVE_NONE,
            CU_TENSOR_MAP_SWIZZLE_128B, CU_TENSOR_MAP_L2_PROMOTION_L2_256B, CU_TENSOR_MAP_FLOAT_OOB_FILL_NONE);
    }
    make_map3(enc, &p.out_st, d_out, SEQ, DM, 64, 1);
    p.xp = (const __nv_bfloat16*)d_in[0];
    p.gate_w = (const __nv_bfloat16*)d_in[9];
    p.out = (__nv_bfloat16*)d_out;
    fused_kernel<<<NUM_SMS, 384, SMEM_BYTES, cudaStreamPerThread>>>(p);
}
```

```cpp
#include <cuda_runtime.h>
#include <cuda_bf16.h>
#include <cuda.h>
#include <stdint.h>

#define INL __attribute__((always_inline))

namespace {

constexpr int SEQ = 2048;
constexpr int DM = 1024;
constexpr int DC = 512;
constexpr int QKV_W = 13312;
constexpr int NUM_SMS = 132;
constexpr int GATE_DELAY_SHORT_NS = 1000, GATE_DELAY_LONG_NS = 3000;
constexpr int CLEAR_KS = 30, CLEAR_GAP_NS = 100;
constexpr float Q_SCALE = 0.08838834764831845f * 1.4426950408889634f;

__device__ __align__(1024) __nv_bfloat16 g_qkv[(size_t)SEQ * QKV_W];
__device__ float g_gate[SEQ];
__device__ uint4 g_halo[16 * 8 * 2 * 5 * 4 * 32];

constexpr int F_Q = 0;
constexpr int F_KV = 1792;
constexpr int F_H = 768;
constexpr int F_CTX = 960;
constexpr int F_GATE = 1600;
constexpr int F_DONE = 1632;
constexpr int F_SPLIT = 1664;
constexpr int F_TICKET = 1696;
constexpr int F_OUT = 1728;
constexpr int GATE_COUNT = NUM_SMS;
__device__ uint32_t g_flags[2304];

#define END_MARK(slot)
#define TRACE_MARK(k, w, i)
#define GTRACE(w)
#define KTRACE(w)
#define PTRACE(i)
#define TRACE_GATE 32
#define TRACE_TID 128

__device__ __forceinline__ uint32_t smem_u32(const void* p) { return (uint32_t)__cvta_generic_to_shared(p); }
__device__ __forceinline__ void mbar_init(uint32_t bar, uint32_t cnt) {
    asm volatile("mbarrier.init.shared::cta.b64 [%0], %1;" ::"r"(bar), "r"(cnt));
}
__device__ __forceinline__ void mbar_arrive(uint32_t bar) {
    asm volatile("mbarrier.arrive.shared::cta.b64 _, [%0];" ::"r"(bar) : "memory");
}
__device__ __forceinline__ bool elect_one() {
    uint32_t r;
    asm volatile("{\n.reg .pred p;\nelect.sync _|p, 0xffffffff;\nselp.b32 %0, 1, 0, p;\n}" : "=r"(r));
    return r != 0;
}
__device__ __forceinline__ uint32_t mapa(uint32_t addr, uint32_t cta) {
    uint32_t r;
    asm("mapa.shared::cluster.u32 %0, %1, %2;" : "=r"(r) : "r"(addr), "r"(cta));
    return r;
}
__device__ __forceinline__ void warp_arrive(uint32_t bar, bool pred = true) {
    asm volatile("{\n.reg .pred p, q;\nsetp.ne.u32 q, %1, 0;\nelect.sync _|p, 0xffffffff;\nand.pred p, p, q;\n"
                 "@p mbarrier.arrive.shared::cta.b64 _, [%0];\n}" ::"r"(bar), "r"((uint32_t)pred) : "memory");
}
__device__ __forceinline__ void warp_arrive2(uint32_t bar0, uint32_t bar1) {
    asm volatile("{\n.reg .pred p;\nelect.sync _|p, 0xffffffff;\n@p mbarrier.arrive.shared::cta.b64 _, [%0];\n"
                 "@p mbarrier.arrive.shared::cta.b64 _, [%1];\n}" ::"r"(bar0), "r"(bar1) : "memory");
}
__device__ __forceinline__ void warp_arrive_pair(uint32_t bar, uint32_t peer_bar, bool pred = true) {
    asm volatile("{\n.reg .pred p, q;\nsetp.ne.u32 q, %2, 0;\nelect.sync _|p, 0xffffffff;\nand.pred p, p, q;\n"
                 "@p mbarrier.arrive.shared::cluster.b64 _, [%1];\n@p mbarrier.arrive.shared::cta.b64 _, [%0];\n}"
                 ::"r"(bar), "r"(peer_bar), "r"((uint32_t)pred) : "memory");
}
__device__ __forceinline__ void mbar_expect_tx(uint32_t bar, uint32_t bytes) {
    asm volatile("mbarrier.arrive.expect_tx.shared::cta.b64 _, [%0], %1;" ::"r"(bar), "r"(bytes) : "memory");
}
constexpr int WAIT_HINT_NS = 20000, WAIT_TRIES = 200000;
__device__ __forceinline__ void mbar_wait(uint32_t bar, uint32_t parity) {
    asm volatile("{\n.reg .pred p;\n.reg .u32 c;\n"
                 "mbarrier.try_wait.parity.shared::cta.b64 p, [%0], %1;\n@p bra DONE;\nmov.u32 c, 0;\n"
                 "SPIN:\nmbarrier.try_wait.parity.shared::cta.b64 p, [%0], %1, %2;\n@p bra DONE;\n"
                 "add.u32 c, c, 1;\nsetp.lt.u32 p, c, %3;\n@p bra SPIN;\ntrap;\nDONE:\n}"
                 ::"r"(bar), "r"(parity), "n"(WAIT_HINT_NS), "n"(WAIT_TRIES) : "memory");
}
__device__ __forceinline__ void mbar_wait_hot(uint32_t bar, uint32_t parity) {
    asm volatile("{\n.reg .pred p, q;\n.reg .u32 c;\n.reg .u64 z;\nmov.u32 c, 0;\nmov.u64 z, 0;\n"
                 "SPIN:\nmbarrier.try_wait.parity.shared::cta.b64 p, [%0], %1;\n"
                 "add.u32 c, c, 1;\nsetp.lt.and.u32 q, c, 4194304, !p;\n@q bra SPIN;\n@!p st.global.u32 [z], c;\n}"
                 ::"r"(bar), "r"(parity) : "memory");
}
constexpr uint64_t POL_STREAM = 0x12F0000000000000ull;
constexpr uint64_t POL_NORMAL = 0x1000000000000000ull;
__device__ __forceinline__ void tma_load_3d(uint32_t dst, const CUtensorMap* map, uint32_t bar, int c0, int c1, int c2, uint64_t pol = POL_NORMAL) {
    asm volatile("cp.async.bulk.tensor.3d.shared::cluster.global.mbarrier::complete_tx::bytes.L2::cache_hint [%0], [%1, {%3, %4, %5}], [%2], %6;"
                 ::"r"(dst), "l"(map), "r"(bar), "r"(c0), "r"(c1), "r"(c2), "l"(pol) : "memory");
}
__device__ __forceinline__ void load_kstep(uint32_t sa, uint32_t sw, uint32_t bar, uint32_t bytes, const CUtensorMap* wmap, int wk, int wblk,
                                           const CUtensorMap* amap, int arow, int kc, uint32_t amode) {
    asm volatile("{\n.reg .pred p, q, r;\n.reg .b32 k;\nelect.sync _|p, 0xffffffff;\nsetp.eq.and.u32 q, %9, 1, p;\nsetp.eq.and.u32 r, %9, 2, p;\nshl.b32 k, %12, 6;\n"
                 "@p mbarrier.arrive.expect_tx.shared::cta.b64 _, [%2], %3;\n"
                 "@p cp.async.bulk.tensor.3d.shared::cluster.global.mbarrier::complete_tx::bytes.multicast::cluster.L2::cache_hint [%1], [%4, {0, k, %5}], [%2], %10, %11;\n"
                 "@q cp.async.bulk.tensor.3d.shared::cluster.global.mbarrier::complete_tx::bytes.L2::cache_hint [%0], [%6, {0, %7, %8}], [%2], %11;\n"
                 "@r cp.async.bulk.tensor.4d.shared::cluster.global.mbarrier::complete_tx::bytes.L2::cache_hint [%0], [%6, {0, %7, 0, %8}], [%2], %11;\n}"
                 ::"r"(sa), "r"(sw), "r"(bar), "r"(bytes), "l"(wmap), "r"(wblk), "l"(amap), "r"(arow), "r"(kc), "r"(amode), "h"((uint16_t)3), "l"(POL_NORMAL), "r"(wk) : "memory");
}
__device__ __forceinline__ void load_operand(uint32_t dst, uint32_t bar, const CUtensorMap* full, const CUtensorMap* half, int row, int blk,
                                             uint32_t rank, bool solo, uint64_t pol) {
    asm volatile("{\n.reg .pred p, q, r;\n.reg .b32 d, b;\nelect.sync _|p, 0xffffffff;\nsetp.ne.and.u32 q, %7, 0, p;\nsetp.eq.and.u32 r, %7, 0, p;\n"
                 "mad.lo.u32 d, %6, 16384, %0;\nadd.u32 b, %5, %6;\n"
                 "@p mbarrier.arrive.expect_tx.shared::cta.b64 _, [%1], 32768;\n"
                 "@q cp.async.bulk.tensor.3d.shared::cluster.global.mbarrier::complete_tx::bytes.L2::cache_hint [%0], [%2, {0, %4, %5}], [%1], %9;\n"
                 "@r cp.async.bulk.tensor.3d.shared::cluster.global.mbarrier::complete_tx::bytes.multicast::cluster.L2::cache_hint [d], [%3, {0, %4, b}], [%1], %8, %9;\n}"
                 ::"r"(dst), "r"(bar), "l"(full), "l"(half), "r"(row), "r"(blk), "r"(rank), "r"((uint32_t)solo), "h"((uint16_t)3), "l"(pol) : "memory");
}
__device__ __forceinline__ void tma_store_par(const CUtensorMap* map, uint32_t src, int pair, int parity, int blk) {
    asm volatile("cp.async.bulk.tensor.4d.global.shared::cta.bulk_group.L2::cache_hint [%0, {0, %2, %3, %4}], [%1], %5;"
                 ::"l"(map), "r"(src), "r"(pair), "r"(parity), "r"(blk), "l"(POL_STREAM) : "memory");
}
__device__ __forceinline__ void tma_store_3d(const CUtensorMap* map, uint32_t src, int c0, int c1, int c2, uint64_t pol) {
    asm volatile("cp.async.bulk.tensor.3d.global.shared::cta.bulk_group.L2::cache_hint [%0, {%2, %3, %4}], [%1], %5;"
                 ::"l"(map), "r"(src), "r"(c0), "r"(c1), "r"(c2), "l"(pol) : "memory");
}
__device__ __forceinline__ void tma_reduce_add_3d(const CUtensorMap* map, uint32_t src, int c0, int c1, int c2) {
    asm volatile("cp.reduce.async.bulk.tensor.3d.global.shared::cta.add.tile.bulk_group [%0, {%2, %3, %4}], [%1];"
                 ::"l"(map), "r"(src), "r"(c0), "r"(c1), "r"(c2) : "memory");
}
__device__ __forceinline__ void bulk_commit() { asm volatile("cp.async.bulk.commit_group;" ::: "memory"); }
template <int N> __device__ __forceinline__ void bulk_wait_read() { asm volatile("cp.async.bulk.wait_group.read %0;" ::"n"(N) : "memory"); }
template <int N> __device__ __forceinline__ void bulk_wait() { asm volatile("cp.async.bulk.wait_group %0;" ::"n"(N) : "memory"); }
__device__ __forceinline__ void fence_async_smem() { asm volatile("fence.proxy.async.shared::cta;" ::: "memory"); }
__device__ __forceinline__ void fence_async_global() { asm volatile("fence.proxy.async.global;" ::: "memory"); }
__device__ __forceinline__ uint32_t ld_acquire(const uint32_t* p) {
    uint32_t v;
    asm volatile("ld.acquire.gpu.global.u32 %0, [%1];" : "=r"(v) : "l"(p) : "memory");
    return v;
}
__device__ __forceinline__ uint32_t ld_relaxed(const uint32_t* p) {
    uint32_t v;
    asm volatile("ld.relaxed.gpu.global.u32 %0, [%1];" : "=r"(v) : "l"(p) : "memory");
    return v;
}
__device__ __forceinline__ void fence_acquire() { asm volatile("fence.acquire.gpu;\nfence.proxy.async.global;" ::: "memory"); }
__device__ __forceinline__ void red_release(uint32_t* p) {
    asm volatile("red.release.gpu.global.add.u32 [%0], 1;" ::"l"(p) : "memory");
}
__device__ __forceinline__ void red_relaxed(uint32_t* p) {
    asm volatile("red.relaxed.gpu.global.add.u32 [%0], 1;" ::"l"(p) : "memory");
}
__device__ __forceinline__ void prefetch_map(const CUtensorMap* map) { asm volatile("prefetch.tensormap [%0];" ::"l"(map) : "memory"); }
__device__ __forceinline__ void trap_if(bool c) { asm volatile("{\n.reg .pred p;\nsetp.ne.u32 p, %0, 0;\n@p trap;\n}" ::"r"((uint32_t)c)); }
__device__ __forceinline__ void setup_arrive() { asm volatile("barrier.cluster.arrive.relaxed.aligned;" ::: "memory"); }
__device__ __forceinline__ void setup_wait() { asm volatile("barrier.cluster.wait.aligned;" ::: "memory"); }
__device__ __forceinline__ uint32_t cluster_rank() { uint32_t r; asm("mov.u32 %0, %%cluster_ctarank;" : "=r"(r)); return r; }
__device__ __forceinline__ void named_sync(int id, int n) { asm volatile("bar.sync %0, %1;" ::"r"(id), "r"(n) : "memory"); }
__device__ __forceinline__ void named_arrive(int id, int n) { asm volatile("bar.arrive %0, %1;" ::"r"(id), "r"(n) : "memory"); }
__device__ __forceinline__ void named_sync_if(bool c, int id, int n) {
    asm volatile("{\n.reg .pred p;\nsetp.ne.u32 p, %0, 0;\n@p bar.sync %1, %2;\n}" ::"r"((uint32_t)c), "r"(id), "r"(n) : "memory");
}
__device__ __forceinline__ void named_arrive_if(bool c, int id, int n) {
    asm volatile("{\n.reg .pred p;\nsetp.ne.u32 p, %0, 0;\n@p bar.arrive %1, %2;\n}" ::"r"((uint32_t)c), "r"(id), "r"(n) : "memory");
}
template <int V> struct IC { static constexpr int v = V; };
template <int N> __device__ __forceinline__ void reg_dec() { asm volatile("setmaxnreg.dec.sync.aligned.u32 %0;" ::"n"(N)); }
template <int N> __device__ __forceinline__ void reg_inc() { asm volatile("setmaxnreg.inc.sync.aligned.u32 %0;" ::"n"(N)); }

__device__ __forceinline__ void wg_fence() { asm volatile("wgmma.fence.sync.aligned;" ::: "memory"); }
__device__ __forceinline__ void wg_commit() { asm volatile("wgmma.commit_group.sync.aligned;" ::: "memory"); }
template <int N> __device__ __forceinline__ void wg_wait() { asm volatile("wgmma.wait_group.sync.aligned %0;" ::"n"(N) : "memory"); }
template <int N> __device__ __forceinline__ void fence_regs(float (&r)[N]) {
#pragma unroll
    for (int i = 0; i < N; i++) asm volatile("" : "+f"(r[i])::"memory");
}
template <int N> __device__ __forceinline__ void fence_regs(uint32_t (&r)[N]) {
#pragma unroll
    for (int i = 0; i < N; i++) asm volatile("" : "+r"(r[i])::"memory");
}
__device__ __forceinline__ uint32_t desc_lo(uint32_t addr, uint32_t lbo) { return ((addr & 0x3FFFF) >> 4) | ((lbo >> 4) << 16); }
__device__ __forceinline__ int uniform(int v) { return __shfl_sync(0xffffffffu, v, 0); }
__device__ __forceinline__ uint32_t pack_bf16(float lo, float hi) {
    uint32_t r;
    asm("cvt.rn.bf16x2.f32 %0, %1, %2;" : "=r"(r) : "f"(hi), "f"(lo));
    return r;
}
__device__ __forceinline__ uint32_t mul_bf16x2(uint32_t x, uint32_t y) {
    uint32_t r;
    asm("mul.rn.bf16x2 %0, %1, %2;" : "=r"(r) : "r"(x), "r"(y));
    return r;
}
__device__ __forceinline__ void stmatrix_x4(uint32_t addr, uint32_t r0, uint32_t r1, uint32_t r2, uint32_t r3) {
    asm volatile("stmatrix.sync.aligned.m8n8.x4.shared.b16 [%0], {%1, %2, %3, %4};"
                 ::"r"(addr), "r"(r0), "r"(r1), "r"(r2), "r"(r3) : "memory");
}
__device__ __forceinline__ void stmatrix_x4(uint32_t addr, uint32_t r0, uint32_t r1, uint32_t r2, uint32_t r3, bool trans) {
    asm volatile("{\n.reg .pred p;\nsetp.ne.u32 p, %5, 0;\n@p stmatrix.sync.aligned.m8n8.x4.trans.shared.b16 [%0], {%1, %2, %3, %4};\n"
                 "@!p stmatrix.sync.aligned.m8n8.x4.shared.b16 [%0], {%1, %2, %3, %4};\n}"
                 ::"r"(addr), "r"(r0), "r"(r1), "r"(r2), "r"(r3), "r"((uint32_t)trans) : "memory");
}
__device__ __forceinline__ void ldmatrix_x4_t(uint32_t addr, uint32_t (&r)[4]) {
    asm volatile("ldmatrix.sync.aligned.m8n8.x4.trans.shared.b16 {%0, %1, %2, %3}, [%4];"
                 : "=r"(r[0]), "=r"(r[1]), "=r"(r[2]), "=r"(r[3]) : "r"(addr) : "memory");
}
__device__ __forceinline__ void mma_16816(float (&d)[4], uint32_t a0, uint32_t a1, uint32_t a2, uint32_t a3, uint32_t b0, uint32_t b1) {
    asm("mma.sync.aligned.m16n8k16.row.col.f32.bf16.bf16.f32 {%0, %1, %2, %3}, {%4, %5, %6, %7}, {%8, %9}, {%0, %1, %2, %3};"
        : "+f"(d[0]), "+f"(d[1]), "+f"(d[2]), "+f"(d[3]) : "r"(a0), "r"(a1), "r"(a2), "r"(a3), "r"(b0), "r"(b1));
}
__device__ __forceinline__ void order_after(float v, uint32_t scratch) {
    asm volatile("{\n.reg .pred p;\nsetp.gt.f32 p, %0, 0f70000000;\n@p st.shared.u32 [%1], 0;\n}" ::"f"(v), "r"(scratch) : "memory");
}
__device__ __forceinline__ float rcp(float x) { float y; asm("rcp.approx.ftz.f32 %0, %1;" : "=f"(y) : "f"(x)); return y; }
__device__ __forceinline__ float ex2(float x) { float y; asm("ex2.approx.ftz.f32 %0, %1;" : "=f"(y) : "f"(x)); return y; }

template <int OA, int OB>
__device__ __forceinline__ void wgmma_ss_n256(float (&d0)[64], float (&d1)[64], uint32_t da, uint32_t db) {
    asm volatile("{\n.reg .b32 ta, tb;\n.reg .b64 da, db;\nadd.u32 ta, %128, %130;\nadd.u32 tb, %129, %131;\n"
        "mov.b64 da, {ta, 0x40000040};\nmov.b64 db, {tb, 0x40000040};\n"
        "wgmma.mma_async.sync.aligned.m64n256k16.f32.bf16.bf16 {%0, %1, %2, %3, %4, %5, %6, %7, %8, %9, %10, %11, %12, %13, %14, %15, %16, %17, %18, %19, %20, %21, %22, %23, %24, %25, %26, %27, %28, %29, %30, %31, %32, %33, %34, %35, %36, %37, %38, %39, %40, %41, %42, %43, %44, %45, %46, %47, %48, %49, %50, %51, %52, %53, %54, %55, %56, %57, %58, %59, %60, %61, %62, %63, %64, %65, %66, %67, %68, %69, %70, %71, %72, %73, %74, %75, %76, %77, %78, %79, %80, %81, %82, %83, %84, %85, %86, %87, %88, %89, %90, %91, %92, %93, %94, %95, %96, %97, %98, %99, %100, %101, %102, %103, %104, %105, %106, %107, %108, %109, %110, %111, %112, %113, %114, %115, %116, %117, %118, %119, %120, %121, %122, %123, %124, %125, %126, %127}, da, db, 1, 1, 1, 0, 1;\n}\n"
        : "+f"(d0[0]), "+f"(d0[1]), "+f"(d0[2]), "+f"(d0[3]), "+f"(d0[4]), "+f"(d0[5]), "+f"(d0[6]), "+f"(d0[7]), "+f"(d0[8]), "+f"(d0[9]), "+f"(d0[10]), "+f"(d0[11]), "+f"(d0[12]), "+f"(d0[13]), "+f"(d0[14]), "+f"(d0[15]), "+f"(d0[16]), "+f"(d0[17]), "+f"(d0[18]), "+f"(d0[19]), "+f"(d0[20]), "+f"(d0[21]), "+f"(d0[22]), "+f"(d0[23]), "+f"(d0[24]), "+f"(d0[25]), "+f"(d0[26]), "+f"(d0[27]), "+f"(d0[28]), "+f"(d0[29]), "+f"(d0[30]), "+f"(d0[31]), "+f"(d0[32]), "+f"(d0[33]), "+f"(d0[34]), "+f"(d0[35]), "+f"(d0[36]), "+f"(d0[37]), "+f"(d0[38]), "+f"(d0[39]), "+f"(d0[40]), "+f"(d0[41]), "+f"(d0[42]), "+f"(d0[43]), "+f"(d0[44]), "+f"(d0[45]), "+f"(d0[46]), "+f"(d0[47]), "+f"(d0[48]), "+f"(d0[49]), "+f"(d0[50]), "+f"(d0[51]), "+f"(d0[52]), "+f"(d0[53]), "+f"(d0[54]), "+f"(d0[55]), "+f"(d0[56]), "+f"(d0[57]), "+f"(d0[58]), "+f"(d0[59]), "+f"(d0[60]), "+f"(d0[61]), "+f"(d0[62]), "+f"(d0[63]), "+f"(d1[0]), "+f"(d1[1]), "+f"(d1[2]), "+f"(d1[3]), "+f"(d1[4]), "+f"(d1[5]), "+f"(d1[6]), "+f"(d1[7]), "+f"(d1[8]), "+f"(d1[9]), "+f"(d1[10]), "+f"(d1[11]), "+f"(d1[12]), "+f"(d1[13]), "+f"(d1[14]), "+f"(d1[15]), "+f"(d1[16]), "+f"(d1[17]), "+f"(d1[18]), "+f"(d1[19]), "+f"(d1[20]), "+f"(d1[21]), "+f"(d1[22]), "+f"(d1[23]), "+f"(d1[24]), "+f"(d1[25]), "+f"(d1[26]), "+f"(d1[27]), "+f"(d1[28]), "+f"(d1[29]), "+f"(d1[30]), "+f"(d1[31]), "+f"(d1[32]), "+f"(d1[33]), "+f"(d1[34]), "+f"(d1[35]), "+f"(d1[36]), "+f"(d1[37]), "+f"(d1[38]), "+f"(d1[39]), "+f"(d1[40]), "+f"(d1[41]), "+f"(d1[42]), "+f"(d1[43]), "+f"(d1[44]), "+f"(d1[45]), "+f"(d1[46]), "+f"(d1[47]), "+f"(d1[48]), "+f"(d1[49]), "+f"(d1[50]), "+f"(d1[51]), "+f"(d1[52]), "+f"(d1[53]), "+f"(d1[54]), "+f"(d1[55]), "+f"(d1[56]), "+f"(d1[57]), "+f"(d1[58]), "+f"(d1[59]), "+f"(d1[60]), "+f"(d1[61]), "+f"(d1[62]), "+f"(d1[63])
        : "r"(da), "r"(db), "n"(OA), "n"(OB));
}

__device__ __forceinline__ void wgmma_ss_n256_init(float (&d0)[64], float (&d1)[64], uint32_t da, uint32_t db) {
    asm volatile("{\n.reg .b64 da, db;\n"
        "mov.b64 da, {%128, 0x40000040};\nmov.b64 db, {%129, 0x40000040};\n"
        "wgmma.mma_async.sync.aligned.m64n256k16.f32.bf16.bf16 {%0, %1, %2, %3, %4, %5, %6, %7, %8, %9, %10, %11, %12, %13, %14, %15, %16, %17, %18, %19, %20, %21, %22, %23, %24, %25, %26, %27, %28, %29, %30, %31, %32, %33, %34, %35, %36, %37, %38, %39, %40, %41, %42, %43, %44, %45, %46, %47, %48, %49, %50, %51, %52, %53, %54, %55, %56, %57, %58, %59, %60, %61, %62, %63, %64, %65, %66, %67, %68, %69, %70, %71, %72, %73, %74, %75, %76, %77, %78, %79, %80, %81, %82, %83, %84, %85, %86, %87, %88, %89, %90, %91, %92, %93, %94, %95, %96, %97, %98, %99, %100, %101, %102, %103, %104, %105, %106, %107, %108, %109, %110, %111, %112, %113, %114, %115, %116, %117, %118, %119, %120, %121, %122, %123, %124, %125, %126, %127}, da, db, 0, 1, 1, 0, 1;\n}\n"
        : "=f"(d0[0]), "=f"(d0[1]), "=f"(d0[2]), "=f"(d0[3]), "=f"(d0[4]), "=f"(d0[5]), "=f"(d0[6]), "=f"(d0[7]), "=f"(d0[8]), "=f"(d0[9]), "=f"(d0[10]), "=f"(d0[11]), "=f"(d0[12]), "=f"(d0[13]), "=f"(d0[14]), "=f"(d0[15]), "=f"(d0[16]), "=f"(d0[17]), "=f"(d0[18]), "=f"(d0[19]), "=f"(d0[20]), "=f"(d0[21]), "=f"(d0[22]), "=f"(d0[23]), "=f"(d0[24]), "=f"(d0[25]), "=f"(d0[26]), "=f"(d0[27]), "=f"(d0[28]), "=f"(d0[29]), "=f"(d0[30]), "=f"(d0[31]), "=f"(d0[32]), "=f"(d0[33]), "=f"(d0[34]), "=f"(d0[35]), "=f"(d0[36]), "=f"(d0[37]), "=f"(d0[38]), "=f"(d0[39]), "=f"(d0[40]), "=f"(d0[41]), "=f"(d0[42]), "=f"(d0[43]), "=f"(d0[44]), "=f"(d0[45]), "=f"(d0[46]), "=f"(d0[47]), "=f"(d0[48]), "=f"(d0[49]), "=f"(d0[50]), "=f"(d0[51]), "=f"(d0[52]), "=f"(d0[53]), "=f"(d0[54]), "=f"(d0[55]), "=f"(d0[56]), "=f"(d0[57]), "=f"(d0[58]), "=f"(d0[59]), "=f"(d0[60]), "=f"(d0[61]), "=f"(d0[62]), "=f"(d0[63]), "=f"(d1[0]), "=f"(d1[1]), "=f"(d1[2]), "=f"(d1[3]), "=f"(d1[4]), "=f"(d1[5]), "=f"(d1[6]), "=f"(d1[7]), "=f"(d1[8]), "=f"(d1[9]), "=f"(d1[10]), "=f"(d1[11]), "=f"(d1[12]), "=f"(d1[13]), "=f"(d1[14]), "=f"(d1[15]), "=f"(d1[16]), "=f"(d1[17]), "=f"(d1[18]), "=f"(d1[19]), "=f"(d1[20]), "=f"(d1[21]), "=f"(d1[22]), "=f"(d1[23]), "=f"(d1[24]), "=f"(d1[25]), "=f"(d1[26]), "=f"(d1[27]), "=f"(d1[28]), "=f"(d1[29]), "=f"(d1[30]), "=f"(d1[31]), "=f"(d1[32]), "=f"(d1[33]), "=f"(d1[34]), "=f"(d1[35]), "=f"(d1[36]), "=f"(d1[37]), "=f"(d1[38]), "=f"(d1[39]), "=f"(d1[40]), "=f"(d1[41]), "=f"(d1[42]), "=f"(d1[43]), "=f"(d1[44]), "=f"(d1[45]), "=f"(d1[46]), "=f"(d1[47]), "=f"(d1[48]), "=f"(d1[49]), "=f"(d1[50]), "=f"(d1[51]), "=f"(d1[52]), "=f"(d1[53]), "=f"(d1[54]), "=f"(d1[55]), "=f"(d1[56]), "=f"(d1[57]), "=f"(d1[58]), "=f"(d1[59]), "=f"(d1[60]), "=f"(d1[61]), "=f"(d1[62]), "=f"(d1[63])
        : "r"(da), "r"(db));
}

template <int TB, int OA, int OB>
__device__ __forceinline__ void wgmma_ss_n128_init(float (&d)[64], uint32_t da, uint32_t db) {
    asm volatile("{\n.reg .b32 ta, tb;\n.reg .b64 da, db;\nadd.u32 ta, %64, %66;\nadd.u32 tb, %65, %67;\n"
        "mov.b64 da, {ta, 0x40000040};\nmov.b64 db, {tb, 0x40000040};\n"
        "wgmma.mma_async.sync.aligned.m64n128k16.f32.bf16.bf16 {%0, %1, %2, %3, %4, %5, %6, %7, %8, %9, %10, %11, %12, %13, %14, %15, %16, %17, %18, %19, %20, %21, %22, %23, %24, %25, %26, %27, %28, %29, %30, %31, %32, %33, %34, %35, %36, %37, %38, %39, %40, %41, %42, %43, %44, %45, %46, %47, %48, %49, %50, %51, %52, %53, %54, %55, %56, %57, %58, %59, %60, %61, %62, %63}, da, db, 0, 1, 1, 0, %68;\n}\n"
        : "=f"(d[0]), "=f"(d[1]), "=f"(d[2]), "=f"(d[3]), "=f"(d[4]), "=f"(d[5]), "=f"(d[6]), "=f"(d[7]), "=f"(d[8]), "=f"(d[9]), "=f"(d[10]), "=f"(d[11]), "=f"(d[12]), "=f"(d[13]), "=f"(d[14]), "=f"(d[15]), "=f"(d[16]), "=f"(d[17]), "=f"(d[18]), "=f"(d[19]), "=f"(d[20]), "=f"(d[21]), "=f"(d[22]), "=f"(d[23]), "=f"(d[24]), "=f"(d[25]), "=f"(d[26]), "=f"(d[27]), "=f"(d[28]), "=f"(d[29]), "=f"(d[30]), "=f"(d[31]), "=f"(d[32]), "=f"(d[33]), "=f"(d[34]), "=f"(d[35]), "=f"(d[36]), "=f"(d[37]), "=f"(d[38]), "=f"(d[39]), "=f"(d[40]), "=f"(d[41]), "=f"(d[42]), "=f"(d[43]), "=f"(d[44]), "=f"(d[45]), "=f"(d[46]), "=f"(d[47]), "=f"(d[48]), "=f"(d[49]), "=f"(d[50]), "=f"(d[51]), "=f"(d[52]), "=f"(d[53]), "=f"(d[54]), "=f"(d[55]), "=f"(d[56]), "=f"(d[57]), "=f"(d[58]), "=f"(d[59]), "=f"(d[60]), "=f"(d[61]), "=f"(d[62]), "=f"(d[63])
        : "r"(da), "r"(db), "n"(OA), "n"(OB), "n"(TB));
}

template <int OA, int OB>
__device__ __forceinline__ void wgmma_ss_n128_tb0(float (&d)[64], uint32_t da, uint32_t db, int scale_d) {
    asm volatile("{\n.reg .pred p;\n.reg .b32 ta, tb;\n.reg .b64 da, db;\nsetp.ne.b32 p, %66, 0;\nadd.u32 ta, %64, %67;\nadd.u32 tb, %65, %68;\n"
        "mov.b64 da, {ta, 0x40000040};\nmov.b64 db, {tb, 0x40000040};\n"
        "wgmma.mma_async.sync.aligned.m64n128k16.f32.bf16.bf16 "
        "{%0, %1, %2, %3, %4, %5, %6, %7, %8, %9, %10, %11, %12, %13, %14, %15, %16, %17, %18, %19, %20, %21, %22, %23, %24, %25, %26, %27, %28, %29, %30, %31, %32, %33, %34, %35, %36, %37, %38, %39, %40, %41, %42, %43, %44, %45, %46, %47, %48, %49, %50, %51, %52, %53, %54, %55, %56, %57, %58, %59, %60, %61, %62, %63}, da, db, p, 1, 1, 0, 0;\n}\n"
        : "+f"(d[0]), "+f"(d[1]), "+f"(d[2]), "+f"(d[3]), "+f"(d[4]), "+f"(d[5]), "+f"(d[6]), "+f"(d[7]), "+f"(d[8]), "+f"(d[9]), "+f"(d[10]), "+f"(d[11]), "+f"(d[12]), "+f"(d[13]), "+f"(d[14]), "+f"(d[15]), "+f"(d[16]), "+f"(d[17]), "+f"(d[18]), "+f"(d[19]), "+f"(d[20]), "+f"(d[21]), "+f"(d[22]), "+f"(d[23]), "+f"(d[24]), "+f"(d[25]), "+f"(d[26]), "+f"(d[27]), "+f"(d[28]), "+f"(d[29]), "+f"(d[30]), "+f"(d[31]), "+f"(d[32]), "+f"(d[33]), "+f"(d[34]), "+f"(d[35]), "+f"(d[36]), "+f"(d[37]), "+f"(d[38]), "+f"(d[39]), "+f"(d[40]), "+f"(d[41]), "+f"(d[42]), "+f"(d[43]), "+f"(d[44]), "+f"(d[45]), "+f"(d[46]), "+f"(d[47]), "+f"(d[48]), "+f"(d[49]), "+f"(d[50]), "+f"(d[51]), "+f"(d[52]), "+f"(d[53]), "+f"(d[54]), "+f"(d[55]), "+f"(d[56]), "+f"(d[57]), "+f"(d[58]), "+f"(d[59]), "+f"(d[60]), "+f"(d[61]), "+f"(d[62]), "+f"(d[63])
        : "r"(da), "r"(db), "r"(scale_d), "n"(OA), "n"(OB));
}

template <int OB>
__device__ __forceinline__ void wgmma_rs_n128_tb1(float (&d)[64], uint32_t a0, uint32_t a1, uint32_t a2, uint32_t a3, uint32_t db, int scale_d) {
    asm volatile("{\n.reg .pred p;\n.reg .b32 tb;\n.reg .b64 db;\nsetp.ne.b32 p, %69, 0;\nadd.u32 tb, %68, %70;\n"
        "mov.b64 db, {tb, 0x40000040};\n"
        "wgmma.mma_async.sync.aligned.m64n128k16.f32.bf16.bf16 "
        "{%0, %1, %2, %3, %4, %5, %6, %7, %8, %9, %10, %11, %12, %13, %14, %15, %16, %17, %18, %19, %20, %21, %22, %23, %24, %25, %26, %27, %28, %29, %30, %31, %32, %33, %34, %35, %36, %37, %38, %39, %40, %41, %42, %43, %44, %45, %46, %47, %48, %49, %50, %51, %52, %53, %54, %55, %56, %57, %58, %59, %60, %61, %62, %63}, {%64, %65, %66, %67}, db, p, 1, 1, 1;\n}\n"
        : "+f"(d[0]), "+f"(d[1]), "+f"(d[2]), "+f"(d[3]), "+f"(d[4]), "+f"(d[5]), "+f"(d[6]), "+f"(d[7]), "+f"(d[8]), "+f"(d[9]), "+f"(d[10]), "+f"(d[11]), "+f"(d[12]), "+f"(d[13]), "+f"(d[14]), "+f"(d[15]), "+f"(d[16]), "+f"(d[17]), "+f"(d[18]), "+f"(d[19]), "+f"(d[20]), "+f"(d[21]), "+f"(d[22]), "+f"(d[23]), "+f"(d[24]), "+f"(d[25]), "+f"(d[26]), "+f"(d[27]), "+f"(d[28]), "+f"(d[29]), "+f"(d[30]), "+f"(d[31]), "+f"(d[32]), "+f"(d[33]), "+f"(d[34]), "+f"(d[35]), "+f"(d[36]), "+f"(d[37]), "+f"(d[38]), "+f"(d[39]), "+f"(d[40]), "+f"(d[41]), "+f"(d[42]), "+f"(d[43]), "+f"(d[44]), "+f"(d[45]), "+f"(d[46]), "+f"(d[47]), "+f"(d[48]), "+f"(d[49]), "+f"(d[50]), "+f"(d[51]), "+f"(d[52]), "+f"(d[53]), "+f"(d[54]), "+f"(d[55]), "+f"(d[56]), "+f"(d[57]), "+f"(d[58]), "+f"(d[59]), "+f"(d[60]), "+f"(d[61]), "+f"(d[62]), "+f"(d[63])
        : "r"(a0), "r"(a1), "r"(a2), "r"(a3), "r"(db), "r"(scale_d), "n"(OB));
}

__device__ __forceinline__ uint32_t stage_addr(uint32_t block, int warp, int lane) {
    return block + (warp * 16 + (lane & 7) + ((lane >> 3) & 1) * 8) * 128 + (((lane >> 4) ^ (lane & 7)) << 4);
}
template <int OFF, int N>
__device__ __forceinline__ void stage_packed_64x64(uint32_t a0, int off, const uint32_t (&v)[N]) {
#pragma unroll
    for (int j = 0; j < 8; j += 2) {
        uint32_t a = a0;
        if (j) asm volatile("xor.b32 %0, %1, %2;" : "=r"(a) : "r"(a0), "r"(j << 4));
        stmatrix_x4(a + off, v[OFF + j * 2], v[OFF + j * 2 + 1], v[OFF + j * 2 + 2], v[OFF + j * 2 + 3]);
    }
}

template <int OFF, int N>
__device__ __forceinline__ void stage_packed_64x64(const uint32_t (&a)[4], int off, const uint32_t (&v)[N]) {
#pragma unroll
    for (int j = 0; j < 4; j++) stmatrix_x4(a[j] + off, v[OFF + j * 4], v[OFF + j * 4 + 1], v[OFF + j * 4 + 2], v[OFF + j * 4 + 3]);
}

template <int OFF, int N>
__device__ __forceinline__ void stage_packed_64x64(const uint32_t (&a)[4], int off, const uint32_t (&v)[N], bool trans) {
#pragma unroll
    for (int j = 0; j < 4; j++) stmatrix_x4(a[j] + off, v[OFF + j * 4], v[OFF + j * 4 + 1], v[OFF + j * 4 + 2], v[OFF + j * 4 + 3], trans);
}

constexpr int MAX_JOBS = 24;
constexpr int MAX_ROUNDS = 44;
constexpr int T_P = 0, T_O = 1, T_A = 2;
constexpr int HQ_A = 4, HQ_B = 28;
__host__ __device__ constexpr int unit_head(int g) { return g + (g < 4 ? HQ_A : HQ_B - 4); }
constexpr int G_STAGE = 49152;
constexpr int OFF_Q0 = 0, OFF_K0 = 32768, OFF_Q1 = 65536, OFF_K1 = 98304, OFF_V0 = 131072, OFF_V1 = 163840;
constexpr int OFF_STG = 196608;
constexpr int OFF_BAR = 229376;
constexpr int SMEM_BYTES = OFF_BAR + 640;
constexpr int TURN_THREADS = 288;

struct Params {
    CUtensorMap amap[2];
    CUtensorMap wmap[4];
    CUtensorMap x_par, wo_a, wo_b, qkv_st, qkv_ld, qkv_half, st_par, out_st;
    const __nv_bfloat16* xp;
    const __nv_bfloat16* gate_w;
    __nv_bfloat16* out;
    uint2 first[NUM_SMS];
    int16_t jobs[NUM_SMS][MAX_JOBS];
    uint16_t rounds[NUM_SMS / 2][MAX_ROUNDS];
};

constexpr int O_STAGGER = 4;
constexpr int O_F0 = 35, O_H1 = 5;
constexpr int O_FLEX = 16, O_H0 = O_F0 + 8, O_T0 = 8, O_T1 = 64 - O_F0 - O_FLEX - O_H1;
__device__ __forceinline__ int o_head(int job) { return (job & 32) ? O_H1 : O_H0; }
__device__ __forceinline__ int o_tail(int job) { return (job & 32) ? O_T1 : O_T0; }
__device__ __forceinline__ uint32_t o_state(uint32_t word, int have) {
    uint32_t v;
    asm volatile("{\n.reg .pred p, q;\n.reg .u32 c, t;\nmov.u32 c, 0;\n"
                 "SPIN:\nld.volatile.shared.u32 %0, [%1];\nand.b32 t, %0, 1;\nsetp.ne.u32 q, t, 0;\nsetp.gt.or.u32 p, %0, %2, q;\n@p bra DONE;\n"
                 "add.u32 c, c, 1;\nsetp.lt.u32 q, c, 16777216;\n@q bra SPIN;\ntrap;\nDONE:\n}"
                 : "=r"(v) : "r"(word), "r"(2 * have + 1) : "memory");
    return v;
}

template <class T> __device__ __forceinline__ T* page_ptr(int off) {
    extern __shared__ __align__(1024) uint8_t smem_raw[];
    return *reinterpret_cast<T* volatile*>(smem_raw + OFF_BAR + off);
}
template <int SLEEP_NS = 0>
__device__ __forceinline__ bool wait_flags(bool active, int idx, uint32_t target, bool block = true) {
    for (uint32_t tries = 0;; tries++) {
        const bool ok = !active | ((int32_t)(ld_acquire(g_flags + idx) - target) >= 0);
        if (__all_sync(0xffffffffu, ok)) break;
        if (!block) return false;
        if (SLEEP_NS) __nanosleep(SLEEP_NS);
        trap_if(tries > (1u << 22));
    }
    fence_async_global();
    return true;
}

__global__ void __cluster_dims__(2, 1, 1) __launch_bounds__(384, 1)
fused_kernel(const __grid_constant__ Params p) {
    extern __shared__ __align__(1024) uint8_t smem_raw[];
    const uint32_t base = smem_u32(smem_raw);
    const uint32_t bars = base + OFF_BAR;
    const uint32_t gfull = bars, gempty = bars + 32, sfull = bars + 64, sempty = bars + 96;
    const uint32_t qfull = bars + 128, qempty = bars + 144, kfull = bars + 160, kempty = bars + 176;
    const uint32_t vfull = bars + 192, vempty = bars + 208, lready = bars + 224, hout = bars + 240;
    const uint32_t tfull = bars + 256, aready = bars + 272, gatefull = bars + 280;
    const uint32_t otile = bars + 528;
    const uint32_t olim = bars + 504;
    const uint32_t stg = base + OFF_STG;
    uint32_t* rounds = reinterpret_cast<uint32_t*>(smem_raw + OFF_BAR + 416);
    const uint32_t rank = cluster_rank();
    int* jobs = reinterpret_cast<int*>(smem_raw + OFF_BAR + 312);
    auto w_map = [&](uint32_t rec, uint32_t half) INL { return &p.wmap[(rec & 8) ? 2 + half : ((rec >> 15) && half ? 0 : rec >> 4 & 1)]; };
    auto w_blk = [&](uint32_t rec, uint32_t half) INL -> int {
        const int col = rec >> 6 & 15;
        if (rec & 8) return (col + (rec & 16)) * 2;
        return rec >> 14 == 0 ? col * 4 + half * 2 : (rec >> 14 == 1 ? 16 + half * 16 + col * 2 : (half ? unit_head(col) : col) * 2);
    };
    auto load_round = [&](uint32_t rec, int st0, uint32_t parity) INL {
        const CUtensorMap* wm = w_map(rec, rank);
        const CUtensorMap* am = rec >> 14 ? &p.x_par : &p.amap[rec >> 3 & 1];
        const int wb = w_blk(rec, rank), kc0 = (rec >> 10 & 3) * 4, arow = ((rec & 7) * 256 + rank * 128) >> (rec >> 14 ? 1 : 0);
        const uint32_t bytes = (rec & 4096) ? G_STAGE - 16384 : G_STAGE, amode = (rec & 4096) ? 0 : (rec >> 14 ? 2 : 1);
#pragma unroll 1
        for (int st = st0; st < 4; st++) {
            const uint32_t sa = base + st * G_STAGE;
            mbar_wait(gempty + st * 8, parity);
            load_kstep(sa, sa + 16384 + rank * 16384, gfull + st * 8, bytes, wm, kc0 + st, wb, am, arow, kc0 + st, amode);
        }
    };
    if (threadIdx.x < 32) {
        if (elect_one()) {
            const uint2 r = p.first[blockIdx.x];
            mbar_init(gfull, 1);
            fence_async_smem();
            const char* maps;
            asm("mov.b64 %0, %1;" : "=l"(maps) : "l"(&p.amap[0]));
            asm volatile("{\n.reg .pred q;\nsetp.eq.u32 q, %8, 0;\n"
                         "mbarrier.arrive.expect_tx.shared::cta.b64 _, [%1], 49152;\n"
                         "cp.async.bulk.tensor.3d.shared::cluster.global.mbarrier::complete_tx::bytes.L2::cache_hint [%9], [%3, {0, 0, %6}], [%1], %11;\n"
                         "cp.async.bulk.tensor.3d.shared::cluster.global.mbarrier::complete_tx::bytes.L2::cache_hint [%10], [%4, {0, 0, %7}], [%1], %11;\n"
                         "@q cp.async.bulk.tensor.3d.shared::cluster.global.mbarrier::complete_tx::bytes.L2::cache_hint [%0], [%2, {0, %5, 0}], [%1], %11;\n"
                         "@!q cp.async.bulk.tensor.4d.shared::cluster.global.mbarrier::complete_tx::bytes.L2::cache_hint [%0], [%2, {0, %5, 0, 0}], [%1], %11;\n}"
                         ::"r"(base), "r"(gfull), "l"(maps + (r.x & 0x780)), "l"(maps + (r.x >> 4 & 0x780)), "l"(maps + (r.x >> 8 & 0x780)),
                           "r"(r.x >> 20), "r"(r.y & 0xffff), "r"(r.y >> 16), "r"(r.x & 1), "r"(base + 16384), "r"(base + 32768), "l"(POL_NORMAL) : "memory");
            asm volatile("fence.mbarrier_init.release.cluster;" ::: "memory");
        }
        __syncwarp();
    }
    const int tid = threadIdx.x, warp = uniform(tid >> 5), lane = tid & 31, wg = warp >> 2;
    if (warp == 1) {
        if (elect_one()) {
#pragma unroll
            for (int i = 1; i < 39; i++)
                mbar_init(bars + i * 8, (0x0CC000F0ull >> i & 1) ? 16 : ((0x300000F00ull >> i & 1) ? 4 : ((0xC0000ull >> i & 1) ? 8 : 1)));
            asm volatile("fence.mbarrier_init.release.cluster;" ::: "memory");
            fence_async_smem();
        }
        __syncwarp();
    }
    setup_arrive();
    if (warp > 3) {
        reg_inc<232>();
        named_sync(0, 352);
        const int w = wg - 1, wwarp = warp & 3;
        const uint32_t slot_a = stage_addr(stg + w * 16384, wwarp, lane);
        const uint32_t bars_peer = uniform(mapa(bars, rank ^ 1));
        auto arrive_pair = [&](uint32_t bar, bool pred = true) INL { warp_arrive_pair(bar, bars_peer + (bar - bars), pred); };
        uint32_t gph = 0;
        uint32_t sph = 1;
        int jb = 0;
        int job = uniform(jobs[0]);
        auto next_job = [&]() INL { jb++; job = uniform(jobs[jb]); };
        auto slot_wait = [&](int q) INL { mbar_wait(sempty + (w * 2 + (q & 1)) * 8, (q >> 1) ^ sph ^ 1); };
        auto signal = [&](int q) INL {
            __syncwarp();
            warp_arrive(sfull + (w * 2 + (q & 1)) * 8);
        };
        uint32_t pk[64];
        float O[64];
        float oscale1 = 1.f;
        uint32_t slot4[4];
        bool ptrans = false;
        auto stage_quarter = [&](const int Q) INL {
            slot_wait(Q);
            if (Q == 0) stage_packed_64x64<0>(slot4, 0, pk, ptrans);
            if (Q == 1) stage_packed_64x64<16>(slot4, 8192, pk, ptrans);
            if (Q == 2) stage_packed_64x64<32>(slot4, 0, pk);
            if (Q == 3) stage_packed_64x64<48>(slot4, 8192, pk);
        };
        auto stage_pair = [&]() INL {
            slot_wait(1);
            stage_packed_64x64<0>(slot4, 0, pk, ptrans);
            stage_packed_64x64<16>(slot4, 8192, pk, ptrans);
        };
        auto signal_both = [&]() INL {
            __syncwarp();
            warp_arrive2(sfull + w * 16, sfull + w * 16 + 8);
        };
        uint32_t un = 0;
        auto lane_id = [&]() INL { uint32_t ln; asm volatile("mov.u32 %0, %%laneid;" : "=r"(ln)); return ln; };
        auto v_addr = [&](uint32_t ln) INL { return stg + w * 16384 + (wwarp * 16 + (ln & 7)) * 128 + (((ln >> 3) ^ (ln & 7)) << 4); };
        auto v_off = [&](uint32_t a, const int h) INL { return (a ^ ((h & 1) * 64)) + (h >> 1) * 8192; };
        auto halo_ptr = [&](int mt, int g, int slot, uint32_t ln) INL { return page_ptr<uint4>(512) + (((mt * 8 + g) * 2 + w) * 5 + slot) * 128 + ln; };
        auto pack_k = [&](const float (&acc)[64]) INL {
#pragma unroll
            for (int j = 0; j < 16; j++) { pk[j] = pack_bf16(acc[4 * j], acc[4 * j + 1]); pk[16 + j] = pack_bf16(acc[4 * j + 2], acc[4 * j + 3]); }
        };
        auto unit_export = [&](int cur) INL {
            const uint32_t ln = lane_id();
            uint4* dst = halo_ptr((cur & 7) * 2 + rank, cur >> 3 & 7, wwarp, ln);
            slot_wait(1);
            stage_packed_64x64<32>(slot4, 0, pk);
            stage_packed_64x64<48>(slot4, 8192, pk);
#pragma unroll
            for (int h = 0; h < 4; h++) __stcg(dst + h * 32, make_uint4(pk[16 + h * 4], pk[17 + h * 4], pk[18 + h * 4], pk[19 + h * 4]));
            __syncwarp();
            if (wwarp == 3) {
                const uint32_t va = v_addr(ln) + 1024;
#pragma unroll
                for (int h = 0; h < 4; h++) {
                    uint32_t t[4];
                    ldmatrix_x4_t(v_off(va, h), t);
                    pk[32 + h * 4] = t[0]; pk[33 + h * 4] = t[1]; pk[34 + h * 4] = t[2]; pk[35 + h * 4] = t[3];
                }
#pragma unroll
                for (int h = 0; h < 4; h++) __stcg(dst + 128 + h * 32, make_uint4(pk[32 + h * 4], pk[33 + h * 4], pk[34 + h * 4], pk[35 + h * 4]));
                __syncwarp();
                warp_arrive(hout + w * 8);
            }
        };
        auto unit_import = [&](int cur) INL {
            const uint32_t ln = lane_id();
            const int mt = (cur & 7) * 2 + rank;
            mbar_wait(lready + un * 8, 0);
            un++;
            const uint4* src = halo_ptr(wwarp ? mt : max(mt - 1, 0), cur >> 3 & 7, (wwarp + 3) & 3, ln);
#pragma unroll
            for (int h = 0; h < 4; h++) {
                const uint4 t = __ldcg(src + h * 32);
                pk[32 + h * 4] = t.x; pk[33 + h * 4] = t.y; pk[34 + h * 4] = t.z; pk[35 + h * 4] = t.w;
            }
            if (wwarp) {
                const uint32_t va = v_addr(ln) - 1024;
#pragma unroll
                for (int h = 0; h < 4; h++) {
                    uint32_t t[4];
                    ldmatrix_x4_t(v_off(va, h), t);
                    pk[48 + h * 4] = t[0]; pk[49 + h * 4] = t[1]; pk[50 + h * 4] = t[2]; pk[51 + h * 4] = t[3];
                }
            } else {
#pragma unroll
                for (int h = 0; h < 4; h++) {
                    const uint4 t = __ldcg(src + 128 + h * 32);
                    pk[48 + h * 4] = t.x; pk[49 + h * 4] = t.y; pk[50 + h * 4] = t.z; pk[51 + h * 4] = t.w;
                }
            }
        };
        auto unit_attend = [&](const float (&q)[64], int cur) INL {
            const float cs = 0.17677669529663687f * 1.4426950408889634f;
            const uint32_t ln = lane_id();
            const int g = ln >> 2, c2 = (ln & 3) * 2, mt = (cur & 7) * 2 + rank;
            uint32_t qf[32], vo[8][4];
#pragma unroll
            for (int i = 0; i < 32; i++) qf[i] = pack_bf16(q[2 * i], q[2 * i + 1]);
            fence_regs(qf);
            const float* gp = page_ptr<float>(520) + mt * 128 + wwarp * 32 + g * 2 + w;
            const float lg0 = 1.f - __ldcg(gp), lg1 = 1.f - __ldcg(gp + 16);
            const uint32_t va = stg + w * 16384 + (wwarp * 16 + (ln & 7) + (ln >> 4) * 8) * 128 + ((((ln >> 3) & 1) ^ (ln & 7)) << 4);
#pragma unroll
            for (int i = 0; i < 8; i++) ldmatrix_x4_t((va ^ ((i & 3) * 32)) + (i >> 2) * 8192, vo[i]);
            const bool m0 = c2 > g, m1 = c2 + 1 > g, first = mt + wwarp == 0;
            const uint32_t mk = (m0 ? 0xffffu : 0u) | (m1 ? 0xffff0000u : 0u);
#pragma unroll
            for (int h = 0; h < 4; h++) {
                float s[3][4] = {};
#pragma unroll
                for (int k = 0; k < 2; k++) {
                    const int i = h * 8 + k * 4, j = h * 4 + k * 2;
                    mma_16816(s[0], qf[i], qf[i + 1], qf[i + 2], qf[i + 3], pk[32 + j], pk[33 + j]);
                    mma_16816(s[1], qf[i], qf[i + 1], qf[i + 2], qf[i + 3], pk[j], pk[j + 1]);
                    mma_16816(s[2], qf[i], qf[i + 1], qf[i + 2], qf[i + 3], pk[16 + j], pk[17 + j]);
                }
                if (first) s[0][0] = s[0][1] = -INFINITY;
                float u0 = m0 ? s[0][0] : s[1][0], u1 = m1 ? s[0][1] : s[1][1], v0 = m0 ? s[1][2] : s[2][2], v1 = m1 ? s[1][3] : s[2][3];
                float mu = fmaxf(u0, u1), mv = fmaxf(v0, v1);
                mu = fmaxf(mu, __shfl_xor_sync(0xffffffffu, mu, 1)); mv = fmaxf(mv, __shfl_xor_sync(0xffffffffu, mv, 1));
                mu = fmaxf(mu, __shfl_xor_sync(0xffffffffu, mu, 2)); mv = fmaxf(mv, __shfl_xor_sync(0xffffffffu, mv, 2));
                mu *= -cs; mv *= -cs;
                u0 = ex2(fmaf(u0, cs, mu)); u1 = ex2(fmaf(u1, cs, mu)); v0 = ex2(fmaf(v0, cs, mv)); v1 = ex2(fmaf(v1, cs, mv));
                float lu = u0 + u1, lv = v0 + v1;
                lu += __shfl_xor_sync(0xffffffffu, lu, 1); lv += __shfl_xor_sync(0xffffffffu, lv, 1);
                lu += __shfl_xor_sync(0xffffffffu, lu, 2); lv += __shfl_xor_sync(0xffffffffu, lv, 2);
                const float su = lg0 * rcp(lu), sv = lg1 * rcp(lv);
                const uint32_t pu = pack_bf16(u0 * su, u1 * su), pv = pack_bf16(v0 * sv, v1 * sv);
#pragma unroll
                for (int d = 0; d < 2; d++) {
                    const uint32_t (&vv)[4] = vo[h * 2 + d];
                    float oa[4] = {}, ob[4] = {};
                    mma_16816(oa, pk[48 + h * 4 + d * 2], pk[49 + h * 4 + d * 2], vv[0], vv[1], pu & mk, pu & ~mk);
                    mma_16816(ob, vv[0], vv[1], vv[2], vv[3], pv & mk, pv & ~mk);
                    qf[h * 8 + d * 4] = pack_bf16(oa[0], oa[1]); qf[h * 8 + d * 4 + 1] = pack_bf16(ob[0], ob[1]);
                    qf[h * 8 + d * 4 + 2] = pack_bf16(oa[2], oa[3]); qf[h * 8 + d * 4 + 3] = pack_bf16(ob[2], ob[3]);
                }
            }
#pragma unroll
            for (int i = 0; i < 32; i++) pk[i] = qf[i];
            named_sync(3 + w, 128);
        };
        auto pack_half = [&](const float (&acc)[64], const int OFF, float scale) INL {
#pragma unroll
            for (int i = 0; i < 32; i++) pk[OFF + i] = pack_bf16(acc[2 * i] * scale, acc[2 * i + 1] * scale);
        };
        auto gemm_run = [&]() INL {
                float acc0[64], acc1[64];
#pragma unroll
                for (int i = 0; i < 64; i++) pk[i] = 0;
#pragma unroll
                for (int j = 0; j < 4; j++) asm volatile("xor.b32 %0, %1, %2;" : "=r"(slot4[j]) : "r"(slot_a), "r"(j << 5));
                const uint32_t dA = desc_lo(base + w * 8192, 0), dB = desc_lo(base + 16384, 8192);
                auto wait_full = [&](int st) INL { mbar_wait_hot(gfull + st * 8, gph); };
                auto release = [&](int st) INL { arrive_pair(gempty + st * 8); };
                bool pend = false;
                auto kstep = [&](auto st_, const int Q, bool ending = false) INL {
                    constexpr int st = decltype(st_)::v, OA = st * (G_STAGE >> 4);
                    wait_full(st);
                    if (st == 2) named_sync_if(ending && w, 6, 256);
                    wg_fence();
                    wgmma_ss_n256<OA, OA>(acc0, acc1, dA, dB);
                    wg_commit();
                    wg_wait<1>();
                    release((st + 3) & 3);
                    wg_fence();
                    wgmma_ss_n256<OA + 2, OA + 128>(acc0, acc1, dA, dB);
                    wgmma_ss_n256<OA + 4, OA + 256>(acc0, acc1, dA, dB);
                    if (st == 3) named_arrive_if(ending && !w, 6, 256);
                    wgmma_ss_n256<OA + 6, OA + 384>(acc0, acc1, dA, dB);
                    wg_commit();
                    if (Q >= 0) { stage_quarter(Q); signal(Q); }
                    KTRACE(w);
                };
                wait_full(0);
                GTRACE(w);
                while (true) {
                    wg_fence();
                    wgmma_ss_n256_init(acc0, acc1, dA, dB);
                    wgmma_ss_n256<2, 128>(acc0, acc1, dA, dB);
                    wgmma_ss_n256<4, 256>(acc0, acc1, dA, dB);
                    wgmma_ss_n256<6, 384>(acc0, acc1, dA, dB);
                    wg_commit();
                    KTRACE(w);
                    const int cur = job;
                    const bool is_o = cur >= (T_O << 12), unit2 = (cur >> 6) == 3;
                    const int tail = o_tail(cur);
                    int lim = is_o ? o_head(cur) + tail : (cur < 256 ? 16 : 8);
                    int left = unit2 ? 11 : lim - (is_o ? O_STAGGER + 1 : 1);
                    bool imp = unit2;
                    next_job();
                    if (__builtin_expect(unit2, 0)) { if (tid == TRACE_TID) PTRACE(4); unit_export(cur); if (tid == TRACE_TID) PTRACE(5); }
                    if (pend) {
                        kstep(IC<1>{}, 0);
                        kstep(IC<2>{}, -1);
                        kstep(IC<3>{}, 1);
                        GTRACE(w);
                        gph ^= 1;
                        kstep(IC<0>{}, -1);
                        kstep(IC<1>{}, 2);
                        kstep(IC<2>{}, 3, left == 7);
                        kstep(IC<3>{}, -1, left == 7);
                        GTRACE(w);
                        gph ^= 1;
                        left -= 7;
                        if (left > 0) { kstep(IC<0>{}, -1); left--; }
                    }
                    int last_st = 3;
#pragma unroll 1
                    while (left > 0) {
                        auto ends = [&]() INL -> bool {
                            if (__builtin_expect(--left > 0, 1)) return false;
                            if (is_o) {
                                const uint32_t v = uniform(o_state(olim, lim - tail));
                                const int n = (v >> 1) + ((v & 1) ? 0 : tail);
                                left = n - lim; lim = n;
                            }
                            return left == 0;
                        };
                        kstep(IC<1>{}, -1);
                        if (ends()) { last_st = 1; break; }
                        kstep(IC<2>{}, -1, left == 2 && !is_o && !imp);
                        if (ends()) { last_st = 2; break; }
                        kstep(IC<3>{}, -1, left == 1 && !is_o && !imp);
                        GTRACE(w);
                        gph ^= 1;
                        if (ends()) {
                            if (!imp) break;
                            if (tid == TRACE_TID) PTRACE(6);
                            unit_import(cur);
                            if (tid == TRACE_TID) PTRACE(7);
                            imp = false; left = 4;
                        }
                        kstep(IC<0>{}, -1);
                        if (ends()) { last_st = 0; break; }
                    }
                    if (is_o) {
                        if (w) {
                            wg_wait<0>();
                            release(last_st);
                            named_sync(6, 256);
                        }
#pragma unroll 1
                        for (int i = 1; i <= O_STAGGER; i++) {
                            const int st = (last_st + i) & 3;
                            if (i > 1 && st == 0) gph ^= 1;
                            wait_full(st);
                            const uint32_t a = dA + st * (G_STAGE >> 4), b = dB + st * (G_STAGE >> 4);
                            wg_fence();
                            wgmma_ss_n256<0, 0>(acc0, acc1, a, b);
                            wgmma_ss_n256<2, 128>(acc0, acc1, a, b);
                            wgmma_ss_n256<4, 256>(acc0, acc1, a, b);
                            wgmma_ss_n256<6, 384>(acc0, acc1, a, b);
                            wg_commit();
                            named_arrive_if(!w && i == O_STAGGER, 6, 256);
                            wg_wait<1>();
                            arrive_pair(gempty + last_st * 8, i == 1 && !w);
                        }
                        slot_wait(1);
                        wg_wait<0>();
                        fence_regs(acc0);
                        fence_regs(acc1);
                        auto put = [&](const float (&acc)[64], const int Q, int off) INL {
#pragma unroll
                            for (int j = 0; j < 4; j++) {
                                const float* o = acc + Q * 32 + j * 8;
                                stmatrix_x4(slot4[j] + off, pack_bf16(o[0], o[1]), pack_bf16(o[2], o[3]), pack_bf16(o[4], o[5]), pack_bf16(o[6], o[7]));
                            }
                        };
                        put(acc0, 0, 0);
                        signal(0);
                        put(acc0, 1, 8192);
                        signal(1);
                        put(acc1, 0, -OFF_STG - w * 8192);
                        put(acc1, 1, G_STAGE - OFF_STG - w * 8192);
                        __syncwarp();
                        warp_arrive(tfull + w * 8);
#pragma unroll
                        for (int i = 1; i <= O_STAGGER; i++) release((last_st + i) & 3);
                        GTRACE(w);
#pragma unroll
                        for (int i = 0; i < 64; i++) O[i] = 0.f;
                        break;
                    }
                    if (tid == 128 && !is_o) PTRACE(12);
                    oscale1 = cur < 128 || unit2 ? Q_SCALE : 1.f;
                    ptrans = unit2;
                    if (tid == TRACE_TID && unit2) PTRACE(1);
                    named_arrive_if(w && job >= (T_A << 12), 1, TURN_THREADS);
                    wg_wait<0>();
                    fence_regs(acc0);
                    fence_regs(acc1);
                    release(3);
                    if (tid == TRACE_TID && unit2) PTRACE(2);
                    if (__builtin_expect(unit2, 0)) { unit_attend(acc0, cur); if (tid == TRACE_TID) PTRACE(3); }
                    else if (__builtin_expect((cur >> 6) == 2, 0)) pack_k(acc0);
                    else if (cur < 128) pack_half(acc0, 0, Q_SCALE);
                    else pack_half(acc0, 0, 1.f);
                    if (job >= (T_A << 12)) {
                        stage_pair();
                        signal_both();
#pragma unroll
                        for (int i = 0; i < 64; i++) asm volatile("mul.f32 %0, %1, %2;" : "=f"(O[i]) : "f"(acc1[i]), "f"(oscale1));
                        break;
                    }
                    if (cur < 128 || unit2) pack_half(acc1, 32, Q_SCALE);
                    else pack_half(acc1, 32, 1.f);
                    fence_regs(pk);
                    wait_full(0);
                    pend = (cur >> 6) != 2;
                }
        };
        setup_wait();
#pragma unroll 1
        while (true) {
        gemm_run();
        if (job < 0) break;
        if (tid == 128) PTRACE(11);
        GTRACE(w);
        {
            {
                sph ^= 1;
                uint32_t step = ~0u, ajob = ~0u;
                const int r0 = w * 64 + wwarp * 16 + (lane >> 2);
                float S[64];
                uint32_t P[32] = {};
                fence_regs(P);
                float m0 = 0.f, m1 = 0.f, l0 = 0.25f, l1 = 0.25f, g0 = 1.f, g1 = 1.f, e0 = 0.f, e1 = 0.f;
                constexpr float SUM_MAX = 1.1529215e18f;
                float sum_max = SUM_MAX;
                int rem = 0;
                int maskrem = 0;
                uint32_t starts = 1;
                auto issue_S = [&]() INL {
                    const uint32_t da = desc_lo(base + OFF_Q0 + w * 8192, 0) + (ajob & 1) * ((OFF_Q1 - OFF_Q0) >> 4);
                    const uint32_t db = desc_lo(base + OFF_K0, 0) + (step & 1) * ((OFF_K1 - OFF_K0) >> 4);
                    wg_fence();
                    wgmma_ss_n128_init<0, 0, 0>(S, da, db);
                    wgmma_ss_n128_tb0<2, 2>(S, da, db, 1);
                    wgmma_ss_n128_tb0<4, 4>(S, da, db, 1);
                    wgmma_ss_n128_tb0<6, 6>(S, da, db, 1);
                    wgmma_ss_n128_tb0<1024, 1024>(S, da, db, 1);
                    wgmma_ss_n128_tb0<1026, 1026>(S, da, db, 1);
                    wgmma_ss_n128_tb0<1028, 1028>(S, da, db, 1);
                    wgmma_ss_n128_tb0<1030, 1030>(S, da, db, 1);
                    wg_commit();
                };
                auto issue_PV = [&](uint32_t t, int pass) INL {
                    const uint32_t db = desc_lo(base + OFF_V0, 16384) + (t & 1) * ((OFF_V1 - OFF_V0) >> 4);
                    mbar_wait_hot(vfull + (t & 1) * 8, (t >> 1) & 1);
                    wg_fence();
                    wgmma_rs_n128_tb1<0>(O, P[0], P[1], P[2], P[3], db, !(starts & 2));
                    wgmma_rs_n128_tb1<128>(O, P[4], P[5], P[6], P[7], db, 1);
                    wgmma_rs_n128_tb1<256>(O, P[8], P[9], P[10], P[11], db, 1);
                    wgmma_rs_n128_tb1<384>(O, P[12], P[13], P[14], P[15], db, 1);
                    if (pass) named_arrive(pass, TURN_THREADS);
                    wgmma_rs_n128_tb1<512>(O, P[16], P[17], P[18], P[19], db, 1);
                    wgmma_rs_n128_tb1<640>(O, P[20], P[21], P[22], P[23], db, 1);
                    wgmma_rs_n128_tb1<768>(O, P[24], P[25], P[26], P[27], db, 1);
                    wgmma_rs_n128_tb1<896>(O, P[28], P[29], P[30], P[31], db, 1);
                    wg_commit();
                };
                auto pv_done = [&](uint32_t t) INL {
                    wg_wait<0>();
                    fence_regs(O);
                    arrive_pair(vempty + (t & 1) * 8, t != ~0u);
                };
                auto row_max = [&](float& a0, float& a1) INL {
                    a0 = fmaxf(S[0], S[1]); a1 = fmaxf(S[2], S[3]);
#pragma unroll
                    for (int j = 1; j < 16; j++) {
                        a0 = fmaxf(a0, fmaxf(S[j * 4], S[j * 4 + 1]));
                        a1 = fmaxf(a1, fmaxf(S[j * 4 + 2], S[j * 4 + 3]));
                    }
                    a0 = fmaxf(a0, __shfl_xor_sync(0xffffffffu, a0, 1));
                    a1 = fmaxf(a1, __shfl_xor_sync(0xffffffffu, a1, 1));
                    a0 = fmaxf(a0, __shfl_xor_sync(0xffffffffu, a0, 2));
                    a1 = fmaxf(a1, __shfl_xor_sync(0xffffffffu, a1, 2));
                };
                auto mask_diag = [&]() INL {
                    const int d = (r0 & 63) - (lane & 3) * 2;
                    auto mask_block = [&](const int J0) INL {
                        bool up0 = false, up1 = false;
#pragma unroll
                        for (int j = 0; j < 8; j++) {
                            const bool c0 = j * 8 > d, c1 = j * 8 + 1 > d;
                            if (c0) S[(J0 + j) * 4] = -INFINITY;
                            if (c1) S[(J0 + j) * 4 + 1] = -INFINITY;
                            if (up0) S[(J0 + j) * 4 + 2] = -INFINITY;
                            if (up1) S[(J0 + j) * 4 + 3] = -INFINITY;
                            up0 = c0; up1 = c1;
                        }
                    };
                    if (w) {
                        mask_block(8);
                    } else {
                        mask_block(0);
#pragma unroll
                        for (int i = 32; i < 64; i++) S[i] = -INFINITY;
                    }
                };
                auto exp_part = [&](float& t0, float& t1, const int J0, const int J1, const bool SUB) INL {
#pragma unroll
                    for (int j = J0; j < J1; j++) {
                        const float e0 = ex2(SUB ? S[j * 4] - m0 : S[j * 4]), e1 = ex2(SUB ? S[j * 4 + 1] - m0 : S[j * 4 + 1]);
                        const float e2 = ex2(SUB ? S[j * 4 + 2] - m1 : S[j * 4 + 2]), e3 = ex2(SUB ? S[j * 4 + 3] - m1 : S[j * 4 + 3]);
                        t0 = (j ? t0 : l0) + (e0 + e1);
                        t1 = (j ? t1 : l1) + (e2 + e3);
                        P[j * 2] = pack_bf16(e0, e1);
                        P[j * 2 + 1] = pack_bf16(e2, e3);
                    }
                };
                auto exp_head = [&](float& t0, float& t1, auto j1_) INL {
                    constexpr int J1 = decltype(j1_)::v;
                    float E[J1 * 4];
#pragma unroll
                    for (int j = 0; j < J1; j++) {
#pragma unroll
                        for (int e = 0; e < 4; e++) E[j * 4 + e] = ex2(S[j * 4 + e]);
                        t0 = (j ? t0 : l0) + (E[j * 4] + E[j * 4 + 1]);
                        t1 = (j ? t1 : l1) + (E[j * 4 + 2] + E[j * 4 + 3]);
                    }
                    order_after(t0 + t1, bars + 508);
                    pv_done(step - 1);
                    fence_regs(P);
                    fence_regs(S);
                    fence_regs(E);
#pragma unroll
                    for (int i = 0; i < J1 * 2; i++) P[i] = pack_bf16(E[i * 2], E[i * 2 + 1]);
                };
                auto close_job = [&]() INL {
                    l0 += __shfl_xor_sync(0xffffffffu, l0, 1); l1 += __shfl_xor_sync(0xffffffffu, l1, 1);
                    l0 += __shfl_xor_sync(0xffffffffu, l0, 2); l1 += __shfl_xor_sync(0xffffffffu, l1, 2);
                    e0 = g0 * rcp(l0); e1 = g1 * rcp(l1);
                };
                auto put_O = [&]() INL {
                    mbar_wait_hot(sempty + (w * 2 + 1) * 8, sph ^ 1);
                    uint32_t a[4];
#pragma unroll
                    for (int j = 0; j < 4; j++) asm volatile("xor.b32 %0, %1, %2;" : "=r"(a[j]) : "r"(slot_a), "r"(j << 5));
                    const uint32_t h0 = pack_bf16(e0, e0), h1 = pack_bf16(e1, e1);
#pragma unroll
                    for (int q = 0; q < 8; q++) {
                        const float* o = O + q * 8;
                        stmatrix_x4(a[q & 3] + (q >> 2) * 8192, mul_bf16x2(pack_bf16(o[0], o[1]), h0), mul_bf16x2(pack_bf16(o[2], o[3]), h1),
                                    mul_bf16x2(pack_bf16(o[4], o[5]), h0), mul_bf16x2(pack_bf16(o[6], o[7]), h1));
                    }
                    sph ^= 1;
                    signal_both();
                };
                auto exp_plain = [&](float& t0, float& t1) INL {
                    exp_head(t0, t1, IC<5>{});
                    exp_part(t0, t1, 5, 16, false);
                    fence_regs(P);
                };
                auto exp_diag = [&](float& t0, float& t1) INL {
                    const int d = warp - 4, dd = (r0 & 7) - (int)(slot_a >> 6 & 6);
                    auto tri = [&](const int B) INL {
                        if (0 > dd) S[8 * B] = S[8 * B + 6] = -INFINITY;
                        if (1 > dd) S[8 * B + 1] = S[8 * B + 7] = -INFINITY;
                        S[8 * B + 4] = S[8 * B + 5] = -INFINITY;
                        asm volatile("" ::: "memory");
                    };
                    auto blocks = [&](const int B) INL {
                        auto zero = [&](const int B0) INL {
#pragma unroll
                            for (int i = 4 * B0; i < 4 * B + 12; i++) P[i] = 0;
                            asm volatile("" ::: "memory");
                        };
                        auto block = [&](const int B0) INL { exp_part(t0, t1, 2 * B0, 2 * B0 + 2, false); asm volatile("" ::: "memory"); };
                        if (d < B) zero(B);
                        else {
                            block(B);
                            if (d < B + 1) zero(B + 1);
                            else {
                                block(B + 1);
                                if (d < B + 2) zero(B + 2); else block(B + 2);
                            }
                        }
                    };
                    if (d > 3) {
                        if (d < 6) { if (d == 4) tri(4); else tri(5); } else { if (d == 6) tri(6); else tri(7); }
                        exp_head(t0, t1, IC<5>{});
                        exp_part(t0, t1, 5, 10, false);
                        blocks(5);
                    } else {
                        if (d < 2) { if (d == 0) tri(0); else tri(1); } else { if (d == 2) tri(2); else tri(3); }
                        exp_head(t0, t1, IC<2>{});
#pragma unroll
                        for (int i = 16; i < 32; i++) P[i] = 0;
                        blocks(1);
                    }
                    fence_regs(P);
                };
                auto unsafe_tile = [&](float t0, float t1, bool fresh) INL -> bool {
                    const bool unsafe = !(t0 + t1 <= sum_max) |
                                        (fresh & ((slot_a & 0x180) == 0) & !(fminf(t0, t1) >= 8.6736174e-19f));
                    return __any_sync(0xffffffffu, unsafe);
                };
                auto redo_tile = [&](float& t0, float& t1, bool fresh) INL {
                    wg_wait<0>();
                    fence_regs(O);
                    if (rem == maskrem) mask_diag();
                    float a0, a1;
                    row_max(a0, a1);
                    if (!fresh) { a0 = fmaxf(a0, m0); a1 = fmaxf(a1, m1); }
                    const float c0 = fresh ? 1.f : ex2(m0 - a0), c1 = fresh ? 1.f : ex2(m1 - a1);
                    m0 = a0; m1 = a1; sum_max = -1.f;
                    l0 *= c0; l1 *= c1;
#pragma unroll
                    for (int j = 0; j < 16; j++) { O[j * 4] *= c0; O[j * 4 + 1] *= c0; O[j * 4 + 2] *= c1; O[j * 4 + 3] *= c1; }
                    exp_part(t0, t1, 0, 16, true);
                };
                auto finish = [&]() INL {
                    if (starts & 2) put_O();
                    named_sync(1 + w, TURN_THREADS);
                    TRACE_MARK(0, w, step + 1);
                    issue_PV(step, w == 0 ? 2 : 0);
                    close_job();
                    pv_done(step);
                    put_O();
                };
                auto open_job = [&]() INL {
                    ajob++; rem = (job & 15) + 1; maskrem = (job & 512) ? 0 : job & 15;
                };
                auto do_step = [&]() INL -> bool {
                    float t0, t1;
                    const bool fresh = starts & 1, pending = starts & 2;
                    rem--; step++;
                    named_sync(1 + w, TURN_THREADS);
                    TRACE_MARK(0, w, step);
                    issue_S();
                    if (__builtin_expect(pending || fresh, 0)) {
                        if (pending) put_O();
                        if (fresh) {
                            close_job();
                            g0 = __ldcg(g_gate + (job & 15) * 128 + r0); g1 = __ldcg(g_gate + (job & 15) * 128 + r0 + 8);
                            l0 = 0.f; l1 = 0.f; m0 = 0.f; m1 = 0.f; sum_max = SUM_MAX;
                            if (step == 0) {
                                wg_fence();
                                wg_commit();
                                named_arrive(2 - w, TURN_THREADS);
                                goto issued;
                            }
                        }
                    }
                    issue_PV(step - 1, 2 - w);
                issued:
                    starts = (starts << 1 & 2) | (rem == 0);
                    TRACE_MARK(1, w, step);
                    wg_wait<1>();
                    fence_regs(S);
                    arrive_pair(kempty + (step & 1) * 8);
                    TRACE_MARK(2, w, step);
                    if (__builtin_expect(rem != maskrem, 1)) {
                        exp_plain(t0, t1);
                        if (__builtin_expect(!unsafe_tile(t0, t1, false) && starts == 0, 1)) {
                            l0 = t0; l1 = t1;
                            TRACE_MARK(3, w, step);
                            return true;
                        }
                    } else {
                        exp_diag(t0, t1);
                    }
                    if (unsafe_tile(t0, t1, fresh)) redo_tile(t0, t1, fresh);
                    l0 = t0; l1 = t1;
                    TRACE_MARK(3, w, step);
                    if (rem == 0) {
                        warp_arrive(qempty + (ajob & 1) * 8);
                        next_job();
                        if ((job >> 12) != T_A) return false;
                        open_job();
                    }
                    return true;
                };
                open_job();
#pragma unroll 1
                while (do_step()) {}
                finish();
            }
        }
        GTRACE(w);
        jb = uniform(jb); job = uniform(job); sph = uniform(sph); gph = uniform(gph);
        if (job < 0) break;
        }
    } else {
        reg_dec<40>();
        if (base & 1023) __trap();
        if (warp == 0) {
            const uint2 r = p.first[blockIdx.x];
            const char* maps = reinterpret_cast<const char*>(&p.amap[0]);
            const CUtensorMap* wm = reinterpret_cast<const CUtensorMap*>(maps + (r.x >> (rank ? 8 : 4) & 0x780));
            const CUtensorMap* am = reinterpret_cast<const CUtensorMap*>(maps + (r.x & 0x780));
            const int wb = rank ? r.y >> 16 : r.y & 0xffff;
            setup_wait();
#pragma unroll 1
            for (int st = 1; st < 4; st++) {
                const uint32_t sa = base + st * G_STAGE;
                load_kstep(sa, sa + 16384 + rank * 16384, gfull + st * 8, G_STAGE, wm, st, wb, am, r.x >> 20, st, 1 + (r.x & 1));
            }
            named_sync(7, 96);
        } else {
            if (warp == 2) {
                const int jl = lane < MAX_JOBS ? p.jobs[blockIdx.x][lane] : -1;
                if (lane <= MAX_JOBS) jobs[lane] = jl;
                if ((jl >> 12) == T_O) *reinterpret_cast<volatile uint32_t*>(smem_raw + OFF_BAR + 504) = 2 * o_head(jl);
                if (lane == 31) *reinterpret_cast<volatile uint32_t*>(smem_raw + OFF_BAR + 528) = 0;
            } else if (warp == 3) {
                if (lane == 31) *reinterpret_cast<ulonglong2*>(smem_raw + OFF_BAR + 512) = make_ulonglong2((uint64_t)g_halo, (uint64_t)g_gate);
                if (lane < MAX_ROUNDS / 2) rounds[lane] = reinterpret_cast<const uint32_t*>(p.rounds[blockIdx.x >> 1])[lane];
            }
            named_arrive_if(warp > 1, 7, 96);
            named_sync(0, 352);
            setup_wait();
        }
        volatile uint32_t* epoch_word = reinterpret_cast<volatile uint32_t*>(smem_raw + OFF_BAR + 532);
        uint32_t epoch1 = 0;
        if (warp > 0) {
        if (warp == 3) { epoch1 = uniform(ld_acquire(g_flags + F_DONE)) / NUM_SMS + 1; if (lane == 0) *epoch_word = epoch1; }
        {
            if (warp == 1 && elect_one()) {
#pragma unroll
                for (int i = 0; i < 7; i++) prefetch_map(&p.amap[0] + i);
            }
            __syncwarp();
            if (warp < 3) __nanosleep(jobs[0] < 256 ? GATE_DELAY_LONG_NS : GATE_DELAY_SHORT_NS);
            if (tid == TRACE_GATE) PTRACE(10);
            float* gate_vals = reinterpret_cast<float*>(smem_raw + OFF_BAR + 576);
            if (warp == 3) {
                if (blockIdx.x == 0) g_flags[F_SPLIT + lane] = g_flags[F_TICKET + lane] = 0;
                named_sync(5, 96);
                if (lane < 16 && blockIdx.x + lane * NUM_SMS < SEQ) g_gate[blockIdx.x + lane * NUM_SMS] = 1.f / (1.f + __expf(-gate_vals[lane]));
                if (tid == TRACE_GATE) PTRACE(9);
                __threadfence();
                __syncwarp();
                if (lane == 0) red_release(g_flags + F_GATE);
            } else {
                const uint32_t bar = gatefull + (warp - 1) * 16;
                auto fetch = [&](int r) INL {
                    if (lane == 0) mbar_expect_tx(bar + (r & 2) * 4, 4096);
                    __syncwarp();
                    if (lane < 2) asm volatile("cp.async.bulk.shared::cluster.global.mbarrier::complete_tx::bytes [%0], [%1], 2048, [%2];"
                                               ::"r"(stg + ((warp - 1) * 8 + r + lane) * 2048), "l"(p.xp + (size_t)min((int)blockIdx.x + ((warp - 1) * 8 + r + lane) * NUM_SMS, SEQ - 1) * DM), "r"(bar + (r & 2) * 4) : "memory");
                };
                fetch(0); fetch(2);
                uint32_t gw[16];
#pragma unroll
                for (int i = 0; i < 4; i++) {
                    const uint4 t = __ldg(reinterpret_cast<const uint4*>(p.gate_w) + i * 32 + lane);
                    gw[i * 4] = t.x; gw[i * 4 + 1] = t.y; gw[i * 4 + 2] = t.z; gw[i * 4 + 3] = t.w;
                }
#pragma unroll 1
                for (int r = 0; r < 8; r += 2) {
                    mbar_wait(bar + (r & 2) * 4, r >> 2);
                    if (r < 4) fetch(r + 4);
                    fence_regs(gw);
                    float acc0 = 0.f, acc1 = 0.f;
                    uint32_t ln;
                    asm volatile("mov.u32 %0, %%laneid;" : "=r"(ln));
#pragma unroll
                    for (int i = 0; i < 4; i++) {
                        const uint4* xr = reinterpret_cast<const uint4*>(smem_raw + OFF_STG + ((warp - 1) * 8 + r) * 2048) + i * 32 + ln;
                        const uint4 a = xr[0], c = xr[128];
                        const uint32_t av[4] = {a.x, a.y, a.z, a.w}, cv[4] = {c.x, c.y, c.z, c.w};
#pragma unroll
                        for (int e = 0; e < 4; e++) {
                            const float lo = __uint_as_float(gw[i * 4 + e] << 16), hi = __uint_as_float(gw[i * 4 + e] & 0xffff0000u);
                            acc0 = fmaf(__uint_as_float(av[e] << 16), lo, acc0);
                            acc1 = fmaf(__uint_as_float(cv[e] << 16), lo, acc1);
                            acc0 = fmaf(__uint_as_float(av[e] & 0xffff0000u), hi, acc0);
                            acc1 = fmaf(__uint_as_float(cv[e] & 0xffff0000u), hi, acc1);
                        }
                    }
                    float t = (lane < 16 ? acc0 : acc1) + __shfl_xor_sync(0xffffffffu, lane < 16 ? acc1 : acc0, 16);
#pragma unroll
                    for (int o = 8; o > 0; o >>= 1) t += __shfl_xor_sync(0xffffffffu, t, o);
                    if ((lane & 15) == 0) gate_vals[(warp - 1) * 8 + r + (lane >> 4)] = t;
                }
                uint32_t t2;
                asm volatile("mov.u32 %0, %%tid.x;" : "=r"(t2));
                warp_arrive2(sempty - 16 + (t2 >> 5) * 16, sempty - 8 + (t2 >> 5) * 16);
                named_arrive(5, 96);
                if (tid == TRACE_GATE) PTRACE(9);
            }
            if (tid == TRACE_GATE) PTRACE(8);
        }
        if (warp < 3) {
            if (elect_one()) {
                const int w = warp - 1;
                uint32_t qn = 0, un = 0;
                prefetch_map(&p.qkv_st); prefetch_map(&p.st_par);
                for (int jb = 0; jb < MAX_JOBS; jb++) {
                    const int job = jobs[jb];
                    if (job < 0) break;
                    const int type = job >> 12, pl = type == T_O ? o_state(otile, 0) >> 1 : job & 0xFFF;
                    const CUtensorMap* map = &p.qkv_st;
                    int nq = 4, mt, ob0, ob1, flag, flag2 = -1;
                    bool par = false;
                    if (type <= T_O) {
                        const int n = pl >> 3;
                        mt = (pl & 7) * 2 + rank;
                        if (type == T_O)  {
                            map = &p.out_st; ob0 = (n & 3) * 4; ob1 = ob0 + 2; flag = -1;
                            for (uint32_t tries = 0; (int32_t)(ld_acquire(g_flags + F_OUT + pl * 2 + rank) - *epoch_word) < 0; tries++) {
                                __nanosleep(300);
                                if (tries > (1u << 22)) __trap();
                            }
                            fence_async_global();
                        }
                        else if (n < 16)  { ob0 = n * 4; ob1 = ob0 + 2; flag = F_Q + n * 32 + mt; flag2 = flag + 16; }
                        else if (n < 24)  {
                            mbar_wait(hout + w * 8, un++ & 1);
                            nq = ob0 = ob1 = 0; flag = F_H + mt * 8 + (n & 7);
                        } else if (n < 32) {
                            par = true; ob0 = 192 + (n & 7) * 2; ob1 = unit_head(n & 7) * 2;
                            flag = F_CTX + mt * 40 + 32 + (n & 7); flag2 = F_Q + ob1 * 8 + mt;
                        } else            { ob0 = n * 2; ob1 = ob0 + 64; flag = F_KV + (n - 32) * 16 + mt; }
                    } else {
                        nq = 2; mt = pl & 15; ob0 = ob1 = ((pl >> 4) & 31) * 2; flag = F_CTX + mt * 40 + ((pl >> 4) & 31);
                    }
                    for (int q = 0; q < nq; q++, qn++) {
                        const uint32_t slot = w * 2 + (qn & 1);
                        const int blk = (q < 2 ? ob0 : ob1) + (q & 1);
                        if (type == T_O && q == 2) {
                            mbar_wait(tfull + w * 8, 0);
                            fence_async_smem();
                            tma_reduce_add_3d(map, base + w * 8192, 0, mt * 128 + w * 64, ob1);
                            tma_reduce_add_3d(map, base + G_STAGE + w * 8192, 0, mt * 128 + w * 64, ob1 + 1);
                            bulk_commit();
                            break;
                        }
                        mbar_wait(sfull + slot * 8, (qn >> 1) & 1);
                        fence_async_smem();
                        if (type == T_O) {
                            tma_reduce_add_3d(map, stg + slot * 8192, 0, mt * 128 + w * 64, blk);
                        } else if (par) {
                            tma_store_par(&p.st_par, stg + slot * 8192, mt * 64, w, blk);
                        } else {
                            tma_store_3d(map, stg + slot * 8192, 0, mt * 128 + w * 64, blk, POL_STREAM);
                        }
                        bulk_commit();
                        if (type == T_O) continue;
                        if (!(q & 1)) continue;
                        bulk_wait_read<1>();
                        mbar_arrive(sempty + (slot ^ 1) * 8);
                        bulk_wait_read<0>();
                        mbar_arrive(sempty + slot * 8);
                    }
                    bulk_wait<0>();
                    END_MARK(jb);
                    if (flag >= 0) {
                        asm volatile("fence.release.gpu;" ::: "memory");
                        red_relaxed(g_flags + flag);
                        if (flag2 >= 0) red_relaxed(g_flags + flag2);
                    }
                }
            }
        } else {
            int jb = 0;
            for (int un = 0; (jobs[jb] >> 12) == T_P; jb++) {
                const int n = jobs[jb] >> 3, mt = (jobs[jb] & 7) * 2 + rank;
                if ((n >> 3) != 3) continue;
                wait_flags<200>(lane == 31 || (lane == 0 && mt > 0), lane == 31 ? F_GATE : F_H + max(mt - 1, 0) * 8 + (n & 7),
                                epoch1 * (lane == 31 ? GATE_COUNT : 2));
                if (lane == 0) mbar_arrive(lready + un * 8);
                un++;
            }
            if ((jobs[jb] >> 12) != T_A) {
                wait_flags<200>(lane == 0, F_GATE, epoch1 * GATE_COUNT);
                if (lane == 0) { mbar_arrive(aready); red_relaxed(g_flags + F_DONE); }
            } else {
                const int jh = jobs[jb] >> 4 & 31, jq = jobs[jb] & 15;
                wait_flags<100>(lane <= jq || lane >= 30, lane == 31 ? F_GATE : (lane == 30 ? F_Q + jh * 16 + jq : F_KV + jh * 16 + (lane & 15)),
                                epoch1 * (lane == 31 ? GATE_COUNT : 2));
                if (lane == 0) { mbar_arrive(aready); red_relaxed(g_flags + F_DONE); }
            int left = 0, nxt = jobs[jb];
            uint32_t ajob = 0;
#pragma unroll 1
            for (uint32_t astep = 0;; astep++) {
                if (left == 0) {
                    if ((nxt >> 12) != T_A) break;
                    left = (nxt & 15) + 1;
                    nxt = jobs[++jb];
                    mbar_wait(qfull + (ajob & 1) * 8, (ajob >> 1) & 1);
                    ajob++;
                }
                left--;
                mbar_wait(kfull + (astep & 1) * 8, (astep >> 1) & 1);
                named_sync(1, TURN_THREADS);
                named_sync(2, TURN_THREADS);
            }
            named_sync(1, TURN_THREADS);
            named_sync(2, TURN_THREADS);
            }
            if (jobs[jb] == (T_O << 12)) {
                mbar_wait(gatefull, 0);
                const int tile = o_state(otile, 0) >> 1;
                uint4* dst = reinterpret_cast<uint4*>(p.out) + ((tile & 7) * 256 + rank * 128) * (DM / 8) + (tile >> 3) * 32 + lane;
#pragma unroll 4
                for (int r = 0; r < 128; r++) {
                    dst[r * (DM / 8)] = make_uint4(0, 0, 0, 0);
                    if ((r & 3) == 3) __nanosleep(CLEAR_GAP_NS);
                }
                __threadfence();
                fence_async_global();
                __syncwarp();
                if (lane == 0) red_release(g_flags + F_OUT + tile * 2 + rank);
            }
        }
        } else {
            uint32_t gph = 1;
            int vrow = 0, vblk = 0;
            bool vsolo = false;
            auto load_kv = [&](uint32_t dst, uint32_t bar, int row, int blk, bool solo) INL {
                load_operand(dst, bar, &p.qkv_ld, &p.qkv_half, row, blk, rank, solo, POL_NORMAL);
            };
            auto load_v = [&](uint32_t t) INL {
                if (t == 0) mbar_wait(gempty + 24, gph);
                mbar_wait(vempty + (t & 1) * 8, ((t >> 1) & 1) ^ 1);
                load_kv(base + ((t & 1) ? OFF_V1 : OFF_V0), vfull + (t & 1) * 8, vrow, vblk, vsolo);
            };
            int jb = __ffs(__ballot_sync(0xffffffffu, lane <= MAX_JOBS && (jobs[min(lane, MAX_JOBS)] >> 12) != T_P)) - 1;
            int cur = uniform(jobs[jb]);
            auto announce = [&](uint32_t word, uint32_t v) INL {
                asm volatile("{\n.reg .pred p;\nsetp.lt.u32 p, %2, 2;\n@p red.relaxed.cluster.shared::cluster.max.u32 [%0], %1;\n}"
                             ::"r"(mapa(word, lane & 1)), "r"(v), "r"(lane) : "memory");
                __syncwarp();
            };
            uint32_t ticket = 0;
            auto draw_ticket = [&](int ojob) INL {
                asm volatile("{\n.reg .pred p;\nsetp.ne.u32 p, %2, 0;\n@p atom.relaxed.gpu.global.inc.u32 %0, [%1], 0x7fffffff;\n}"
                             : "+r"(ticket) : "l"(g_flags + F_TICKET + (ojob >> 5 & 1)), "r"((uint32_t)(rank == 0 && lane == 0)) : "memory");
                __syncwarp();
            };
            int pl = 0;
            uint32_t seen_a = 0, seen_b = 0;
            auto ask_ctx = [&]() INL {
                const uint32_t* f = g_flags + F_CTX + ((pl & 7) * 2 + rank) * 40;
                seen_a = ld_relaxed(f + lane); seen_b = ld_relaxed(f + 32 + (lane & 7));
            };
            auto open_tile = [&](int ojob) INL {
                if (rank == 0) {
                    const uint32_t t = uniform(ticket);
                    announce(otile, 2 * ((ojob & 32) ? 31 - t : t) + 1);
                }
                pl = (ojob & 32) | uniform(o_state(otile, 0) >> 1);
                ask_ctx();
            };
            const uint16_t* recs = reinterpret_cast<const uint16_t*>(rounds);
            uint32_t rec = uniform(recs[0]), nrec = uniform(recs[1]);
            int st0 = 4;
#pragma unroll 1
            for (int r = 2; rec != 0xFFFF; r++) {
                const uint32_t nnrec = recs[r];
                load_round(rec, st0, gph);
                gph ^= 1;
                st0 = 0;
                rec = nrec; nrec = uniform(nnrec);
                if (nrec == 0xFFFF || (rec & 8192)) {
                    if (nrec != 0xFFFF) {
                        prefetch_map(&p.qkv_ld); prefetch_map(&p.qkv_half);
                        if ((cur >> 12) == T_O) { prefetch_map(&p.wo_a); prefetch_map(&p.wo_b); prefetch_map(&p.out_st); }
                    } else if ((cur >> 12) == T_O) {
                        if (rec != 0xFFFF) {
                            mbar_wait(aready, 0);
                            draw_ticket(cur);
                        } else {
                            open_tile(cur);
                        }
                    }
                }
            }
            int nxt = cur;
            uint32_t astep = 0;
            if ((cur >> 12) == T_A) {
            {
                const int jh = cur >> 4 & 31, jq = cur & 15, j0 = (cur & 512) ? 0 : jq;
                mbar_wait(aready, 0);
                fence_async_global();
                mbar_wait(gempty, gph);
                load_operand(base + OFF_Q0, qfull, &p.qkv_ld, &p.qkv_ld, jq * 128, jh * 2, 0, true, POL_STREAM);
                PTRACE(17);
                mbar_wait(gempty + 8, gph);
                load_kv(base + OFF_K0, kfull, j0 * 128, 64 + jh * 2, j0 == jq && (jq & 1));
                PTRACE(16);
            }
            epoch1 = *epoch_word;
            jb++;
            nxt = uniform(jobs[jb]);
            int i = 0;
            uint32_t ajob = 1;
            bool q_issued = false;
#pragma unroll 1
            while (true) {
                const int qt = cur & 15;
                const bool last = i == qt;
                const int j = (cur & 512) ? i : qt - i, blk = (cur >> 4 & 31) * 2;
                const bool solo = j == qt && (qt & 1);
                {
                    const uint32_t sl = astep & 1;
                    if (astep == 0) {
                        mbar_wait(gempty + 16, gph);
                    } else {
                        mbar_wait(kempty + sl * 8, ((astep >> 1) & 1) ^ 1);
                        load_kv(base + (sl ? OFF_K1 : OFF_K0), kfull + sl * 8, j * 128, 64 + blk, solo);
                        if (astep == 1) PTRACE(14);
                        load_v(astep - 1);
                        if (astep == 1) PTRACE(15);
                    }
                }
                vrow = j * 128; vblk = 128 + blk; vsolo = solo;
                astep++;
                if ((nxt >> 12) != T_A) {
                    if (last) break;
                } else if (!q_issued && (last || i == 2 || (i > 2 && i >= qt - 2))) {
                    const int jh = nxt >> 4 & 31, jq = nxt & 15;
                    q_issued = wait_flags(lane <= jq || lane >= 30, lane == 31 ? F_GATE : (lane == 30 ? F_Q + jh * 16 + jq : F_KV + jh * 16 + (lane & 15)),
                                          epoch1 * (lane == 31 ? GATE_COUNT : 2), last);
                    if (q_issued) {
                        mbar_wait(qempty + (ajob & 1) * 8, ((ajob >> 1) & 1) ^ 1);
                        load_operand(base + ((ajob & 1) ? OFF_Q1 : OFF_Q0), qfull + (ajob & 1) * 8, &p.qkv_ld, &p.qkv_ld, jq * 128, jh * 2, 0, true, POL_STREAM);
                    }
                }
                i++;
                if (last) {
                    cur = nxt; jb++; nxt = uniform(jobs[jb]); i = 0; ajob++; q_issued = false;
                    if ((nxt >> 12) == T_O) { prefetch_map(&p.wo_a); prefetch_map(&p.wo_b); prefetch_map(&p.out_st); }
                }
            }
            if (nxt >= 0) draw_ticket(nxt);
            load_v(astep - 1);
            if (nxt >= 0) open_tile(nxt);
            }
            int nks = 0;
            if (nxt >= 0) {
                epoch1 = *epoch_word;
                const int m0 = (pl & 7) * 256 + rank * 128, nb = (pl >> 3 & 3) * 4 + rank * 2, part = pl >> 5 & 1;
                uint32_t ready_a = 0, ready_b = 0;
                uint32_t claim_even = 0, claim_odd = 0;
                const int head = o_head(pl), tail = o_tail(pl);
                int lim = head;
                bool known = false;
#pragma unroll 1
                for (int ks = 0;; ks++) {
                    const int st = ks & 3;
                    if (rank == 0) {
                        auto exchange = [&](uint32_t& claim) INL {
                            if (ks + 1 >= head) {
                                known = (uint32_t)uniform(claim) >= O_FLEX;
                                if (!known) lim = ks + 2;
                                announce(olim, known ? 2 * (lim + tail) + 1 : 2 * lim);
                            }
                            asm volatile("{\n.reg .pred p;\nsetp.ne.u32 p, %2, 0;\n@p atom.relaxed.gpu.global.inc.u32 %0, [%1], 0x7fffffff;\n}"
                                         : "+r"(claim) : "l"(g_flags + F_SPLIT + (pl & 31)), "r"((uint32_t)(!known && lane == 0)) : "memory");
                            __syncwarp();
                        };
                        if (!known && ks + 3 >= head) { if (ks & 1) exchange(claim_odd); else exchange(claim_even); }
                    } else if (!known && ks >= lim) {
                        const uint32_t v = uniform(o_state(olim, ks));
                        known = v & 1;
                        lim = (v >> 1) - (known ? tail : 0);
                    }
                    if (ks >= lim + tail) { nks = ks; break; }
                    if (ks == CLEAR_KS && !part) warp_arrive(gatefull);
                    int acol;
                    if (ks >= lim) acol = (part ? 64 - O_T1 : 200) + ks - lim;
                    else if (part) acol = ks < O_H1 ? O_F0 + ks : O_F0 + 2 * O_H1 + O_FLEX - 1 - ks;
                    else acol = ks < 8 ? 192 + ks : (ks < O_H0 ? ks - 8 : ks - 8 + O_H1);
                    for (uint32_t tries = 0; !(((acol < 192 ? ready_a : ready_b) >> (acol >> 1 & 31)) & 1); tries++) {
                        if (ks | tries) ask_ctx();
                        ready_a = __ballot_sync(0xffffffffu, (int32_t)(seen_a - epoch1 * 2) >= 0);
                        ready_b = __ballot_sync(0xffffffffu, (int32_t)(seen_b - epoch1 * 2) >= 0);
                        fence_acquire();
                        trap_if(tries > (1u << 22));
                    }
                    {
                        const uint32_t sa = base + st * G_STAGE;
                        if (ks < 4 && astep) mbar_wait((ks < 2 ? kempty : vempty) + ((astep - 1) & 1) * 8, ((astep - 1) >> 1) & 1);
                        else mbar_wait(gempty + st * 8, gph);
                        load_kstep(sa, sa + 16384 + rank * 16384, gfull + st * 8, G_STAGE, acol >= 192 ? &p.wo_b : &p.wo_a, acol & 63, nb,
                                   &p.qkv_half, m0, acol, 1);
                    }
                    if (st == 3) gph ^= 1;
                }
            }
            if (lane == 0) {
                if (nxt >= 0) for (int s = 0; s < 4; s++) mbar_wait(gempty + s * 8, gph ^ (s < (nks & 3)));
                else for (uint32_t t = astep; t < astep + 2; t++) {
                    mbar_wait(kempty + (t & 1) * 8, ((t >> 1) & 1) ^ 1);
                    mbar_wait(vempty + (t & 1) * 8, ((t >> 1) & 1) ^ 1);
                }
            }
        }
    }
}

typedef CUresult (*EncodeFn)(CUtensorMap*, CUtensorMapDataType, cuuint32_t, void*, const cuuint64_t*, const cuuint64_t*,
                             const cuuint32_t*, const cuuint32_t*, CUtensorMapInterleave, CUtensorMapSwizzle,
                             CUtensorMapL2promotion, CUtensorMapFloatOOBfill);

void make_map3(EncodeFn enc, CUtensorMap* m, const void* ptr, int rows, int cols, int box_rows, int box_blks, bool blocked = false) {
    cuuint64_t dims[3] = {64, (cuuint64_t)rows, (cuuint64_t)(cols / 64)};
    cuuint64_t strides[2] = {blocked ? 128 : (cuuint64_t)cols * 2, blocked ? (cuuint64_t)rows * 128 : 128};
    cuuint32_t box[3] = {64, (cuuint32_t)box_rows, (cuuint32_t)box_blks};
    cuuint32_t es[3] = {1, 1, 1};
    enc(m, CU_TENSOR_MAP_DATA_TYPE_BFLOAT16, 3, const_cast<void*>(ptr), dims, strides, box, es, CU_TENSOR_MAP_INTERLEAVE_NONE,
        CU_TENSOR_MAP_SWIZZLE_128B, CU_TENSOR_MAP_L2_PROMOTION_L2_256B, CU_TENSOR_MAP_FLOAT_OOB_FILL_NONE);
}

Params h_params;

const int16_t k_jobs[NUM_SMS][MAX_JOBS] = {
    {339,153,217,8890,8339,8802,8311,9042,8405,9008,8551,9134,8677,4128,-1,-1,-1,-1,-1,-1,-1,-1,-1,-1},
    {339,153,217,8891,8338,8803,8310,9043,8404,9009,8550,9135,8676,4128,-1,-1,-1,-1,-1,-1,-1,-1,-1,-1},
    {40,0,307,8888,8289,8720,8259,8854,8539,8898,8627,8998,8655,4128,-1,-1,-1,-1,-1,-1,-1,-1,-1,-1},
    {40,0,307,8889,8288,8721,8258,8855,8538,8899,8626,8999,8654,4128,-1,-1,-1,-1,-1,-1,-1,-1,-1,-1},
    {10,157,221,8706,8269,8820,8457,9006,8687,4128,-1,-1,-1,-1,-1,-1,-1,-1,-1,-1,-1,-1,-1,-1},
    {10,157,221,8707,8268,8821,8456,9007,8686,4128,-1,-1,-1,-1,-1,-1,-1,-1,-1,-1,-1,-1,-1,-1},
    {132,196,296,8730,8333,8940,8503,9082,8697,4128,-1,-1,-1,-1,-1,-1,-1,-1,-1,-1,-1,-1,-1,-1},
    {132,196,296,8731,8332,8941,8502,9083,8696,4128,-1,-1,-1,-1,-1,-1,-1,-1,-1,-1,-1,-1,-1,-1},
    {128,192,8758,8199,8774,8313,9026,8415,9130,8663,4128,-1,-1,-1,-1,-1,-1,-1,-1,-1,-1,-1,-1,-1},
    {128,192,8759,8198,8775,8312,9027,8414,9131,8662,4128,-1,-1,-1,-1,-1,-1,-1,-1,-1,-1,-1,-1,-1},
    {133,197,8742,8369,8704,8285,8768,8543,9022,8601,4128,-1,-1,-1,-1,-1,-1,-1,-1,-1,-1,-1,-1,-1},
    {133,197,8743,8368,8705,8284,8769,8542,9023,8600,4128,-1,-1,-1,-1,-1,-1,-1,-1,-1,-1,-1,-1,-1},
    {131,195,38,8708,8265,8932,8461,8896,8631,9076,8585,4128,-1,-1,-1,-1,-1,-1,-1,-1,-1,-1,-1,-1},
    {131,195,38,8709,8264,8933,8460,8897,8630,9077,8584,4128,-1,-1,-1,-1,-1,-1,-1,-1,-1,-1,-1,-1},
    {137,201,8750,8331,8816,8533,8912,8411,9078,8671,4128,-1,-1,-1,-1,-1,-1,-1,-1,-1,-1,-1,-1,-1},
    {137,201,8751,8330,8817,8532,8913,8410,9079,8670,4128,-1,-1,-1,-1,-1,-1,-1,-1,-1,-1,-1,-1,-1},
    {43,264,440,8744,8201,8858,8417,8954,8483,9016,8649,9152,8691,4128,-1,-1,-1,-1,-1,-1,-1,-1,-1,-1},
    {43,264,440,8745,8200,8859,8416,8955,8482,9017,8648,9153,8690,4128,-1,-1,-1,-1,-1,-1,-1,-1,-1,-1},
    {151,215,8876,8299,8964,8445,9146,8703,4128,-1,-1,-1,-1,-1,-1,-1,-1,-1,-1,-1,-1,-1,-1,-1},
    {151,215,8877,8298,8965,8444,9147,8702,4128,-1,-1,-1,-1,-1,-1,-1,-1,-1,-1,-1,-1,-1,-1,-1},
    {470,5,159,223,8772,8281,8936,8407,9066,8651,4128,-1,-1,-1,-1,-1,-1,-1,-1,-1,-1,-1,-1,-1},
    {470,5,159,223,8773,8280,8937,8406,9067,8650,4128,-1,-1,-1,-1,-1,-1,-1,-1,-1,-1,-1,-1,-1},
    {136,200,444,8760,8275,8848,8477,9040,8525,9148,8681,4128,-1,-1,-1,-1,-1,-1,-1,-1,-1,-1,-1,-1},
    {136,200,444,8761,8274,8849,8476,9041,8524,9149,8680,4128,-1,-1,-1,-1,-1,-1,-1,-1,-1,-1,-1,-1},
    {46,510,462,310,8764,8293,8862,8439,9064,8653,4128,-1,-1,-1,-1,-1,-1,-1,-1,-1,-1,-1,-1,-1},
    {46,510,462,310,8765,8292,8863,8438,9065,8652,4128,-1,-1,-1,-1,-1,-1,-1,-1,-1,-1,-1,-1,-1},
    {145,209,8894,8335,8942,8485,9098,8695,4128,-1,-1,-1,-1,-1,-1,-1,-1,-1,-1,-1,-1,-1,-1,-1},
    {145,209,8895,8334,8943,8484,9099,8694,4128,-1,-1,-1,-1,-1,-1,-1,-1,-1,-1,-1,-1,-1,-1,-1},
    {140,204,8878,8329,8934,8441,9070,8685,4128,-1,-1,-1,-1,-1,-1,-1,-1,-1,-1,-1,-1,-1,-1,-1},
    {140,204,8879,8328,8935,8440,9071,8684,4128,-1,-1,-1,-1,-1,-1,-1,-1,-1,-1,-1,-1,-1,-1,-1},
    {146,210,504,8884,8301,8966,8527,9128,8603,4128,-1,-1,-1,-1,-1,-1,-1,-1,-1,-1,-1,-1,-1,-1},
    {146,210,504,8885,8300,8967,8526,9129,8602,4128,-1,-1,-1,-1,-1,-1,-1,-1,-1,-1,-1,-1,-1,-1},
    {14,6,8868,8245,8806,8267,8938,8547,9000,8611,9108,8643,4128,-1,-1,-1,-1,-1,-1,-1,-1,-1,-1,-1},
    {14,6,8869,8244,8807,8266,8939,8546,9001,8610,9109,8642,4128,-1,-1,-1,-1,-1,-1,-1,-1,-1,-1,-1},
    {144,208,8748,8211,8836,8463,9004,8591,4128,-1,-1,-1,-1,-1,-1,-1,-1,-1,-1,-1,-1,-1,-1,-1},
    {144,208,8749,8210,8837,8462,9005,8590,4128,-1,-1,-1,-1,-1,-1,-1,-1,-1,-1,-1,-1,-1,-1,-1},
    {12,4,8740,8243,8724,8287,8930,8435,8900,8517,9086,8659,4128,-1,-1,-1,-1,-1,-1,-1,-1,-1,-1,-1},
    {12,4,8741,8242,8725,8286,8931,8434,8901,8516,9087,8658,4128,-1,-1,-1,-1,-1,-1,-1,-1,-1,-1,-1},
    {143,207,8866,8353,8752,8205,8830,8409,9056,8561,9140,8581,9104,8679,4128,-1,-1,-1,-1,-1,-1,-1,-1,-1},
    {143,207,8867,8352,8753,8204,8831,8408,9057,8560,9141,8580,9105,8678,4128,-1,-1,-1,-1,-1,-1,-1,-1,-1},
    {147,211,8872,8297,8834,8459,9030,8437,9100,8665,4128,-1,-1,-1,-1,-1,-1,-1,-1,-1,-1,-1,-1,-1},
    {147,211,8873,8296,8835,8458,9031,8436,9101,8664,4128,-1,-1,-1,-1,-1,-1,-1,-1,-1,-1,-1,-1,-1},
    {41,1,8766,8327,8828,8399,9126,8667,4128,-1,-1,-1,-1,-1,-1,-1,-1,-1,-1,-1,-1,-1,-1,-1},
    {41,1,8767,8326,8829,8398,9127,8666,4128,-1,-1,-1,-1,-1,-1,-1,-1,-1,-1,-1,-1,-1,-1,-1},
    {150,214,8882,8223,8832,8473,8980,8413,9094,8669,4128,-1,-1,-1,-1,-1,-1,-1,-1,-1,-1,-1,-1,-1},
    {150,214,8883,8222,8833,8472,8981,8412,9095,8668,4128,-1,-1,-1,-1,-1,-1,-1,-1,-1,-1,-1,-1,-1},
    {141,205,33,8726,8341,8976,8479,9024,8449,9136,8501,9144,8683,4128,-1,-1,-1,-1,-1,-1,-1,-1,-1,-1},
    {141,205,33,8727,8340,8977,8478,9025,8448,9137,8500,9145,8682,4128,-1,-1,-1,-1,-1,-1,-1,-1,-1,-1},
    {277,405,152,216,8718,8475,8902,8403,9150,8661,4128,-1,-1,-1,-1,-1,-1,-1,-1,-1,-1,-1,-1,-1},
    {277,405,152,216,8719,8474,8903,8402,9151,8660,4128,-1,-1,-1,-1,-1,-1,-1,-1,-1,-1,-1,-1,-1},
    {139,203,8886,8203,8856,8433,9032,8393,9080,8599,4128,-1,-1,-1,-1,-1,-1,-1,-1,-1,-1,-1,-1,-1},
    {139,203,8887,8202,8857,8432,9033,8392,9081,8598,4128,-1,-1,-1,-1,-1,-1,-1,-1,-1,-1,-1,-1,-1},
    {149,213,8746,8303,8982,8397,9084,8645,4128,-1,-1,-1,-1,-1,-1,-1,-1,-1,-1,-1,-1,-1,-1,-1},
    {149,213,8747,8302,8983,8396,9085,8644,4128,-1,-1,-1,-1,-1,-1,-1,-1,-1,-1,-1,-1,-1,-1,-1},
    {138,202,8870,8221,8860,8395,9060,8607,4128,-1,-1,-1,-1,-1,-1,-1,-1,-1,-1,-1,-1,-1,-1,-1},
    {138,202,8871,8220,8861,8394,9061,8606,4128,-1,-1,-1,-1,-1,-1,-1,-1,-1,-1,-1,-1,-1,-1,-1},
    {134,198,8738,8225,8728,8283,8962,8541,8992,8499,9074,8609,9124,8595,9184,8693,4128,-1,-1,-1,-1,-1,-1,-1},
    {134,198,8739,8224,8729,8282,8963,8540,8993,8498,9075,8608,9125,8594,9185,8692,4128,-1,-1,-1,-1,-1,-1,-1},
    {142,206,8874,8271,8818,8447,9068,8647,4128,-1,-1,-1,-1,-1,-1,-1,-1,-1,-1,-1,-1,-1,-1,-1},
    {142,206,8875,8270,8819,8446,9069,8646,4128,-1,-1,-1,-1,-1,-1,-1,-1,-1,-1,-1,-1,-1,-1,-1},
    {47,498,506,306,8892,8277,8784,8467,9048,8535,9020,8579,9088,8657,9186,8689,4128,-1,-1,-1,-1,-1,-1,-1},
    {47,498,506,306,8893,8276,8785,8466,9049,8534,9021,8578,9089,8656,9187,8688,4128,-1,-1,-1,-1,-1,-1,-1},
    {148,212,8762,8279,8826,8523,9002,8605,4128,-1,-1,-1,-1,-1,-1,-1,-1,-1,-1,-1,-1,-1,-1,-1},
    {148,212,8763,8278,8827,8522,9003,8604,4128,-1,-1,-1,-1,-1,-1,-1,-1,-1,-1,-1,-1,-1,-1,-1},
    {276,404,268,500,450,490,374,390,430,380,356,412,168,232,9018,8701,-1,-1,-1,-1,-1,-1,-1,-1},
    {276,404,268,500,450,490,374,390,430,380,356,412,168,232,9019,8700,-1,-1,-1,-1,-1,-1,-1,-1},
    {11,403,459,507,329,393,369,377,417,361,433,167,231,9132,8699,-1,-1,-1,-1,-1,-1,-1,-1,-1},
    {11,403,459,507,329,393,369,377,417,361,433,167,231,9133,8698,-1,-1,-1,-1,-1,-1,-1,-1,-1},
    {350,486,502,262,302,334,318,87,52,100,179,243,4096,-1,-1,-1,-1,-1,-1,-1,-1,-1,-1,-1},
    {350,486,502,262,302,334,318,87,52,100,179,243,4096,-1,-1,-1,-1,-1,-1,-1,-1,-1,-1,-1},
    {340,158,222,492,60,108,76,172,236,4096,-1,-1,-1,-1,-1,-1,-1,-1,-1,-1,-1,-1,-1,-1},
    {340,158,222,492,60,108,76,172,236,4096,-1,-1,-1,-1,-1,-1,-1,-1,-1,-1,-1,-1,-1,-1},
    {42,3,35,59,107,360,408,181,245,4096,-1,-1,-1,-1,-1,-1,-1,-1,-1,-1,-1,-1,-1,-1},
    {42,3,35,59,107,360,408,181,245,4096,-1,-1,-1,-1,-1,-1,-1,-1,-1,-1,-1,-1,-1,-1},
    {45,156,220,396,85,109,93,180,244,4096,-1,-1,-1,-1,-1,-1,-1,-1,-1,-1,-1,-1,-1,-1},
    {45,156,220,396,85,109,93,180,244,4096,-1,-1,-1,-1,-1,-1,-1,-1,-1,-1,-1,-1,-1,-1},
    {466,482,266,258,37,69,53,77,183,247,4096,-1,-1,-1,-1,-1,-1,-1,-1,-1,-1,-1,-1,-1},
    {466,482,266,258,37,69,53,77,183,247,4096,-1,-1,-1,-1,-1,-1,-1,-1,-1,-1,-1,-1,-1},
    {471,407,463,442,290,322,314,386,478,382,366,414,182,246,4096,-1,-1,-1,-1,-1,-1,-1,-1,-1},
    {471,407,463,442,290,322,314,386,478,382,366,414,182,246,4096,-1,-1,-1,-1,-1,-1,-1,-1,-1},
    {469,349,485,501,445,333,317,373,477,423,439,415,173,237,4096,-1,-1,-1,-1,-1,-1,-1,-1,-1},
    {469,349,485,501,445,333,317,373,477,423,439,415,173,237,4096,-1,-1,-1,-1,-1,-1,-1,-1,-1},
    {8,269,309,453,449,489,385,425,422,358,92,188,252,4096,-1,-1,-1,-1,-1,-1,-1,-1,-1,-1},
    {8,269,309,453,449,489,385,425,422,358,92,188,252,4096,-1,-1,-1,-1,-1,-1,-1,-1,-1,-1},
    {343,287,487,263,303,455,495,391,51,91,160,224,4096,-1,-1,-1,-1,-1,-1,-1,-1,-1,-1,-1},
    {343,287,487,263,303,455,495,391,51,91,160,224,4096,-1,-1,-1,-1,-1,-1,-1,-1,-1,-1,-1},
    {464,272,480,456,288,488,392,61,379,363,435,176,240,4096,-1,-1,-1,-1,-1,-1,-1,-1,-1,-1},
    {464,272,480,456,288,488,392,61,379,363,435,176,240,4096,-1,-1,-1,-1,-1,-1,-1,-1,-1,-1},
    {336,280,400,256,448,320,312,384,424,416,352,432,472,171,235,4096,-1,-1,-1,-1,-1,-1,-1,-1},
    {336,280,400,256,448,320,312,384,424,416,352,432,472,171,235,4096,-1,-1,-1,-1,-1,-1,-1,-1},
    {337,273,265,155,219,368,376,479,359,102,184,248,4096,-1,-1,-1,-1,-1,-1,-1,-1,-1,-1,-1},
    {337,273,265,155,219,368,376,479,359,102,184,248,4096,-1,-1,-1,-1,-1,-1,-1,-1,-1,-1,-1},
    {468,284,508,260,300,324,332,388,104,72,174,238,4096,-1,-1,-1,-1,-1,-1,-1,-1,-1,-1,-1},
    {468,284,508,260,300,324,332,388,104,72,174,238,4096,-1,-1,-1,-1,-1,-1,-1,-1,-1,-1,-1},
    {338,281,2,34,66,110,78,175,239,4096,-1,-1,-1,-1,-1,-1,-1,-1,-1,-1,-1,-1,-1,-1},
    {338,281,2,34,66,110,78,175,239,4096,-1,-1,-1,-1,-1,-1,-1,-1,-1,-1,-1,-1,-1,-1},
    {130,194,39,63,55,95,103,97,4096,-1,-1,-1,-1,-1,-1,-1,-1,-1,-1,-1,-1,-1,-1,-1},
    {130,194,39,63,55,95,103,97,4096,-1,-1,-1,-1,-1,-1,-1,-1,-1,-1,-1,-1,-1,-1,-1},
    {135,199,454,494,67,83,365,413,191,255,4096,-1,-1,-1,-1,-1,-1,-1,-1,-1,-1,-1,-1,-1},
    {135,199,454,494,67,83,365,413,191,255,4096,-1,-1,-1,-1,-1,-1,-1,-1,-1,-1,-1,-1,-1},
    {348,484,460,308,292,452,316,372,428,420,476,101,187,251,4096,-1,-1,-1,-1,-1,-1,-1,-1,-1},
    {348,484,460,308,292,452,316,372,428,420,476,101,187,251,4096,-1,-1,-1,-1,-1,-1,-1,-1,-1},
    {13,154,218,58,106,74,178,242,4096,-1,-1,-1,-1,-1,-1,-1,-1,-1,-1,-1,-1,-1,-1,-1},
    {13,154,218,58,106,74,178,242,4096,-1,-1,-1,-1,-1,-1,-1,-1,-1,-1,-1,-1,-1,-1,-1},
    {465,481,457,505,289,328,71,111,79,166,230,4096,-1,-1,-1,-1,-1,-1,-1,-1,-1,-1,-1,-1},
    {465,481,457,505,289,328,71,111,79,166,230,4096,-1,-1,-1,-1,-1,-1,-1,-1,-1,-1,-1,-1},
    {44,270,446,294,326,65,81,89,161,225,4096,-1,-1,-1,-1,-1,-1,-1,-1,-1,-1,-1,-1,-1},
    {44,270,446,294,326,65,81,89,161,225,4096,-1,-1,-1,-1,-1,-1,-1,-1,-1,-1,-1,-1,-1},
    {9,511,503,295,327,375,399,381,437,353,409,473,169,233,4096,-1,-1,-1,-1,-1,-1,-1,-1,-1},
    {9,511,503,295,327,375,399,381,437,353,409,473,169,233,4096,-1,-1,-1,-1,-1,-1,-1,-1,-1},
    {347,283,483,259,291,491,331,371,431,383,367,99,186,250,4096,-1,-1,-1,-1,-1,-1,-1,-1,-1},
    {347,283,483,259,291,491,331,371,431,383,367,99,186,250,4096,-1,-1,-1,-1,-1,-1,-1,-1,-1},
    {274,282,458,261,293,493,397,389,429,421,357,75,189,253,4096,-1,-1,-1,-1,-1,-1,-1,-1,-1},
    {274,282,458,261,293,493,397,389,429,421,357,75,189,253,4096,-1,-1,-1,-1,-1,-1,-1,-1,-1},
    {278,286,406,32,64,56,48,88,170,234,4096,-1,-1,-1,-1,-1,-1,-1,-1,-1,-1,-1,-1,-1},
    {278,286,406,32,64,56,48,88,170,234,4096,-1,-1,-1,-1,-1,-1,-1,-1,-1,-1,-1,-1,-1},
    {279,351,271,447,298,330,394,370,426,378,354,434,164,228,4096,-1,-1,-1,-1,-1,-1,-1,-1,-1},
    {279,351,271,447,298,330,394,370,426,378,354,434,164,228,4096,-1,-1,-1,-1,-1,-1,-1,-1,-1},
    {344,345,497,257,297,321,313,82,50,90,98,96,4096,-1,-1,-1,-1,-1,-1,-1,-1,-1,-1,-1},
    {344,345,497,257,297,321,313,82,50,90,98,96,4096,-1,-1,-1,-1,-1,-1,-1,-1,-1,-1,-1},
    {129,193,311,335,319,86,438,364,436,163,227,4096,-1,-1,-1,-1,-1,-1,-1,-1,-1,-1,-1,-1},
    {129,193,311,335,319,86,438,364,436,163,227,4096,-1,-1,-1,-1,-1,-1,-1,-1,-1,-1,-1,-1},
    {341,285,509,461,301,325,398,80,418,362,410,474,177,241,4096,-1,-1,-1,-1,-1,-1,-1,-1,-1},
    {341,285,509,461,301,325,398,80,418,362,410,474,177,241,4096,-1,-1,-1,-1,-1,-1,-1,-1,-1},
    {342,275,267,499,299,451,395,57,49,73,185,249,4096,-1,-1,-1,-1,-1,-1,-1,-1,-1,-1,-1},
    {342,275,267,499,299,451,395,57,49,73,185,249,4096,-1,-1,-1,-1,-1,-1,-1,-1,-1,-1,-1},
    {346,402,496,304,443,323,315,387,427,419,355,411,165,229,4096,-1,-1,-1,-1,-1,-1,-1,-1,-1},
    {346,402,496,304,443,323,315,387,427,419,355,411,165,229,4096,-1,-1,-1,-1,-1,-1,-1,-1,-1},
    {15,401,305,441,70,62,54,94,190,254,4096,-1,-1,-1,-1,-1,-1,-1,-1,-1,-1,-1,-1,-1},
    {15,401,305,441,70,62,54,94,190,254,4096,-1,-1,-1,-1,-1,-1,-1,-1,-1,-1,-1,-1,-1},
    {467,7,36,68,84,105,475,162,226,4096,-1,-1,-1,-1,-1,-1,-1,-1,-1,-1,-1,-1,-1,-1},
    {467,7,36,68,84,105,475,162,226,4096,-1,-1,-1,-1,-1,-1,-1,-1,-1,-1,-1,-1,-1,-1},
};

void build_rounds() {
    for (int c = 0; c < NUM_SMS / 2; c++) {
        const int16_t* jobs = h_params.jobs[2 * c];
        int nr = 0, prev_key = -1, last = 0;
        for (int j = 0; (jobs[j] >> 12) == T_P; j++) {
            const int n = jobs[j] >> 3, a = n >= 32, unit = n >= 16 && n < 32 ? (n >> 3) - 1 : 0, cnt = a ? 2 : 4;
            const int key = (jobs[j] & 7) | a << 3 | (unit > 0) << 4;
            const int wm = n < 16 ? 0 : (n < 32 ? 1 : n >> 4 & 1), col = n < 16 ? n : (n < 32 ? n & 7 : n & 15);
            const bool keep = key == prev_key, final_tile = (jobs[j + 1] >> 12) != T_P;
            const int k0 = keep ? last : 0;
            for (int r = 0; r < cnt; r++) {
                last = (k0 + r) % cnt;
                h_params.rounds[c][nr++] = (uint16_t)((key & 15) | wm << 4 | col << 6 | last << 10 | (keep && r == 0) << 12 | (final_tile && r == 0) << 13 | unit << 14);
            }
            prev_key = key;
        }
        while (nr < MAX_ROUNDS) h_params.rounds[c][nr++] = 0xFFFF;
        {
            const uint32_t rec = h_params.rounds[c][0], col = rec >> 6 & 15, unit = rec >> 14;
            for (uint32_t r = 0; r < 2; r++) {
                uint32_t wm[2], wb[2];
                for (uint32_t h = 0; h < 2; h++) {
                    wm[h] = 2 + ((rec & 8) ? 2 + h : ((rec >> 15) && h ? 0 : rec >> 4 & 1));
                    wb[h] = (rec & 8) ? (col + (rec & 16)) * 2
                                      : (unit == 0 ? col * 4 + h * 2 : (unit == 1 ? 16 + h * 16 + col * 2 : (h ? unit_head(col) : col) * 2));
                }
                const uint32_t am = unit ? 6 : (rec >> 3 & 1), arow = unit ? (rec & 7) * 128 + r * 64 : (rec & 7) * 256 + r * 128;
                h_params.first[2 * c + r] = make_uint2((unit ? 1 : 0) | am << 7 | wm[0] << 11 | wm[1] << 15 | arow << 20, wb[0] | wb[1] << 16);
            }
        }
    }
}

void build_schedule() {
    for (int c = 0; c < NUM_SMS; c++) {
        for (int j = 0; j < MAX_JOBS; j++) h_params.jobs[c][j] = k_jobs[c][j];
    }
    build_rounds();
}

}

extern "C" void kernel_launch(void* const* d_in, const int* in_sizes, int n_in, void* d_out, int out_size) {
    (void)in_sizes; (void)n_in; (void)out_size;
    static EncodeFn enc = nullptr;
    if (!enc) {
        cudaDriverEntryPointQueryResult qr;
        void* fn = nullptr;
        cudaGetDriverEntryPoint("cuTensorMapEncodeTiled", &fn, cudaEnableDefault, &qr);
        enc = (EncodeFn)fn;
        cudaFuncSetAttribute(fused_kernel, cudaFuncAttributeMaxDynamicSharedMemorySize, SMEM_BYTES);
        build_schedule();
    }
    void* qkv;
    cudaGetSymbolAddress(&qkv, g_qkv);
    Params& p = h_params;
    make_map3(enc, &p.amap[0], d_in[0], SEQ, DM, 128, 1);
    make_map3(enc, &p.amap[1], d_in[1], SEQ, DC, 128, 1);
    make_map3(enc, &p.wmap[0], d_in[2], DM, 4096, 64, 2);
    make_map3(enc, &p.wmap[2], d_in[3], DC, 4096, 64, 2);
    make_map3(enc, &p.wmap[3], d_in[4], DC, 4096, 64, 2);
    make_map3(enc, &p.wmap[1], d_in[7], DM, 3072, 64, 2);
    make_map3(enc, &p.wo_a, d_in[5], 4096, DM, 64, 2);
    make_map3(enc, &p.wo_b, d_in[8], DM, DM, 64, 2);
    make_map3(enc, &p.qkv_st, qkv, SEQ, QKV_W, 64, 1, true);
    make_map3(enc, &p.qkv_ld, qkv, SEQ, QKV_W, 128, 2, true);
    make_map3(enc, &p.qkv_half, qkv, SEQ, QKV_W, 128, 1, true);
    {
        cuuint64_t dims[4] = {64, SEQ / 2, 2, QKV_W / 64}, strides[3] = {256, 128, (cuuint64_t)SEQ * 128};
        cuuint32_t box[4] = {64, 64, 1, 1}, es[4] = {1, 1, 1, 1};
        enc(&p.st_par, CU_TENSOR_MAP_DATA_TYPE_BFLOAT16, 4, qkv, dims, strides, box, es, CU_TENSOR_MAP_INTERLEAVE_NONE,
            CU_TENSOR_MAP_SWIZZLE_128B, CU_TENSOR_MAP_L2_PROMOTION_L2_256B, CU_TENSOR_MAP_FLOAT_OOB_FILL_NONE);
        dims[3] = DM / 64; strides[0] = DM * 4; strides[1] = DM * 2; strides[2] = 128; box[2] = 2;
        enc(&p.x_par, CU_TENSOR_MAP_DATA_TYPE_BFLOAT16, 4, d_in[0], dims, strides, box, es, CU_TENSOR_MAP_INTERLEAVE_NONE,
            CU_TENSOR_MAP_SWIZZLE_128B, CU_TENSOR_MAP_L2_PROMOTION_L2_256B, CU_TENSOR_MAP_FLOAT_OOB_FILL_NONE);
    }
    make_map3(enc, &p.out_st, d_out, SEQ, DM, 64, 1);
    p.xp = (const __nv_bfloat16*)d_in[0];
    p.gate_w = (const __nv_bfloat16*)d_in[9];
    p.out = (__nv_bfloat16*)d_out;
    fused_kernel<<<NUM_SMS, 384, SMEM_BYTES, cudaStreamPerThread>>>(p);
}
```

```cpp
#include <cuda_runtime.h>
#include <cuda_bf16.h>
#include <cuda.h>
#include <stdint.h>

#define INL __attribute__((always_inline))

namespace {

constexpr int SEQ = 2048;
constexpr int DM = 1024;
constexpr int DC = 512;
constexpr int QKV_W = 13312;
constexpr int NUM_SMS = 132;
constexpr int GATE_DELAY_SHORT_NS = 1000, GATE_DELAY_LONG_NS = 3000;
constexpr int CLEAR_KS = 44, CLEAR_GAP_NS = 100;
constexpr float Q_SCALE = 0.08838834764831845f * 1.4426950408889634f;

__device__ __align__(1024) __nv_bfloat16 g_qkv[(size_t)SEQ * QKV_W];
__device__ float g_gate[SEQ];
__device__ uint4 g_halo[16 * 8 * 2 * 5 * 4 * 32];

constexpr int F_Q = 0;
constexpr int F_KV = 1792;
constexpr int F_H = 768;
constexpr int F_CTX = 960;
constexpr int F_GATE = 1600;
constexpr int F_DONE = 1632;
constexpr int F_SPLIT = 1664;
constexpr int F_TICKET = 1696;
constexpr int F_OUT = 1728;
constexpr int GATE_COUNT = NUM_SMS;
__device__ uint32_t g_flags[2304];

#define END_MARK(slot)
#define TRACE_MARK(k, w, i)
#define GTRACE(w)
#define KTRACE(w)
#define PTRACE(i)
#define TRACE_GATE 32
#define TRACE_TID 128

__device__ __forceinline__ uint32_t smem_u32(const void* p) { return (uint32_t)__cvta_generic_to_shared(p); }
__device__ __forceinline__ void mbar_init(uint32_t bar, uint32_t cnt) {
    asm volatile("mbarrier.init.shared::cta.b64 [%0], %1;" ::"r"(bar), "r"(cnt));
}
__device__ __forceinline__ void mbar_arrive(uint32_t bar) {
    asm volatile("mbarrier.arrive.shared::cta.b64 _, [%0];" ::"r"(bar) : "memory");
}
__device__ __forceinline__ bool elect_one() {
    uint32_t r;
    asm volatile("{\n.reg .pred p;\nelect.sync _|p, 0xffffffff;\nselp.b32 %0, 1, 0, p;\n}" : "=r"(r));
    return r != 0;
}
__device__ __forceinline__ uint32_t mapa(uint32_t addr, uint32_t cta) {
    uint32_t r;
    asm("mapa.shared::cluster.u32 %0, %1, %2;" : "=r"(r) : "r"(addr), "r"(cta));
    return r;
}
__device__ __forceinline__ void warp_arrive(uint32_t bar, bool pred = true) {
    asm volatile("{\n.reg .pred p, q;\nsetp.ne.u32 q, %1, 0;\nelect.sync _|p, 0xffffffff;\nand.pred p, p, q;\n"
                 "@p mbarrier.arrive.shared::cta.b64 _, [%0];\n}" ::"r"(bar), "r"((uint32_t)pred) : "memory");
}
__device__ __forceinline__ void warp_arrive2(uint32_t bar0, uint32_t bar1) {
    asm volatile("{\n.reg .pred p;\nelect.sync _|p, 0xffffffff;\n@p mbarrier.arrive.shared::cta.b64 _, [%0];\n"
                 "@p mbarrier.arrive.shared::cta.b64 _, [%1];\n}" ::"r"(bar0), "r"(bar1) : "memory");
}
__device__ __forceinline__ void warp_arrive_pair(uint32_t bar, uint32_t peer_bar, bool pred = true) {
    asm volatile("{\n.reg .pred p, q;\nsetp.ne.u32 q, %2, 0;\nelect.sync _|p, 0xffffffff;\nand.pred p, p, q;\n"
                 "@p mbarrier.arrive.shared::cluster.b64 _, [%1];\n@p mbarrier.arrive.shared::cta.b64 _, [%0];\n}"
                 ::"r"(bar), "r"(peer_bar), "r"((uint32_t)pred) : "memory");
}
__device__ __forceinline__ void mbar_expect_tx(uint32_t bar, uint32_t bytes) {
    asm volatile("mbarrier.arrive.expect_tx.shared::cta.b64 _, [%0], %1;" ::"r"(bar), "r"(bytes) : "memory");
}
constexpr int WAIT_HINT_NS = 20000, WAIT_TRIES = 200000;
__device__ __forceinline__ void mbar_wait(uint32_t bar, uint32_t parity) {
    asm volatile("{\n.reg .pred p;\n.reg .u32 c;\n"
                 "mbarrier.try_wait.parity.shared::cta.b64 p, [%0], %1;\n@p bra DONE;\nmov.u32 c, 0;\n"
                 "SPIN:\nmbarrier.try_wait.parity.shared::cta.b64 p, [%0], %1, %2;\n@p bra DONE;\n"
                 "add.u32 c, c, 1;\nsetp.lt.u32 p, c, %3;\n@p bra SPIN;\ntrap;\nDONE:\n}"
                 ::"r"(bar), "r"(parity), "n"(WAIT_HINT_NS), "n"(WAIT_TRIES) : "memory");
}
__device__ __forceinline__ void mbar_wait_hot(uint32_t bar, uint32_t parity) {
    asm volatile("{\n.reg .pred p, q;\n.reg .u32 c;\n.reg .u64 z;\nmov.u32 c, 0;\nmov.u64 z, 0;\n"
                 "SPIN:\nmbarrier.try_wait.parity.shared::cta.b64 p, [%0], %1;\n"
                 "add.u32 c, c, 1;\nsetp.lt.and.u32 q, c, 4194304, !p;\n@q bra SPIN;\n@!p st.global.u32 [z], c;\n}"
                 ::"r"(bar), "r"(parity) : "memory");
}
constexpr uint64_t POL_STREAM = 0x12F0000000000000ull;
constexpr uint64_t POL_NORMAL = 0x1000000000000000ull;
__device__ __forceinline__ void tma_load_3d(uint32_t dst, const CUtensorMap* map, uint32_t bar, int c0, int c1, int c2, uint64_t pol = POL_NORMAL) {
    asm volatile("cp.async.bulk.tensor.3d.shared::cluster.global.mbarrier::complete_tx::bytes.L2::cache_hint [%0], [%1, {%3, %4, %5}], [%2], %6;"
                 ::"r"(dst), "l"(map), "r"(bar), "r"(c0), "r"(c1), "r"(c2), "l"(pol) : "memory");
}
__device__ __forceinline__ void load_kstep(uint32_t sa, uint32_t sw, uint32_t bar, uint32_t bytes, const CUtensorMap* wmap, int wk, int wblk,
                                           const CUtensorMap* amap, int arow, int kc, uint32_t amode) {
    asm volatile("{\n.reg .pred p, q, r;\n.reg .b32 k;\nelect.sync _|p, 0xffffffff;\nsetp.eq.and.u32 q, %9, 1, p;\nsetp.eq.and.u32 r, %9, 2, p;\nshl.b32 k, %12, 6;\n"
                 "@p mbarrier.arrive.expect_tx.shared::cta.b64 _, [%2], %3;\n"
                 "@p cp.async.bulk.tensor.3d.shared::cluster.global.mbarrier::complete_tx::bytes.multicast::cluster.L2::cache_hint [%1], [%4, {0, k, %5}], [%2], %10, %11;\n"
                 "@q cp.async.bulk.tensor.3d.shared::cluster.global.mbarrier::complete_tx::bytes.L2::cache_hint [%0], [%6, {0, %7, %8}], [%2], %11;\n"
                 "@r cp.async.bulk.tensor.4d.shared::cluster.global.mbarrier::complete_tx::bytes.L2::cache_hint [%0], [%6, {0, %7, 0, %8}], [%2], %11;\n}"
                 ::"r"(sa), "r"(sw), "r"(bar), "r"(bytes), "l"(wmap), "r"(wblk), "l"(amap), "r"(arow), "r"(kc), "r"(amode), "h"((uint16_t)3), "l"(POL_NORMAL), "r"(wk) : "memory");
}
__device__ __forceinline__ void load_operand(uint32_t dst, uint32_t bar, const CUtensorMap* full, const CUtensorMap* half, int row, int blk,
                                             uint32_t rank, bool solo, uint64_t pol) {
    asm volatile("{\n.reg .pred p, q, r;\n.reg .b32 d, b;\nelect.sync _|p, 0xffffffff;\nsetp.ne.and.u32 q, %7, 0, p;\nsetp.eq.and.u32 r, %7, 0, p;\n"
                 "mad.lo.u32 d, %6, 16384, %0;\nadd.u32 b, %5, %6;\n"
                 "@p mbarrier.arrive.expect_tx.shared::cta.b64 _, [%1], 32768;\n"
                 "@q cp.async.bulk.tensor.3d.shared::cluster.global.mbarrier::complete_tx::bytes.L2::cache_hint [%0], [%2, {0, %4, %5}], [%1], %9;\n"
                 "@r cp.async.bulk.tensor.3d.shared::cluster.global.mbarrier::complete_tx::bytes.multicast::cluster.L2::cache_hint [d], [%3, {0, %4, b}], [%1], %8, %9;\n}"
                 ::"r"(dst), "r"(bar), "l"(full), "l"(half), "r"(row), "r"(blk), "r"(rank), "r"((uint32_t)solo), "h"((uint16_t)3), "l"(pol) : "memory");
}
__device__ __forceinline__ void tma_store_par(const CUtensorMap* map, uint32_t src, int pair, int parity, int blk) {
    asm volatile("cp.async.bulk.tensor.4d.global.shared::cta.bulk_group.L2::cache_hint [%0, {0, %2, %3, %4}], [%1], %5;"
                 ::"l"(map), "r"(src), "r"(pair), "r"(parity), "r"(blk), "l"(POL_STREAM) : "memory");
}
__device__ __forceinline__ void tma_store_3d(const CUtensorMap* map, uint32_t src, int c0, int c1, int c2, uint64_t pol) {
    asm volatile("cp.async.bulk.tensor.3d.global.shared::cta.bulk_group.L2::cache_hint [%0, {%2, %3, %4}], [%1], %5;"
                 ::"l"(map), "r"(src), "r"(c0), "r"(c1), "r"(c2), "l"(pol) : "memory");
}
__device__ __forceinline__ void tma_reduce_add_3d(const CUtensorMap* map, uint32_t src, int c0, int c1, int c2) {
    asm volatile("cp.reduce.async.bulk.tensor.3d.global.shared::cta.add.tile.bulk_group [%0, {%2, %3, %4}], [%1];"
                 ::"l"(map), "r"(src), "r"(c0), "r"(c1), "r"(c2) : "memory");
}
__device__ __forceinline__ void bulk_commit() { asm volatile("cp.async.bulk.commit_group;" ::: "memory"); }
template <int N> __device__ __forceinline__ void bulk_wait_read() { asm volatile("cp.async.bulk.wait_group.read %0;" ::"n"(N) : "memory"); }
template <int N> __device__ __forceinline__ void bulk_wait() { asm volatile("cp.async.bulk.wait_group %0;" ::"n"(N) : "memory"); }
__device__ __forceinline__ void fence_async_smem() { asm volatile("fence.proxy.async.shared::cta;" ::: "memory"); }
__device__ __forceinline__ void fence_async_global() { asm volatile("fence.proxy.async.global;" ::: "memory"); }
__device__ __forceinline__ uint32_t ld_acquire(const uint32_t* p) {
    uint32_t v;
    asm volatile("ld.acquire.gpu.global.u32 %0, [%1];" : "=r"(v) : "l"(p) : "memory");
    return v;
}
__device__ __forceinline__ uint32_t ld_relaxed(const uint32_t* p) {
    uint32_t v;
    asm volatile("ld.relaxed.gpu.global.u32 %0, [%1];" : "=r"(v) : "l"(p) : "memory");
    return v;
}
__device__ __forceinline__ void fence_acquire() { asm volatile("fence.acquire.gpu;\nfence.proxy.async.global;" ::: "memory"); }
__device__ __forceinline__ void red_release(uint32_t* p) {
    asm volatile("red.release.gpu.global.add.u32 [%0], 1;" ::"l"(p) : "memory");
}
__device__ __forceinline__ void red_relaxed(uint32_t* p) {
    asm volatile("red.relaxed.gpu.global.add.u32 [%0], 1;" ::"l"(p) : "memory");
}
__device__ __forceinline__ void prefetch_map(const CUtensorMap* map) { asm volatile("prefetch.tensormap [%0];" ::"l"(map) : "memory"); }
__device__ __forceinline__ void trap_if(bool c) { asm volatile("{\n.reg .pred p;\nsetp.ne.u32 p, %0, 0;\n@p trap;\n}" ::"r"((uint32_t)c)); }
__device__ __forceinline__ void setup_arrive() { asm volatile("barrier.cluster.arrive.relaxed.aligned;" ::: "memory"); }
__device__ __forceinline__ void setup_wait() { asm volatile("barrier.cluster.wait.aligned;" ::: "memory"); }
__device__ __forceinline__ uint32_t cluster_rank() { uint32_t r; asm("mov.u32 %0, %%cluster_ctarank;" : "=r"(r)); return r; }
__device__ __forceinline__ void named_sync(int id, int n) { asm volatile("bar.sync %0, %1;" ::"r"(id), "r"(n) : "memory"); }
__device__ __forceinline__ void named_arrive(int id, int n) { asm volatile("bar.arrive %0, %1;" ::"r"(id), "r"(n) : "memory"); }
__device__ __forceinline__ void named_sync_if(bool c, int id, int n) {
    asm volatile("{\n.reg .pred p;\nsetp.ne.u32 p, %0, 0;\n@p bar.sync %1, %2;\n}" ::"r"((uint32_t)c), "r"(id), "r"(n) : "memory");
}
__device__ __forceinline__ void named_arrive_if(bool c, int id, int n) {
    asm volatile("{\n.reg .pred p;\nsetp.ne.u32 p, %0, 0;\n@p bar.arrive %1, %2;\n}" ::"r"((uint32_t)c), "r"(id), "r"(n) : "memory");
}
template <int V> struct IC { static constexpr int v = V; };
template <int N> __device__ __forceinline__ void reg_dec() { asm volatile("setmaxnreg.dec.sync.aligned.u32 %0;" ::"n"(N)); }
template <int N> __device__ __forceinline__ void reg_inc() { asm volatile("setmaxnreg.inc.sync.aligned.u32 %0;" ::"n"(N)); }

__device__ __forceinline__ void wg_fence() { asm volatile("wgmma.fence.sync.aligned;" ::: "memory"); }
__device__ __forceinline__ void wg_commit() { asm volatile("wgmma.commit_group.sync.aligned;" ::: "memory"); }
template <int N> __device__ __forceinline__ void wg_wait() { asm volatile("wgmma.wait_group.sync.aligned %0;" ::"n"(N) : "memory"); }
template <int N> __device__ __forceinline__ void fence_regs(float (&r)[N]) {
#pragma unroll
    for (int i = 0; i < N; i++) asm volatile("" : "+f"(r[i])::"memory");
}
template <int N> __device__ __forceinline__ void fence_regs(uint32_t (&r)[N]) {
#pragma unroll
    for (int i = 0; i < N; i++) asm volatile("" : "+r"(r[i])::"memory");
}
__device__ __forceinline__ uint32_t desc_lo(uint32_t addr, uint32_t lbo) { return ((addr & 0x3FFFF) >> 4) | ((lbo >> 4) << 16); }
__device__ __forceinline__ int uniform(int v) { return __shfl_sync(0xffffffffu, v, 0); }
__device__ __forceinline__ uint32_t pack_bf16(float lo, float hi) {
    uint32_t r;
    asm("cvt.rn.bf16x2.f32 %0, %1, %2;" : "=r"(r) : "f"(hi), "f"(lo));
    return r;
}
__device__ __forceinline__ uint32_t mul_bf16x2(uint32_t x, uint32_t y) {
    uint32_t r;
    asm("mul.rn.bf16x2 %0, %1, %2;" : "=r"(r) : "r"(x), "r"(y));
    return r;
}
__device__ __forceinline__ void stmatrix_x4(uint32_t addr, uint32_t r0, uint32_t r1, uint32_t r2, uint32_t r3) {
    asm volatile("stmatrix.sync.aligned.m8n8.x4.shared.b16 [%0], {%1, %2, %3, %4};"
                 ::"r"(addr), "r"(r0), "r"(r1), "r"(r2), "r"(r3) : "memory");
}
__device__ __forceinline__ void stmatrix_x4(uint32_t addr, uint32_t r0, uint32_t r1, uint32_t r2, uint32_t r3, bool trans) {
    asm volatile("{\n.reg .pred p;\nsetp.ne.u32 p, %5, 0;\n@p stmatrix.sync.aligned.m8n8.x4.trans.shared.b16 [%0], {%1, %2, %3, %4};\n"
                 "@!p stmatrix.sync.aligned.m8n8.x4.shared.b16 [%0], {%1, %2, %3, %4};\n}"
                 ::"r"(addr), "r"(r0), "r"(r1), "r"(r2), "r"(r3), "r"((uint32_t)trans) : "memory");
}
__device__ __forceinline__ void ldmatrix_x4_t(uint32_t addr, uint32_t (&r)[4]) {
    asm volatile("ldmatrix.sync.aligned.m8n8.x4.trans.shared.b16 {%0, %1, %2, %3}, [%4];"
                 : "=r"(r[0]), "=r"(r[1]), "=r"(r[2]), "=r"(r[3]) : "r"(addr) : "memory");
}
__device__ __forceinline__ void mma_16816(float (&d)[4], uint32_t a0, uint32_t a1, uint32_t a2, uint32_t a3, uint32_t b0, uint32_t b1) {
    asm("mma.sync.aligned.m16n8k16.row.col.f32.bf16.bf16.f32 {%0, %1, %2, %3}, {%4, %5, %6, %7}, {%8, %9}, {%0, %1, %2, %3};"
        : "+f"(d[0]), "+f"(d[1]), "+f"(d[2]), "+f"(d[3]) : "r"(a0), "r"(a1), "r"(a2), "r"(a3), "r"(b0), "r"(b1));
}
__device__ __forceinline__ void order_after(float v, uint32_t scratch) {
    asm volatile("{\n.reg .pred p;\nsetp.gt.f32 p, %0, 0f70000000;\n@p st.shared.u32 [%1], 0;\n}" ::"f"(v), "r"(scratch) : "memory");
}
__device__ __forceinline__ float rcp(float x) { float y; asm("rcp.approx.ftz.f32 %0, %1;" : "=f"(y) : "f"(x)); return y; }
__device__ __forceinline__ float ex2(float x) { float y; asm("ex2.approx.ftz.f32 %0, %1;" : "=f"(y) : "f"(x)); return y; }

template <int OA, int OB>
__device__ __forceinline__ void wgmma_ss_n256(float (&d0)[64], float (&d1)[64], uint32_t da, uint32_t db) {
    asm volatile("{\n.reg .b32 ta, tb;\n.reg .b64 da, db;\nadd.u32 ta, %128, %130;\nadd.u32 tb, %129, %131;\n"
        "mov.b64 da, {ta, 0x40000040};\nmov.b64 db, {tb, 0x40000040};\n"
        "wgmma.mma_async.sync.aligned.m64n256k16.f32.bf16.bf16 {%0, %1, %2, %3, %4, %5, %6, %7, %8, %9, %10, %11, %12, %13, %14, %15, %16, %17, %18, %19, %20, %21, %22, %23, %24, %25, %26, %27, %28, %29, %30, %31, %32, %33, %34, %35, %36, %37, %38, %39, %40, %41, %42, %43, %44, %45, %46, %47, %48, %49, %50, %51, %52, %53, %54, %55, %56, %57, %58, %59, %60, %61, %62, %63, %64, %65, %66, %67, %68, %69, %70, %71, %72, %73, %74, %75, %76, %77, %78, %79, %80, %81, %82, %83, %84, %85, %86, %87, %88, %89, %90, %91, %92, %93, %94, %95, %96, %97, %98, %99, %100, %101, %102, %103, %104, %105, %106, %107, %108, %109, %110, %111, %112, %113, %114, %115, %116, %117, %118, %119, %120, %121, %122, %123, %124, %125, %126, %127}, da, db, 1, 1, 1, 0, 1;\n}\n"
        : "+f"(d0[0]), "+f"(d0[1]), "+f"(d0[2]), "+f"(d0[3]), "+f"(d0[4]), "+f"(d0[5]), "+f"(d0[6]), "+f"(d0[7]), "+f"(d0[8]), "+f"(d0[9]), "+f"(d0[10]), "+f"(d0[11]), "+f"(d0[12]), "+f"(d0[13]), "+f"(d0[14]), "+f"(d0[15]), "+f"(d0[16]), "+f"(d0[17]), "+f"(d0[18]), "+f"(d0[19]), "+f"(d0[20]), "+f"(d0[21]), "+f"(d0[22]), "+f"(d0[23]), "+f"(d0[24]), "+f"(d0[25]), "+f"(d0[26]), "+f"(d0[27]), "+f"(d0[28]), "+f"(d0[29]), "+f"(d0[30]), "+f"(d0[31]), "+f"(d0[32]), "+f"(d0[33]), "+f"(d0[34]), "+f"(d0[35]), "+f"(d0[36]), "+f"(d0[37]), "+f"(d0[38]), "+f"(d0[39]), "+f"(d0[40]), "+f"(d0[41]), "+f"(d0[42]), "+f"(d0[43]), "+f"(d0[44]), "+f"(d0[45]), "+f"(d0[46]), "+f"(d0[47]), "+f"(d0[48]), "+f"(d0[49]), "+f"(d0[50]), "+f"(d0[51]), "+f"(d0[52]), "+f"(d0[53]), "+f"(d0[54]), "+f"(d0[55]), "+f"(d0[56]), "+f"(d0[57]), "+f"(d0[58]), "+f"(d0[59]), "+f"(d0[60]), "+f"(d0[61]), "+f"(d0[62]), "+f"(d0[63]), "+f"(d1[0]), "+f"(d1[1]), "+f"(d1[2]), "+f"(d1[3]), "+f"(d1[4]), "+f"(d1[5]), "+f"(d1[6]), "+f"(d1[7]), "+f"(d1[8]), "+f"(d1[9]), "+f"(d1[10]), "+f"(d1[11]), "+f"(d1[12]), "+f"(d1[13]), "+f"(d1[14]), "+f"(d1[15]), "+f"(d1[16]), "+f"(d1[17]), "+f"(d1[18]), "+f"(d1[19]), "+f"(d1[20]), "+f"(d1[21]), "+f"(d1[22]), "+f"(d1[23]), "+f"(d1[24]), "+f"(d1[25]), "+f"(d1[26]), "+f"(d1[27]), "+f"(d1[28]), "+f"(d1[29]), "+f"(d1[30]), "+f"(d1[31]), "+f"(d1[32]), "+f"(d1[33]), "+f"(d1[34]), "+f"(d1[35]), "+f"(d1[36]), "+f"(d1[37]), "+f"(d1[38]), "+f"(d1[39]), "+f"(d1[40]), "+f"(d1[41]), "+f"(d1[42]), "+f"(d1[43]), "+f"(d1[44]), "+f"(d1[45]), "+f"(d1[46]), "+f"(d1[47]), "+f"(d1[48]), "+f"(d1[49]), "+f"(d1[50]), "+f"(d1[51]), "+f"(d1[52]), "+f"(d1[53]), "+f"(d1[54]), "+f"(d1[55]), "+f"(d1[56]), "+f"(d1[57]), "+f"(d1[58]), "+f"(d1[59]), "+f"(d1[60]), "+f"(d1[61]), "+f"(d1[62]), "+f"(d1[63])
        : "r"(da), "r"(db), "n"(OA), "n"(OB));
}

__device__ __forceinline__ void wgmma_ss_n256_init(float (&d0)[64], float (&d1)[64], uint32_t da, uint32_t db) {
    asm volatile("{\n.reg .b64 da, db;\n"
        "mov.b64 da, {%128, 0x40000040};\nmov.b64 db, {%129, 0x40000040};\n"
        "wgmma.mma_async.sync.aligned.m64n256k16.f32.bf16.bf16 {%0, %1, %2, %3, %4, %5, %6, %7, %8, %9, %10, %11, %12, %13, %14, %15, %16, %17, %18, %19, %20, %21, %22, %23, %24, %25, %26, %27, %28, %29, %30, %31, %32, %33, %34, %35, %36, %37, %38, %39, %40, %41, %42, %43, %44, %45, %46, %47, %48, %49, %50, %51, %52, %53, %54, %55, %56, %57, %58, %59, %60, %61, %62, %63, %64, %65, %66, %67, %68, %69, %70, %71, %72, %73, %74, %75, %76, %77, %78, %79, %80, %81, %82, %83, %84, %85, %86, %87, %88, %89, %90, %91, %92, %93, %94, %95, %96, %97, %98, %99, %100, %101, %102, %103, %104, %105, %106, %107, %108, %109, %110, %111, %112, %113, %114, %115, %116, %117, %118, %119, %120, %121, %122, %123, %124, %125, %126, %127}, da, db, 0, 1, 1, 0, 1;\n}\n"
        : "=f"(d0[0]), "=f"(d0[1]), "=f"(d0[2]), "=f"(d0[3]), "=f"(d0[4]), "=f"(d0[5]), "=f"(d0[6]), "=f"(d0[7]), "=f"(d0[8]), "=f"(d0[9]), "=f"(d0[10]), "=f"(d0[11]), "=f"(d0[12]), "=f"(d0[13]), "=f"(d0[14]), "=f"(d0[15]), "=f"(d0[16]), "=f"(d0[17]), "=f"(d0[18]), "=f"(d0[19]), "=f"(d0[20]), "=f"(d0[21]), "=f"(d0[22]), "=f"(d0[23]), "=f"(d0[24]), "=f"(d0[25]), "=f"(d0[26]), "=f"(d0[27]), "=f"(d0[28]), "=f"(d0[29]), "=f"(d0[30]), "=f"(d0[31]), "=f"(d0[32]), "=f"(d0[33]), "=f"(d0[34]), "=f"(d0[35]), "=f"(d0[36]), "=f"(d0[37]), "=f"(d0[38]), "=f"(d0[39]), "=f"(d0[40]), "=f"(d0[41]), "=f"(d0[42]), "=f"(d0[43]), "=f"(d0[44]), "=f"(d0[45]), "=f"(d0[46]), "=f"(d0[47]), "=f"(d0[48]), "=f"(d0[49]), "=f"(d0[50]), "=f"(d0[51]), "=f"(d0[52]), "=f"(d0[53]), "=f"(d0[54]), "=f"(d0[55]), "=f"(d0[56]), "=f"(d0[57]), "=f"(d0[58]), "=f"(d0[59]), "=f"(d0[60]), "=f"(d0[61]), "=f"(d0[62]), "=f"(d0[63]), "=f"(d1[0]), "=f"(d1[1]), "=f"(d1[2]), "=f"(d1[3]), "=f"(d1[4]), "=f"(d1[5]), "=f"(d1[6]), "=f"(d1[7]), "=f"(d1[8]), "=f"(d1[9]), "=f"(d1[10]), "=f"(d1[11]), "=f"(d1[12]), "=f"(d1[13]), "=f"(d1[14]), "=f"(d1[15]), "=f"(d1[16]), "=f"(d1[17]), "=f"(d1[18]), "=f"(d1[19]), "=f"(d1[20]), "=f"(d1[21]), "=f"(d1[22]), "=f"(d1[23]), "=f"(d1[24]), "=f"(d1[25]), "=f"(d1[26]), "=f"(d1[27]), "=f"(d1[28]), "=f"(d1[29]), "=f"(d1[30]), "=f"(d1[31]), "=f"(d1[32]), "=f"(d1[33]), "=f"(d1[34]), "=f"(d1[35]), "=f"(d1[36]), "=f"(d1[37]), "=f"(d1[38]), "=f"(d1[39]), "=f"(d1[40]), "=f"(d1[41]), "=f"(d1[42]), "=f"(d1[43]), "=f"(d1[44]), "=f"(d1[45]), "=f"(d1[46]), "=f"(d1[47]), "=f"(d1[48]), "=f"(d1[49]), "=f"(d1[50]), "=f"(d1[51]), "=f"(d1[52]), "=f"(d1[53]), "=f"(d1[54]), "=f"(d1[55]), "=f"(d1[56]), "=f"(d1[57]), "=f"(d1[58]), "=f"(d1[59]), "=f"(d1[60]), "=f"(d1[61]), "=f"(d1[62]), "=f"(d1[63])
        : "r"(da), "r"(db));
}

template <int TB, int OA, int OB>
__device__ __forceinline__ void wgmma_ss_n128_init(float (&d)[64], uint32_t da, uint32_t db) {
    asm volatile("{\n.reg .b32 ta, tb;\n.reg .b64 da, db;\nadd.u32 ta, %64, %66;\nadd.u32 tb, %65, %67;\n"
        "mov.b64 da, {ta, 0x40000040};\nmov.b64 db, {tb, 0x40000040};\n"
        "wgmma.mma_async.sync.aligned.m64n128k16.f32.bf16.bf16 {%0, %1, %2, %3, %4, %5, %6, %7, %8, %9, %10, %11, %12, %13, %14, %15, %16, %17, %18, %19, %20, %21, %22, %23, %24, %25, %26, %27, %28, %29, %30, %31, %32, %33, %34, %35, %36, %37, %38, %39, %40, %41, %42, %43, %44, %45, %46, %47, %48, %49, %50, %51, %52, %53, %54, %55, %56, %57, %58, %59, %60, %61, %62, %63}, da, db, 0, 1, 1, 0, %68;\n}\n"
        : "=f"(d[0]), "=f"(d[1]), "=f"(d[2]), "=f"(d[3]), "=f"(d[4]), "=f"(d[5]), "=f"(d[6]), "=f"(d[7]), "=f"(d[8]), "=f"(d[9]), "=f"(d[10]), "=f"(d[11]), "=f"(d[12]), "=f"(d[13]), "=f"(d[14]), "=f"(d[15]), "=f"(d[16]), "=f"(d[17]), "=f"(d[18]), "=f"(d[19]), "=f"(d[20]), "=f"(d[21]), "=f"(d[22]), "=f"(d[23]), "=f"(d[24]), "=f"(d[25]), "=f"(d[26]), "=f"(d[27]), "=f"(d[28]), "=f"(d[29]), "=f"(d[30]), "=f"(d[31]), "=f"(d[32]), "=f"(d[33]), "=f"(d[34]), "=f"(d[35]), "=f"(d[36]), "=f"(d[37]), "=f"(d[38]), "=f"(d[39]), "=f"(d[40]), "=f"(d[41]), "=f"(d[42]), "=f"(d[43]), "=f"(d[44]), "=f"(d[45]), "=f"(d[46]), "=f"(d[47]), "=f"(d[48]), "=f"(d[49]), "=f"(d[50]), "=f"(d[51]), "=f"(d[52]), "=f"(d[53]), "=f"(d[54]), "=f"(d[55]), "=f"(d[56]), "=f"(d[57]), "=f"(d[58]), "=f"(d[59]), "=f"(d[60]), "=f"(d[61]), "=f"(d[62]), "=f"(d[63])
        : "r"(da), "r"(db), "n"(OA), "n"(OB), "n"(TB));
}

template <int OA, int OB>
__device__ __forceinline__ void wgmma_ss_n128_tb0(float (&d)[64], uint32_t da, uint32_t db, int scale_d) {
    asm volatile("{\n.reg .pred p;\n.reg .b32 ta, tb;\n.reg .b64 da, db;\nsetp.ne.b32 p, %66, 0;\nadd.u32 ta, %64, %67;\nadd.u32 tb, %65, %68;\n"
        "mov.b64 da, {ta, 0x40000040};\nmov.b64 db, {tb, 0x40000040};\n"
        "wgmma.mma_async.sync.aligned.m64n128k16.f32.bf16.bf16 "
        "{%0, %1, %2, %3, %4, %5, %6, %7, %8, %9, %10, %11, %12, %13, %14, %15, %16, %17, %18, %19, %20, %21, %22, %23, %24, %25, %26, %27, %28, %29, %30, %31, %32, %33, %34, %35, %36, %37, %38, %39, %40, %41, %42, %43, %44, %45, %46, %47, %48, %49, %50, %51, %52, %53, %54, %55, %56, %57, %58, %59, %60, %61, %62, %63}, da, db, p, 1, 1, 0, 0;\n}\n"
        : "+f"(d[0]), "+f"(d[1]), "+f"(d[2]), "+f"(d[3]), "+f"(d[4]), "+f"(d[5]), "+f"(d[6]), "+f"(d[7]), "+f"(d[8]), "+f"(d[9]), "+f"(d[10]), "+f"(d[11]), "+f"(d[12]), "+f"(d[13]), "+f"(d[14]), "+f"(d[15]), "+f"(d[16]), "+f"(d[17]), "+f"(d[18]), "+f"(d[19]), "+f"(d[20]), "+f"(d[21]), "+f"(d[22]), "+f"(d[23]), "+f"(d[24]), "+f"(d[25]), "+f"(d[26]), "+f"(d[27]), "+f"(d[28]), "+f"(d[29]), "+f"(d[30]), "+f"(d[31]), "+f"(d[32]), "+f"(d[33]), "+f"(d[34]), "+f"(d[35]), "+f"(d[36]), "+f"(d[37]), "+f"(d[38]), "+f"(d[39]), "+f"(d[40]), "+f"(d[41]), "+f"(d[42]), "+f"(d[43]), "+f"(d[44]), "+f"(d[45]), "+f"(d[46]), "+f"(d[47]), "+f"(d[48]), "+f"(d[49]), "+f"(d[50]), "+f"(d[51]), "+f"(d[52]), "+f"(d[53]), "+f"(d[54]), "+f"(d[55]), "+f"(d[56]), "+f"(d[57]), "+f"(d[58]), "+f"(d[59]), "+f"(d[60]), "+f"(d[61]), "+f"(d[62]), "+f"(d[63])
        : "r"(da), "r"(db), "r"(scale_d), "n"(OA), "n"(OB));
}

template <int OB>
__device__ __forceinline__ void wgmma_rs_n128_tb1(float (&d)[64], uint32_t a0, uint32_t a1, uint32_t a2, uint32_t a3, uint32_t db, int scale_d) {
    asm volatile("{\n.reg .pred p;\n.reg .b32 tb;\n.reg .b64 db;\nsetp.ne.b32 p, %69, 0;\nadd.u32 tb, %68, %70;\n"
        "mov.b64 db, {tb, 0x40000040};\n"
        "wgmma.mma_async.sync.aligned.m64n128k16.f32.bf16.bf16 "
        "{%0, %1, %2, %3, %4, %5, %6, %7, %8, %9, %10, %11, %12, %13, %14, %15, %16, %17, %18, %19, %20, %21, %22, %23, %24, %25, %26, %27, %28, %29, %30, %31, %32, %33, %34, %35, %36, %37, %38, %39, %40, %41, %42, %43, %44, %45, %46, %47, %48, %49, %50, %51, %52, %53, %54, %55, %56, %57, %58, %59, %60, %61, %62, %63}, {%64, %65, %66, %67}, db, p, 1, 1, 1;\n}\n"
        : "+f"(d[0]), "+f"(d[1]), "+f"(d[2]), "+f"(d[3]), "+f"(d[4]), "+f"(d[5]), "+f"(d[6]), "+f"(d[7]), "+f"(d[8]), "+f"(d[9]), "+f"(d[10]), "+f"(d[11]), "+f"(d[12]), "+f"(d[13]), "+f"(d[14]), "+f"(d[15]), "+f"(d[16]), "+f"(d[17]), "+f"(d[18]), "+f"(d[19]), "+f"(d[20]), "+f"(d[21]), "+f"(d[22]), "+f"(d[23]), "+f"(d[24]), "+f"(d[25]), "+f"(d[26]), "+f"(d[27]), "+f"(d[28]), "+f"(d[29]), "+f"(d[30]), "+f"(d[31]), "+f"(d[32]), "+f"(d[33]), "+f"(d[34]), "+f"(d[35]), "+f"(d[36]), "+f"(d[37]), "+f"(d[38]), "+f"(d[39]), "+f"(d[40]), "+f"(d[41]), "+f"(d[42]), "+f"(d[43]), "+f"(d[44]), "+f"(d[45]), "+f"(d[46]), "+f"(d[47]), "+f"(d[48]), "+f"(d[49]), "+f"(d[50]), "+f"(d[51]), "+f"(d[52]), "+f"(d[53]), "+f"(d[54]), "+f"(d[55]), "+f"(d[56]), "+f"(d[57]), "+f"(d[58]), "+f"(d[59]), "+f"(d[60]), "+f"(d[61]), "+f"(d[62]), "+f"(d[63])
        : "r"(a0), "r"(a1), "r"(a2), "r"(a3), "r"(db), "r"(scale_d), "n"(OB));
}

__device__ __forceinline__ uint32_t stage_addr(uint32_t block, int warp, int lane) {
    return block + (warp * 16 + (lane & 7) + ((lane >> 3) & 1) * 8) * 128 + (((lane >> 4) ^ (lane & 7)) << 4);
}
template <int OFF, int N>
__device__ __forceinline__ void stage_packed_64x64(uint32_t a0, int off, const uint32_t (&v)[N]) {
#pragma unroll
    for (int j = 0; j < 8; j += 2) {
        uint32_t a = a0;
        if (j) asm volatile("xor.b32 %0, %1, %2;" : "=r"(a) : "r"(a0), "r"(j << 4));
        stmatrix_x4(a + off, v[OFF + j * 2], v[OFF + j * 2 + 1], v[OFF + j * 2 + 2], v[OFF + j * 2 + 3]);
    }
}

template <int OFF, int N>
__device__ __forceinline__ void stage_packed_64x64(const uint32_t (&a)[4], int off, const uint32_t (&v)[N]) {
#pragma unroll
    for (int j = 0; j < 4; j++) stmatrix_x4(a[j] + off, v[OFF + j * 4], v[OFF + j * 4 + 1], v[OFF + j * 4 + 2], v[OFF + j * 4 + 3]);
}

template <int OFF, int N>
__device__ __forceinline__ void stage_packed_64x64(const uint32_t (&a)[4], int off, const uint32_t (&v)[N], bool trans) {
#pragma unroll
    for (int j = 0; j < 4; j++) stmatrix_x4(a[j] + off, v[OFF + j * 4], v[OFF + j * 4 + 1], v[OFF + j * 4 + 2], v[OFF + j * 4 + 3], trans);
}

constexpr int MAX_JOBS = 24;
constexpr int MAX_ROUNDS = 44;
constexpr int T_P = 0, T_O = 1, T_A = 2;
constexpr int HQ_A = 4, HQ_B = 28;
__host__ __device__ constexpr int unit_head(int g) { return g + (g < 4 ? HQ_A : HQ_B - 4); }
constexpr int G_STAGE = 49152;
constexpr int OFF_Q0 = 0, OFF_K0 = 32768, OFF_Q1 = 65536, OFF_K1 = 98304, OFF_V0 = 131072, OFF_V1 = 163840;
constexpr int OFF_STG = 196608;
constexpr int OFF_BAR = 229376;
constexpr int SMEM_BYTES = OFF_BAR + 640;
constexpr int TURN_THREADS = 288;

struct Params {
    CUtensorMap amap[2];
    CUtensorMap wmap[4];
    CUtensorMap x_par, wo_a, wo_b, qkv_st, qkv_ld, qkv_half, st_par, out_st;
    const __nv_bfloat16* xp;
    const __nv_bfloat16* gate_w;
    __nv_bfloat16* out;
    uint2 first[NUM_SMS];
    int16_t jobs[NUM_SMS][MAX_JOBS];
    uint16_t rounds[NUM_SMS / 2][MAX_ROUNDS];
};

constexpr int O_STAGGER = 4;
constexpr int O_F0 = 35, O_H1 = 5;
constexpr int O_FLEX = 16, O_H0 = O_F0 + 8, O_T0 = 8, O_T1 = 64 - O_F0 - O_FLEX - O_H1;
__device__ __forceinline__ int o_head(int job) { return (job & 32) ? O_H1 : O_H0; }
__device__ __forceinline__ int o_tail(int job) { return (job & 32) ? O_T1 : O_T0; }
__device__ __forceinline__ uint32_t o_state(uint32_t word, int have) {
    uint32_t v;
    asm volatile("{\n.reg .pred p, q;\n.reg .u32 c, t;\nmov.u32 c, 0;\n"
                 "SPIN:\nld.volatile.shared.u32 %0, [%1];\nand.b32 t, %0, 1;\nsetp.ne.u32 q, t, 0;\nsetp.gt.or.u32 p, %0, %2, q;\n@p bra DONE;\n"
                 "add.u32 c, c, 1;\nsetp.lt.u32 q, c, 16777216;\n@q bra SPIN;\ntrap;\nDONE:\n}"
                 : "=r"(v) : "r"(word), "r"(2 * have + 1) : "memory");
    return v;
}

template <class T> __device__ __forceinline__ T* page_ptr(int off) {
    extern __shared__ __align__(1024) uint8_t smem_raw[];
    return *reinterpret_cast<T* volatile*>(smem_raw + OFF_BAR + off);
}
template <int SLEEP_NS = 0>
__device__ __forceinline__ bool wait_flags(bool active, int idx, uint32_t target, bool block = true) {
    for (uint32_t tries = 0;; tries++) {
        const bool ok = !active | ((int32_t)(ld_acquire(g_flags + idx) - target) >= 0);
        if (__all_sync(0xffffffffu, ok)) break;
        if (!block) return false;
        if (SLEEP_NS) __nanosleep(SLEEP_NS);
        trap_if(tries > (1u << 22));
    }
    fence_async_global();
    return true;
}

__global__ void __cluster_dims__(2, 1, 1) __launch_bounds__(384, 1)
fused_kernel(const __grid_constant__ Params p) {
    extern __shared__ __align__(1024) uint8_t smem_raw[];
    const uint32_t base = smem_u32(smem_raw);
    const uint32_t bars = base + OFF_BAR;
    const uint32_t gfull = bars, gempty = bars + 32, sfull = bars + 64, sempty = bars + 96;
    const uint32_t qfull = bars + 128, qempty = bars + 144, kfull = bars + 160, kempty = bars + 176;
    const uint32_t vfull = bars + 192, vempty = bars + 208, lready = bars + 224, hout = bars + 240;
    const uint32_t tfull = bars + 256, aready = bars + 272, gatefull = bars + 280;
    const uint32_t otile = bars + 528;
    const uint32_t olim = bars + 504;
    const uint32_t stg = base + OFF_STG;
    uint32_t* rounds = reinterpret_cast<uint32_t*>(smem_raw + OFF_BAR + 416);
    const uint32_t rank = cluster_rank();
    int* jobs = reinterpret_cast<int*>(smem_raw + OFF_BAR + 312);
    auto w_map = [&](uint32_t rec, uint32_t half) INL { return &p.wmap[(rec & 8) ? 2 + half : ((rec >> 15) && half ? 0 : rec >> 4 & 1)]; };
    auto w_blk = [&](uint32_t rec, uint32_t half) INL -> int {
        const int col = rec >> 6 & 15;
        if (rec & 8) return (col + (rec & 16)) * 2;
        return rec >> 14 == 0 ? col * 4 + half * 2 : (rec >> 14 == 1 ? 16 + half * 16 + col * 2 : (half ? unit_head(col) : col) * 2);
    };
    auto load_round = [&](uint32_t rec, int st0, uint32_t parity) INL {
        const CUtensorMap* wm = w_map(rec, rank);
        const CUtensorMap* am = rec >> 14 ? &p.x_par : &p.amap[rec >> 3 & 1];
        const int wb = w_blk(rec, rank), kc0 = (rec >> 10 & 3) * 4, arow = ((rec & 7) * 256 + rank * 128) >> (rec >> 14 ? 1 : 0);
        const uint32_t bytes = (rec & 4096) ? G_STAGE - 16384 : G_STAGE, amode = (rec & 4096) ? 0 : (rec >> 14 ? 2 : 1);
#pragma unroll 1
        for (int st = st0; st < 4; st++) {
            const uint32_t sa = base + st * G_STAGE;
            mbar_wait(gempty + st * 8, parity);
            load_kstep(sa, sa + 16384 + rank * 16384, gfull + st * 8, bytes, wm, kc0 + st, wb, am, arow, kc0 + st, amode);
        }
    };
    if (threadIdx.x < 32) {
        if (elect_one()) {
            const uint2 r = p.first[blockIdx.x];
            mbar_init(gfull, 1);
            fence_async_smem();
            const char* maps;
            asm("mov.b64 %0, %1;" : "=l"(maps) : "l"(&p.amap[0]));
            asm volatile("{\n.reg .pred q;\nsetp.eq.u32 q, %8, 0;\n"
                         "mbarrier.arrive.expect_tx.shared::cta.b64 _, [%1], 49152;\n"
                         "cp.async.bulk.tensor.3d.shared::cluster.global.mbarrier::complete_tx::bytes.L2::cache_hint [%9], [%3, {0, 0, %6}], [%1], %11;\n"
                         "cp.async.bulk.tensor.3d.shared::cluster.global.mbarrier::complete_tx::bytes.L2::cache_hint [%10], [%4, {0, 0, %7}], [%1], %11;\n"
                         "@q cp.async.bulk.tensor.3d.shared::cluster.global.mbarrier::complete_tx::bytes.L2::cache_hint [%0], [%2, {0, %5, 0}], [%1], %11;\n"
                         "@!q cp.async.bulk.tensor.4d.shared::cluster.global.mbarrier::complete_tx::bytes.L2::cache_hint [%0], [%2, {0, %5, 0, 0}], [%1], %11;\n}"
                         ::"r"(base), "r"(gfull), "l"(maps + (r.x & 0x780)), "l"(maps + (r.x >> 4 & 0x780)), "l"(maps + (r.x >> 8 & 0x780)),
                           "r"(r.x >> 20), "r"(r.y & 0xffff), "r"(r.y >> 16), "r"(r.x & 1), "r"(base + 16384), "r"(base + 32768), "l"(POL_NORMAL) : "memory");
            asm volatile("fence.mbarrier_init.release.cluster;" ::: "memory");
        }
        __syncwarp();
    }
    const int tid = threadIdx.x, warp = uniform(tid >> 5), lane = tid & 31, wg = warp >> 2;
    if (warp == 1) {
        if (elect_one()) {
#pragma unroll
            for (int i = 1; i < 39; i++)
                mbar_init(bars + i * 8, (0x0CC000F0ull >> i & 1) ? 16 : ((0x300000F00ull >> i & 1) ? 4 : ((0xC0000ull >> i & 1) ? 8 : 1)));
            asm volatile("fence.mbarrier_init.release.cluster;" ::: "memory");
            fence_async_smem();
        }
        __syncwarp();
    }
    setup_arrive();
    if (warp > 3) {
        reg_inc<232>();
        named_sync(0, 352);
        const int w = wg - 1, wwarp = warp & 3;
        const uint32_t slot_a = stage_addr(stg + w * 16384, wwarp, lane);
        const uint32_t bars_peer = uniform(mapa(bars, rank ^ 1));
        auto arrive_pair = [&](uint32_t bar, bool pred = true) INL { warp_arrive_pair(bar, bars_peer + (bar - bars), pred); };
        uint32_t gph = 0;
        uint32_t sph = 1;
        int jb = 0;
        int job = uniform(jobs[0]);
        auto next_job = [&]() INL { jb++; job = uniform(jobs[jb]); };
        auto slot_wait = [&](int q) INL { mbar_wait(sempty + (w * 2 + (q & 1)) * 8, (q >> 1) ^ sph ^ 1); };
        auto signal = [&](int q) INL {
            __syncwarp();
            warp_arrive(sfull + (w * 2 + (q & 1)) * 8);
        };
        uint32_t pk[64];
        float O[64];
        float oscale1 = 1.f;
        uint32_t slot4[4];
        bool ptrans = false;
        auto stage_quarter = [&](const int Q) INL {
            slot_wait(Q);
            if (Q == 0) stage_packed_64x64<0>(slot4, 0, pk, ptrans);
            if (Q == 1) stage_packed_64x64<16>(slot4, 8192, pk, ptrans);
            if (Q == 2) stage_packed_64x64<32>(slot4, 0, pk);
            if (Q == 3) stage_packed_64x64<48>(slot4, 8192, pk);
        };
        auto stage_pair = [&]() INL {
            slot_wait(1);
            stage_packed_64x64<0>(slot4, 0, pk, ptrans);
            stage_packed_64x64<16>(slot4, 8192, pk, ptrans);
        };
        auto signal_both = [&]() INL {
            __syncwarp();
            warp_arrive2(sfull + w * 16, sfull + w * 16 + 8);
        };
        uint32_t un = 0;
        auto lane_id = [&]() INL { uint32_t ln; asm volatile("mov.u32 %0, %%laneid;" : "=r"(ln)); return ln; };
        auto v_addr = [&](uint32_t ln) INL { return stg + w * 16384 + (wwarp * 16 + (ln & 7)) * 128 + (((ln >> 3) ^ (ln & 7)) << 4); };
        auto v_off = [&](uint32_t a, const int h) INL { return (a ^ ((h & 1) * 64)) + (h >> 1) * 8192; };
        auto halo_ptr = [&](int mt, int g, int slot, uint32_t ln) INL { return page_ptr<uint4>(512) + (((mt * 8 + g) * 2 + w) * 5 + slot) * 128 + ln; };
        auto pack_k = [&](const float (&acc)[64]) INL {
#pragma unroll
            for (int j = 0; j < 16; j++) { pk[j] = pack_bf16(acc[4 * j], acc[4 * j + 1]); pk[16 + j] = pack_bf16(acc[4 * j + 2], acc[4 * j + 3]); }
        };
        auto unit_export = [&](int cur) INL {
            const uint32_t ln = lane_id();
            uint4* dst = halo_ptr((cur & 7) * 2 + rank, cur >> 3 & 7, wwarp, ln);
            slot_wait(1);
            stage_packed_64x64<32>(slot4, 0, pk);
            stage_packed_64x64<48>(slot4, 8192, pk);
#pragma unroll
            for (int h = 0; h < 4; h++) __stcg(dst + h * 32, make_uint4(pk[16 + h * 4], pk[17 + h * 4], pk[18 + h * 4], pk[19 + h * 4]));
            __syncwarp();
            if (wwarp == 3) {
                const uint32_t va = v_addr(ln) + 1024;
#pragma unroll
                for (int h = 0; h < 4; h++) {
                    uint32_t t[4];
                    ldmatrix_x4_t(v_off(va, h), t);
                    pk[32 + h * 4] = t[0]; pk[33 + h * 4] = t[1]; pk[34 + h * 4] = t[2]; pk[35 + h * 4] = t[3];
                }
#pragma unroll
                for (int h = 0; h < 4; h++) __stcg(dst + 128 + h * 32, make_uint4(pk[32 + h * 4], pk[33 + h * 4], pk[34 + h * 4], pk[35 + h * 4]));
                __syncwarp();
                warp_arrive(hout + w * 8);
            }
        };
        auto unit_import = [&](int cur) INL {
            const uint32_t ln = lane_id();
            const int mt = (cur & 7) * 2 + rank;
            mbar_wait(lready + un * 8, 0);
            un++;
            const uint4* src = halo_ptr(wwarp ? mt : max(mt - 1, 0), cur >> 3 & 7, (wwarp + 3) & 3, ln);
#pragma unroll
            for (int h = 0; h < 4; h++) {
                const uint4 t = __ldcg(src + h * 32);
                pk[32 + h * 4] = t.x; pk[33 + h * 4] = t.y; pk[34 + h * 4] = t.z; pk[35 + h * 4] = t.w;
            }
            if (wwarp) {
                const uint32_t va = v_addr(ln) - 1024;
#pragma unroll
                for (int h = 0; h < 4; h++) {
                    uint32_t t[4];
                    ldmatrix_x4_t(v_off(va, h), t);
                    pk[48 + h * 4] = t[0]; pk[49 + h * 4] = t[1]; pk[50 + h * 4] = t[2]; pk[51 + h * 4] = t[3];
                }
            } else {
#pragma unroll
                for (int h = 0; h < 4; h++) {
                    const uint4 t = __ldcg(src + 128 + h * 32);
                    pk[48 + h * 4] = t.x; pk[49 + h * 4] = t.y; pk[50 + h * 4] = t.z; pk[51 + h * 4] = t.w;
                }
            }
        };
        auto unit_attend = [&](const float (&q)[64], int cur) INL {
            const float cs = 0.17677669529663687f * 1.4426950408889634f;
            const uint32_t ln = lane_id();
            const int g = ln >> 2, c2 = (ln & 3) * 2, mt = (cur & 7) * 2 + rank;
            uint32_t qf[32], vo[8][4];
#pragma unroll
            for (int i = 0; i < 32; i++) qf[i] = pack_bf16(q[2 * i], q[2 * i + 1]);
            fence_regs(qf);
            const float* gp = page_ptr<float>(520) + mt * 128 + wwarp * 32 + g * 2 + w;
            const float lg0 = 1.f - __ldcg(gp), lg1 = 1.f - __ldcg(gp + 16);
            const uint32_t va = stg + w * 16384 + (wwarp * 16 + (ln & 7) + (ln >> 4) * 8) * 128 + ((((ln >> 3) & 1) ^ (ln & 7)) << 4);
#pragma unroll
            for (int i = 0; i < 8; i++) ldmatrix_x4_t((va ^ ((i & 3) * 32)) + (i >> 2) * 8192, vo[i]);
            const bool m0 = c2 > g, m1 = c2 + 1 > g, first = mt + wwarp == 0;
            const uint32_t mk = (m0 ? 0xffffu : 0u) | (m1 ? 0xffff0000u : 0u);
#pragma unroll
            for (int h = 0; h < 4; h++) {
                float s[3][4] = {};
#pragma unroll
                for (int k = 0; k < 2; k++) {
                    const int i = h * 8 + k * 4, j = h * 4 + k * 2;
                    mma_16816(s[0], qf[i], qf[i + 1], qf[i + 2], qf[i + 3], pk[32 + j], pk[33 + j]);
                    mma_16816(s[1], qf[i], qf[i + 1], qf[i + 2], qf[i + 3], pk[j], pk[j + 1]);
                    mma_16816(s[2], qf[i], qf[i + 1], qf[i + 2], qf[i + 3], pk[16 + j], pk[17 + j]);
                }
                if (first) s[0][0] = s[0][1] = -INFINITY;
                float u0 = m0 ? s[0][0] : s[1][0], u1 = m1 ? s[0][1] : s[1][1], v0 = m0 ? s[1][2] : s[2][2], v1 = m1 ? s[1][3] : s[2][3];
                float mu = fmaxf(u0, u1), mv = fmaxf(v0, v1);
                mu = fmaxf(mu, __shfl_xor_sync(0xffffffffu, mu, 1)); mv = fmaxf(mv, __shfl_xor_sync(0xffffffffu, mv, 1));
                mu = fmaxf(mu, __shfl_xor_sync(0xffffffffu, mu, 2)); mv = fmaxf(mv, __shfl_xor_sync(0xffffffffu, mv, 2));
                mu *= -cs; mv *= -cs;
                u0 = ex2(fmaf(u0, cs, mu)); u1 = ex2(fmaf(u1, cs, mu)); v0 = ex2(fmaf(v0, cs, mv)); v1 = ex2(fmaf(v1, cs, mv));
                float lu = u0 + u1, lv = v0 + v1;
                lu += __shfl_xor_sync(0xffffffffu, lu, 1); lv += __shfl_xor_sync(0xffffffffu, lv, 1);
                lu += __shfl_xor_sync(0xffffffffu, lu, 2); lv += __shfl_xor_sync(0xffffffffu, lv, 2);
                const float su = lg0 * rcp(lu), sv = lg1 * rcp(lv);
                const uint32_t pu = pack_bf16(u0 * su, u1 * su), pv = pack_bf16(v0 * sv, v1 * sv);
#pragma unroll
                for (int d = 0; d < 2; d++) {
                    const uint32_t (&vv)[4] = vo[h * 2 + d];
                    float oa[4] = {}, ob[4] = {};
                    mma_16816(oa, pk[48 + h * 4 + d * 2], pk[49 + h * 4 + d * 2], vv[0], vv[1], pu & mk, pu & ~mk);
                    mma_16816(ob, vv[0], vv[1], vv[2], vv[3], pv & mk, pv & ~mk);
                    qf[h * 8 + d * 4] = pack_bf16(oa[0], oa[1]); qf[h * 8 + d * 4 + 1] = pack_bf16(ob[0], ob[1]);
                    qf[h * 8 + d * 4 + 2] = pack_bf16(oa[2], oa[3]); qf[h * 8 + d * 4 + 3] = pack_bf16(ob[2], ob[3]);
                }
            }
#pragma unroll
            for (int i = 0; i < 32; i++) pk[i] = qf[i];
            named_sync(3 + w, 128);
        };
        auto pack_half = [&](const float (&acc)[64], const int OFF, float scale) INL {
#pragma unroll
            for (int i = 0; i < 32; i++) pk[OFF + i] = pack_bf16(acc[2 * i] * scale, acc[2 * i + 1] * scale);
        };
        auto gemm_run = [&]() INL {
                float acc0[64], acc1[64];
#pragma unroll
                for (int i = 0; i < 64; i++) pk[i] = 0;
#pragma unroll
                for (int j = 0; j < 4; j++) asm volatile("xor.b32 %0, %1, %2;" : "=r"(slot4[j]) : "r"(slot_a), "r"(j << 5));
                const uint32_t dA = desc_lo(base + w * 8192, 0), dB = desc_lo(base + 16384, 8192);
                auto wait_full = [&](int st) INL { mbar_wait_hot(gfull + st * 8, gph); };
                auto release = [&](int st) INL { arrive_pair(gempty + st * 8); };
                bool pend = false;
                auto kstep = [&](auto st_, const int Q, bool ending = false) INL {
                    constexpr int st = decltype(st_)::v, OA = st * (G_STAGE >> 4);
                    const bool held = st == 2 && ending && w;
                    if (st == 2 && __builtin_expect(held, 0)) {
                        wg_wait<0>();
                        release(1);
                        named_sync(6, 256);
                    }
                    wait_full(st);
                    wg_fence();
                    wgmma_ss_n256<OA, OA>(acc0, acc1, dA, dB);
                    wg_commit();
                    wg_wait<1>();
                    arrive_pair(gempty + ((st + 3) & 3) * 8, !held);
                    wg_fence();
                    wgmma_ss_n256<OA + 2, OA + 128>(acc0, acc1, dA, dB);
                    wgmma_ss_n256<OA + 4, OA + 256>(acc0, acc1, dA, dB);
                    if (st == 3) named_arrive_if(ending && !w, 6, 256);
                    wgmma_ss_n256<OA + 6, OA + 384>(acc0, acc1, dA, dB);
                    wg_commit();
                    if (Q >= 0) { stage_quarter(Q); signal(Q); }
                    KTRACE(w);
                };
                wait_full(0);
                GTRACE(w);
                while (true) {
                    wg_fence();
                    wgmma_ss_n256_init(acc0, acc1, dA, dB);
                    wgmma_ss_n256<2, 128>(acc0, acc1, dA, dB);
                    wgmma_ss_n256<4, 256>(acc0, acc1, dA, dB);
                    wgmma_ss_n256<6, 384>(acc0, acc1, dA, dB);
                    wg_commit();
                    KTRACE(w);
                    const int cur = job;
                    const bool is_o = cur >= (T_O << 12), unit2 = (cur >> 6) == 3;
                    const int tail = o_tail(cur);
                    int lim = is_o ? o_head(cur) + tail : (cur < 256 ? 16 : 8);
                    int left = unit2 ? 11 : lim - (is_o ? O_STAGGER + 1 : 1);
                    bool imp = unit2;
                    next_job();
                    if (__builtin_expect(unit2, 0)) { if (tid == TRACE_TID) PTRACE(4); unit_export(cur); if (tid == TRACE_TID) PTRACE(5); }
                    if (pend) {
                        kstep(IC<1>{}, 0);
                        kstep(IC<2>{}, -1);
                        kstep(IC<3>{}, 1);
                        GTRACE(w);
                        gph ^= 1;
                        kstep(IC<0>{}, -1);
                        kstep(IC<1>{}, 2);
                        kstep(IC<2>{}, 3, left == 7);
                        kstep(IC<3>{}, -1, left == 7);
                        GTRACE(w);
                        gph ^= 1;
                        left -= 7;
                        if (left > 0) { kstep(IC<0>{}, -1); left--; }
                    }
                    int last_st = 3;
#pragma unroll 1
                    while (left > 0) {
                        auto ends = [&]() INL -> bool {
                            if (__builtin_expect(--left > 0, 1)) return false;
                            if (is_o) {
                                const uint32_t v = uniform(o_state(olim, lim - tail));
                                const int n = (v >> 1) + ((v & 1) ? 0 : tail);
                                left = n - lim; lim = n;
                            }
                            return left == 0;
                        };
                        kstep(IC<1>{}, -1);
                        if (ends()) { last_st = 1; break; }
                        kstep(IC<2>{}, -1, left == 2 && !is_o && !imp);
                        if (ends()) { last_st = 2; break; }
                        kstep(IC<3>{}, -1, left == 1 && !is_o && !imp);
                        GTRACE(w);
                        gph ^= 1;
                        if (ends()) {
                            if (!imp) break;
                            if (tid == TRACE_TID) PTRACE(6);
                            unit_import(cur);
                            if (tid == TRACE_TID) PTRACE(7);
                            imp = false; left = 4;
                        }
                        kstep(IC<0>{}, -1);
                        if (ends()) { last_st = 0; break; }
                    }
                    if (is_o) {
                        if (w) {
                            wg_wait<0>();
                            release(last_st);
                            named_sync(6, 256);
                        }
#pragma unroll 1
                        for (int i = 1; i <= O_STAGGER; i++) {
                            const int st = (last_st + i) & 3;
                            if (i > 1 && st == 0) gph ^= 1;
                            wait_full(st);
                            const uint32_t a = dA + st * (G_STAGE >> 4), b = dB + st * (G_STAGE >> 4);
                            wg_fence();
                            wgmma_ss_n256<0, 0>(acc0, acc1, a, b);
                            wgmma_ss_n256<2, 128>(acc0, acc1, a, b);
                            wgmma_ss_n256<4, 256>(acc0, acc1, a, b);
                            wgmma_ss_n256<6, 384>(acc0, acc1, a, b);
                            wg_commit();
                            named_arrive_if(!w && i == O_STAGGER, 6, 256);
                            wg_wait<1>();
                            arrive_pair(gempty + last_st * 8, i == 1 && !w);
                        }
                        slot_wait(1);
                        wg_wait<0>();
                        fence_regs(acc0);
                        fence_regs(acc1);
                        auto put = [&](const float (&acc)[64], const int Q, int off) INL {
#pragma unroll
                            for (int j = 0; j < 4; j++) {
                                const float* o = acc + Q * 32 + j * 8;
                                stmatrix_x4(slot4[j] + off, pack_bf16(o[0], o[1]), pack_bf16(o[2], o[3]), pack_bf16(o[4], o[5]), pack_bf16(o[6], o[7]));
                            }
                        };
                        put(acc0, 0, 0);
                        signal(0);
                        put(acc0, 1, 8192);
                        signal(1);
                        put(acc1, 0, -OFF_STG - w * 8192);
                        put(acc1, 1, G_STAGE - OFF_STG - w * 8192);
                        __syncwarp();
                        warp_arrive(tfull + w * 8);
#pragma unroll
                        for (int i = 1; i <= O_STAGGER; i++) release((last_st + i) & 3);
                        GTRACE(w);
#pragma unroll
                        for (int i = 0; i < 64; i++) O[i] = 0.f;
                        break;
                    }
                    if (tid == 128 && !is_o) PTRACE(12);
                    oscale1 = cur < 128 || unit2 ? Q_SCALE : 1.f;
                    ptrans = unit2;
                    if (tid == TRACE_TID && unit2) PTRACE(1);
                    named_arrive_if(w && job >= (T_A << 12), 1, TURN_THREADS);
                    wg_wait<0>();
                    fence_regs(acc0);
                    fence_regs(acc1);
                    release(3);
                    if (tid == TRACE_TID && unit2) PTRACE(2);
                    if (__builtin_expect(unit2, 0)) { unit_attend(acc0, cur); if (tid == TRACE_TID) PTRACE(3); }
                    else if (__builtin_expect((cur >> 6) == 2, 0)) pack_k(acc0);
                    else if (cur < 128) pack_half(acc0, 0, Q_SCALE);
                    else pack_half(acc0, 0, 1.f);
                    if (job >= (T_A << 12)) {
                        stage_pair();
                        signal_both();
#pragma unroll
                        for (int i = 0; i < 64; i++) asm volatile("mul.f32 %0, %1, %2;" : "=f"(O[i]) : "f"(acc1[i]), "f"(oscale1));
                        break;
                    }
                    if (cur < 128 || unit2) pack_half(acc1, 32, Q_SCALE);
                    else pack_half(acc1, 32, 1.f);
                    fence_regs(pk);
                    wait_full(0);
                    pend = (cur >> 6) != 2;
                }
        };
        setup_wait();
#pragma unroll 1
        while (true) {
        gemm_run();
        if (job < 0) break;
        if (tid == 128) PTRACE(11);
        GTRACE(w);
        {
            {
                sph ^= 1;
                uint32_t step = ~0u, ajob = ~0u;
                const int r0 = w * 64 + wwarp * 16 + (lane >> 2);
                float S[64];
                uint32_t P[32] = {};
                fence_regs(P);
                float m0 = 0.f, m1 = 0.f, l0 = 0.25f, l1 = 0.25f, g0 = 1.f, g1 = 1.f, e0 = 0.f, e1 = 0.f;
                constexpr float SUM_MAX = 1.1529215e18f;
                float sum_max = SUM_MAX;
                int rem = 0;
                int maskrem = 0;
                uint32_t starts = 1;
                auto issue_S = [&]() INL {
                    const uint32_t da = desc_lo(base + OFF_Q0 + w * 8192, 0) + (ajob & 1) * ((OFF_Q1 - OFF_Q0) >> 4);
                    const uint32_t db = desc_lo(base + OFF_K0, 0) + (step & 1) * ((OFF_K1 - OFF_K0) >> 4);
                    wg_fence();
                    wgmma_ss_n128_init<0, 0, 0>(S, da, db);
                    wgmma_ss_n128_tb0<2, 2>(S, da, db, 1);
                    wgmma_ss_n128_tb0<4, 4>(S, da, db, 1);
                    wgmma_ss_n128_tb0<6, 6>(S, da, db, 1);
                    wgmma_ss_n128_tb0<1024, 1024>(S, da, db, 1);
                    wgmma_ss_n128_tb0<1026, 1026>(S, da, db, 1);
                    wgmma_ss_n128_tb0<1028, 1028>(S, da, db, 1);
                    wgmma_ss_n128_tb0<1030, 1030>(S, da, db, 1);
                    wg_commit();
                };
                auto issue_PV = [&](uint32_t t, int pass) INL {
                    const uint32_t db = desc_lo(base + OFF_V0, 16384) + (t & 1) * ((OFF_V1 - OFF_V0) >> 4);
                    mbar_wait_hot(vfull + (t & 1) * 8, (t >> 1) & 1);
                    wg_fence();
                    wgmma_rs_n128_tb1<0>(O, P[0], P[1], P[2], P[3], db, !(starts & 2));
                    wgmma_rs_n128_tb1<128>(O, P[4], P[5], P[6], P[7], db, 1);
                    wgmma_rs_n128_tb1<256>(O, P[8], P[9], P[10], P[11], db, 1);
                    wgmma_rs_n128_tb1<384>(O, P[12], P[13], P[14], P[15], db, 1);
                    if (pass) named_arrive(pass, TURN_THREADS);
                    wgmma_rs_n128_tb1<512>(O, P[16], P[17], P[18], P[19], db, 1);
                    wgmma_rs_n128_tb1<640>(O, P[20], P[21], P[22], P[23], db, 1);
                    wgmma_rs_n128_tb1<768>(O, P[24], P[25], P[26], P[27], db, 1);
                    wgmma_rs_n128_tb1<896>(O, P[28], P[29], P[30], P[31], db, 1);
                    wg_commit();
                };
                auto pv_done = [&](uint32_t t) INL {
                    wg_wait<0>();
                    fence_regs(O);
                    arrive_pair(vempty + (t & 1) * 8, t != ~0u);
                };
                auto row_max = [&](float& a0, float& a1) INL {
                    a0 = fmaxf(S[0], S[1]); a1 = fmaxf(S[2], S[3]);
#pragma unroll
                    for (int j = 1; j < 16; j++) {
                        a0 = fmaxf(a0, fmaxf(S[j * 4], S[j * 4 + 1]));
                        a1 = fmaxf(a1, fmaxf(S[j * 4 + 2], S[j * 4 + 3]));
                    }
                    a0 = fmaxf(a0, __shfl_xor_sync(0xffffffffu, a0, 1));
                    a1 = fmaxf(a1, __shfl_xor_sync(0xffffffffu, a1, 1));
                    a0 = fmaxf(a0, __shfl_xor_sync(0xffffffffu, a0, 2));
                    a1 = fmaxf(a1, __shfl_xor_sync(0xffffffffu, a1, 2));
                };
                auto mask_diag = [&]() INL {
                    const int d = (r0 & 63) - (lane & 3) * 2;
                    auto mask_block = [&](const int J0) INL {
                        bool up0 = false, up1 = false;
#pragma unroll
                        for (int j = 0; j < 8; j++) {
                            const bool c0 = j * 8 > d, c1 = j * 8 + 1 > d;
                            if (c0) S[(J0 + j) * 4] = -INFINITY;
                            if (c1) S[(J0 + j) * 4 + 1] = -INFINITY;
                            if (up0) S[(J0 + j) * 4 + 2] = -INFINITY;
                            if (up1) S[(J0 + j) * 4 + 3] = -INFINITY;
                            up0 = c0; up1 = c1;
                        }
                    };
                    if (w) {
                        mask_block(8);
                    } else {
                        mask_block(0);
#pragma unroll
                        for (int i = 32; i < 64; i++) S[i] = -INFINITY;
                    }
                };
                auto exp_part = [&](float& t0, float& t1, const int J0, const int J1, const bool SUB) INL {
#pragma unroll
                    for (int j = J0; j < J1; j++) {
                        const float e0 = ex2(SUB ? S[j * 4] - m0 : S[j * 4]), e1 = ex2(SUB ? S[j * 4 + 1] - m0 : S[j * 4 + 1]);
                        const float e2 = ex2(SUB ? S[j * 4 + 2] - m1 : S[j * 4 + 2]), e3 = ex2(SUB ? S[j * 4 + 3] - m1 : S[j * 4 + 3]);
                        t0 = (j ? t0 : l0) + (e0 + e1);
                        t1 = (j ? t1 : l1) + (e2 + e3);
                        P[j * 2] = pack_bf16(e0, e1);
                        P[j * 2 + 1] = pack_bf16(e2, e3);
                    }
                };
                auto exp_head = [&](float& t0, float& t1, auto j1_) INL {
                    constexpr int J1 = decltype(j1_)::v;
                    float E[J1 * 4];
#pragma unroll
                    for (int j = 0; j < J1; j++) {
#pragma unroll
                        for (int e = 0; e < 4; e++) E[j * 4 + e] = ex2(S[j * 4 + e]);
                        t0 = (j ? t0 : l0) + (E[j * 4] + E[j * 4 + 1]);
                        t1 = (j ? t1 : l1) + (E[j * 4 + 2] + E[j * 4 + 3]);
                    }
                    order_after(t0 + t1, bars + 508);
                    pv_done(step - 1);
                    fence_regs(P);
                    fence_regs(S);
                    fence_regs(E);
#pragma unroll
                    for (int i = 0; i < J1 * 2; i++) P[i] = pack_bf16(E[i * 2], E[i * 2 + 1]);
                };
                auto close_job = [&]() INL {
                    l0 += __shfl_xor_sync(0xffffffffu, l0, 1); l1 += __shfl_xor_sync(0xffffffffu, l1, 1);
                    l0 += __shfl_xor_sync(0xffffffffu, l0, 2); l1 += __shfl_xor_sync(0xffffffffu, l1, 2);
                    e0 = g0 * rcp(l0); e1 = g1 * rcp(l1);
                };
                auto put_O = [&]() INL {
                    mbar_wait_hot(sempty + (w * 2 + 1) * 8, sph ^ 1);
                    uint32_t a[4];
#pragma unroll
                    for (int j = 0; j < 4; j++) asm volatile("xor.b32 %0, %1, %2;" : "=r"(a[j]) : "r"(slot_a), "r"(j << 5));
                    const uint32_t h0 = pack_bf16(e0, e0), h1 = pack_bf16(e1, e1);
#pragma unroll
                    for (int q = 0; q < 8; q++) {
                        const float* o = O + q * 8;
                        stmatrix_x4(a[q & 3] + (q >> 2) * 8192, mul_bf16x2(pack_bf16(o[0], o[1]), h0), mul_bf16x2(pack_bf16(o[2], o[3]), h1),
                                    mul_bf16x2(pack_bf16(o[4], o[5]), h0), mul_bf16x2(pack_bf16(o[6], o[7]), h1));
                    }
                    sph ^= 1;
                    signal_both();
                };
                auto exp_plain = [&](float& t0, float& t1) INL {
                    exp_head(t0, t1, IC<5>{});
                    exp_part(t0, t1, 5, 16, false);
                    fence_regs(P);
                };
                auto exp_diag = [&](float& t0, float& t1) INL {
                    const int d = warp - 4, dd = (r0 & 7) - (int)(slot_a >> 6 & 6);
                    auto tri = [&](const int B) INL {
                        if (0 > dd) S[8 * B] = S[8 * B + 6] = -INFINITY;
                        if (1 > dd) S[8 * B + 1] = S[8 * B + 7] = -INFINITY;
                        S[8 * B + 4] = S[8 * B + 5] = -INFINITY;
                        asm volatile("" ::: "memory");
                    };
                    auto blocks = [&](const int B) INL {
                        auto zero = [&](const int B0) INL {
#pragma unroll
                            for (int i = 4 * B0; i < 4 * B + 12; i++) P[i] = 0;
                            asm volatile("" ::: "memory");
                        };
                        auto block = [&](const int B0) INL { exp_part(t0, t1, 2 * B0, 2 * B0 + 2, false); asm volatile("" ::: "memory"); };
                        if (d < B) zero(B);
                        else {
                            block(B);
                            if (d < B + 1) zero(B + 1);
                            else {
                                block(B + 1);
                                if (d < B + 2) zero(B + 2); else block(B + 2);
                            }
                        }
                    };
                    if (d > 3) {
                        if (d < 6) { if (d == 4) tri(4); else tri(5); } else { if (d == 6) tri(6); else tri(7); }
                        exp_head(t0, t1, IC<5>{});
                        exp_part(t0, t1, 5, 10, false);
                        blocks(5);
                    } else {
                        if (d < 2) { if (d == 0) tri(0); else tri(1); } else { if (d == 2) tri(2); else tri(3); }
                        exp_head(t0, t1, IC<2>{});
#pragma unroll
                        for (int i = 16; i < 32; i++) P[i] = 0;
                        blocks(1);
                    }
                    fence_regs(P);
                };
                auto unsafe_tile = [&](float t0, float t1, bool fresh) INL -> bool {
                    const bool unsafe = !(t0 + t1 <= sum_max) |
                                        (fresh & ((slot_a & 0x180) == 0) & !(fminf(t0, t1) >= 8.6736174e-19f));
                    return __any_sync(0xffffffffu, unsafe);
                };
                auto redo_tile = [&](float& t0, float& t1, bool fresh) INL {
                    wg_wait<0>();
                    fence_regs(O);
                    if (rem == maskrem) mask_diag();
                    float a0, a1;
                    row_max(a0, a1);
                    if (!fresh) { a0 = fmaxf(a0, m0); a1 = fmaxf(a1, m1); }
                    const float c0 = fresh ? 1.f : ex2(m0 - a0), c1 = fresh ? 1.f : ex2(m1 - a1);
                    m0 = a0; m1 = a1; sum_max = -1.f;
                    l0 *= c0; l1 *= c1;
#pragma unroll
                    for (int j = 0; j < 16; j++) { O[j * 4] *= c0; O[j * 4 + 1] *= c0; O[j * 4 + 2] *= c1; O[j * 4 + 3] *= c1; }
                    exp_part(t0, t1, 0, 16, true);
                };
                auto finish = [&]() INL {
                    if (starts & 2) put_O();
                    named_sync(1 + w, TURN_THREADS);
                    TRACE_MARK(0, w, step + 1);
                    issue_PV(step, w == 0 ? 2 : 0);
                    close_job();
                    pv_done(step);
                    put_O();
                };
                auto open_job = [&]() INL {
                    ajob++; rem = (job & 15) + 1; maskrem = (job & 512) ? 0 : job & 15;
                };
                auto do_step = [&]() INL -> bool {
                    float t0, t1;
                    const bool fresh = starts & 1, pending = starts & 2;
                    rem--; step++;
                    named_sync(1 + w, TURN_THREADS);
                    TRACE_MARK(0, w, step);
                    issue_S();
                    if (__builtin_expect(pending || fresh, 0)) {
                        if (pending) put_O();
                        if (fresh) {
                            close_job();
                            g0 = __ldcg(g_gate + (job & 15) * 128 + r0); g1 = __ldcg(g_gate + (job & 15) * 128 + r0 + 8);
                            l0 = 0.f; l1 = 0.f; m0 = 0.f; m1 = 0.f; sum_max = SUM_MAX;
                            if (step == 0) {
                                wg_fence();
                                wg_commit();
                                named_arrive(2 - w, TURN_THREADS);
                                goto issued;
                            }
                        }
                    }
                    issue_PV(step - 1, 2 - w);
                issued:
                    starts = (starts << 1 & 2) | (rem == 0);
                    TRACE_MARK(1, w, step);
                    wg_wait<1>();
                    fence_regs(S);
                    arrive_pair(kempty + (step & 1) * 8);
                    TRACE_MARK(2, w, step);
                    if (__builtin_expect(rem != maskrem, 1)) {
                        exp_plain(t0, t1);
                        if (__builtin_expect(!unsafe_tile(t0, t1, false) && starts == 0, 1)) {
                            l0 = t0; l1 = t1;
                            TRACE_MARK(3, w, step);
                            return true;
                        }
                    } else {
                        exp_diag(t0, t1);
                    }
                    if (unsafe_tile(t0, t1, fresh)) redo_tile(t0, t1, fresh);
                    l0 = t0; l1 = t1;
                    TRACE_MARK(3, w, step);
                    if (rem == 0) {
                        warp_arrive(qempty + (ajob & 1) * 8);
                        next_job();
                        if ((job >> 12) != T_A) return false;
                        open_job();
                    }
                    return true;
                };
                open_job();
#pragma unroll 1
                while (do_step()) {}
                finish();
            }
        }
        GTRACE(w);
        jb = uniform(jb); job = uniform(job); sph = uniform(sph); gph = uniform(gph);
        if (job < 0) break;
        }
    } else {
        reg_dec<40>();
        if (base & 1023) __trap();
        if (warp == 0) {
            const uint2 r = p.first[blockIdx.x];
            const char* maps = reinterpret_cast<const char*>(&p.amap[0]);
            const CUtensorMap* wm = reinterpret_cast<const CUtensorMap*>(maps + (r.x >> (rank ? 8 : 4) & 0x780));
            const CUtensorMap* am = reinterpret_cast<const CUtensorMap*>(maps + (r.x & 0x780));
            const int wb = rank ? r.y >> 16 : r.y & 0xffff;
            setup_wait();
#pragma unroll 1
            for (int st = 1; st < 4; st++) {
                const uint32_t sa = base + st * G_STAGE;
                load_kstep(sa, sa + 16384 + rank * 16384, gfull + st * 8, G_STAGE, wm, st, wb, am, r.x >> 20, st, 1 + (r.x & 1));
            }
            named_sync(7, 96);
        } else {
            if (warp == 2) {
                const int jl = lane < MAX_JOBS ? p.jobs[blockIdx.x][lane] : -1;
                if (lane <= MAX_JOBS) jobs[lane] = jl;
                if ((jl >> 12) == T_O) *reinterpret_cast<volatile uint32_t*>(smem_raw + OFF_BAR + 504) = 2 * o_head(jl);
                if (lane == 31) *reinterpret_cast<volatile uint32_t*>(smem_raw + OFF_BAR + 528) = 0;
            } else if (warp == 3) {
                if (lane == 31) *reinterpret_cast<ulonglong2*>(smem_raw + OFF_BAR + 512) = make_ulonglong2((uint64_t)g_halo, (uint64_t)g_gate);
                if (lane < MAX_ROUNDS / 2) rounds[lane] = reinterpret_cast<const uint32_t*>(p.rounds[blockIdx.x >> 1])[lane];
            }
            named_arrive_if(warp > 1, 7, 96);
            named_sync(0, 352);
            setup_wait();
        }
        volatile uint32_t* epoch_word = reinterpret_cast<volatile uint32_t*>(smem_raw + OFF_BAR + 532);
        uint32_t epoch1 = 0;
        if (warp > 0) {
        if (warp == 3) { epoch1 = uniform(ld_acquire(g_flags + F_DONE)) / NUM_SMS + 1; if (lane == 0) *epoch_word = epoch1; }
        {
            if (warp == 1 && elect_one()) {
#pragma unroll
                for (int i = 0; i < 7; i++) prefetch_map(&p.amap[0] + i);
            }
            __syncwarp();
            if (warp < 3) __nanosleep(jobs[0] < 256 ? GATE_DELAY_LONG_NS : GATE_DELAY_SHORT_NS);
            if (tid == TRACE_GATE) PTRACE(10);
            float* gate_vals = reinterpret_cast<float*>(smem_raw + OFF_BAR + 576);
            if (warp == 3) {
                if (blockIdx.x == 0) g_flags[F_SPLIT + lane] = g_flags[F_TICKET + lane] = 0;
                named_sync(5, 96);
                if (lane < 16 && blockIdx.x + lane * NUM_SMS < SEQ) g_gate[blockIdx.x + lane * NUM_SMS] = 1.f / (1.f + __expf(-gate_vals[lane]));
                if (tid == TRACE_GATE) PTRACE(9);
                __threadfence();
                __syncwarp();
                if (lane == 0) red_release(g_flags + F_GATE);
            } else {
                const uint32_t bar = gatefull + (warp - 1) * 16;
                auto fetch = [&](int r) INL {
                    if (lane == 0) mbar_expect_tx(bar + (r & 2) * 4, 4096);
                    __syncwarp();
                    if (lane < 2) asm volatile("cp.async.bulk.shared::cluster.global.mbarrier::complete_tx::bytes [%0], [%1], 2048, [%2];"
                                               ::"r"(stg + ((warp - 1) * 8 + r + lane) * 2048), "l"(p.xp + (size_t)min((int)blockIdx.x + ((warp - 1) * 8 + r + lane) * NUM_SMS, SEQ - 1) * DM), "r"(bar + (r & 2) * 4) : "memory");
                };
                fetch(0); fetch(2);
                uint32_t gw[16];
#pragma unroll
                for (int i = 0; i < 4; i++) {
                    const uint4 t = __ldg(reinterpret_cast<const uint4*>(p.gate_w) + i * 32 + lane);
                    gw[i * 4] = t.x; gw[i * 4 + 1] = t.y; gw[i * 4 + 2] = t.z; gw[i * 4 + 3] = t.w;
                }
#pragma unroll 1
                for (int r = 0; r < 8; r += 2) {
                    mbar_wait(bar + (r & 2) * 4, r >> 2);
                    if (r < 4) fetch(r + 4);
                    fence_regs(gw);
                    float acc0 = 0.f, acc1 = 0.f;
                    uint32_t ln;
                    asm volatile("mov.u32 %0, %%laneid;" : "=r"(ln));
#pragma unroll
                    for (int i = 0; i < 4; i++) {
                        const uint4* xr = reinterpret_cast<const uint4*>(smem_raw + OFF_STG + ((warp - 1) * 8 + r) * 2048) + i * 32 + ln;
                        const uint4 a = xr[0], c = xr[128];
                        const uint32_t av[4] = {a.x, a.y, a.z, a.w}, cv[4] = {c.x, c.y, c.z, c.w};
#pragma unroll
                        for (int e = 0; e < 4; e++) {
                            const float lo = __uint_as_float(gw[i * 4 + e] << 16), hi = __uint_as_float(gw[i * 4 + e] & 0xffff0000u);
                            acc0 = fmaf(__uint_as_float(av[e] << 16), lo, acc0);
                            acc1 = fmaf(__uint_as_float(cv[e] << 16), lo, acc1);
                            acc0 = fmaf(__uint_as_float(av[e] & 0xffff0000u), hi, acc0);
                            acc1 = fmaf(__uint_as_float(cv[e] & 0xffff0000u), hi, acc1);
                        }
                    }
                    float t = (lane < 16 ? acc0 : acc1) + __shfl_xor_sync(0xffffffffu, lane < 16 ? acc1 : acc0, 16);
#pragma unroll
                    for (int o = 8; o > 0; o >>= 1) t += __shfl_xor_sync(0xffffffffu, t, o);
                    if ((lane & 15) == 0) gate_vals[(warp - 1) * 8 + r + (lane >> 4)] = t;
                }
                uint32_t t2;
                asm volatile("mov.u32 %0, %%tid.x;" : "=r"(t2));
                warp_arrive2(sempty - 16 + (t2 >> 5) * 16, sempty - 8 + (t2 >> 5) * 16);
                named_arrive(5, 96);
                if (tid == TRACE_GATE) PTRACE(9);
            }
            if (tid == TRACE_GATE) PTRACE(8);
        }
        if (warp < 3) {
            if (elect_one()) {
                const int w = warp - 1;
                uint32_t qn = 0, un = 0;
                prefetch_map(&p.qkv_st); prefetch_map(&p.st_par);
                for (int jb = 0; jb < MAX_JOBS; jb++) {
                    const int job = jobs[jb];
                    if (job < 0) break;
                    const int type = job >> 12, pl = type == T_O ? o_state(otile, 0) >> 1 : job & 0xFFF;
                    const CUtensorMap* map = &p.qkv_st;
                    int nq = 4, mt, ob0, ob1, flag, flag2 = -1;
                    bool par = false;
                    if (type <= T_O) {
                        const int n = pl >> 3;
                        mt = (pl & 7) * 2 + rank;
                        if (type == T_O)  {
                            map = &p.out_st; ob0 = (n & 3) * 4; ob1 = ob0 + 2; flag = -1;
                            for (uint32_t tries = 0; (int32_t)(ld_acquire(g_flags + F_OUT + pl * 2 + rank) - *epoch_word) < 0; tries++) {
                                __nanosleep(300);
                                if (tries > (1u << 22)) __trap();
                            }
                            fence_async_global();
                        }
                        else if (n < 16)  { ob0 = n * 4; ob1 = ob0 + 2; flag = F_Q + n * 32 + mt; flag2 = flag + 16; }
                        else if (n < 24)  {
                            mbar_wait(hout + w * 8, un++ & 1);
                            nq = ob0 = ob1 = 0; flag = F_H + mt * 8 + (n & 7);
                        } else if (n < 32) {
                            par = true; ob0 = 192 + (n & 7) * 2; ob1 = unit_head(n & 7) * 2;
                            flag = F_CTX + mt * 40 + 32 + (n & 7); flag2 = F_Q + ob1 * 8 + mt;
                        } else            { ob0 = n * 2; ob1 = ob0 + 64; flag = F_KV + (n - 32) * 16 + mt; }
                    } else {
                        nq = 2; mt = pl & 15; ob0 = ob1 = ((pl >> 4) & 31) * 2; flag = F_CTX + mt * 40 + ((pl >> 4) & 31);
                    }
                    for (int q = 0; q < nq; q++, qn++) {
                        const uint32_t slot = w * 2 + (qn & 1);
                        const int blk = (q < 2 ? ob0 : ob1) + (q & 1);
                        if (type == T_O && q == 2) {
                            mbar_wait(tfull + w * 8, 0);
                            fence_async_smem();
                            tma_reduce_add_3d(map, base + w * 8192, 0, mt * 128 + w * 64, ob1);
                            tma_reduce_add_3d(map, base + G_STAGE + w * 8192, 0, mt * 128 + w * 64, ob1 + 1);
                            bulk_commit();
                            break;
                        }
                        mbar_wait(sfull + slot * 8, (qn >> 1) & 1);
                        fence_async_smem();
                        if (type == T_O) {
                            tma_reduce_add_3d(map, stg + slot * 8192, 0, mt * 128 + w * 64, blk);
                        } else if (par) {
                            tma_store_par(&p.st_par, stg + slot * 8192, mt * 64, w, blk);
                        } else {
                            tma_store_3d(map, stg + slot * 8192, 0, mt * 128 + w * 64, blk, POL_STREAM);
                        }
                        bulk_commit();
                        if (type == T_O) continue;
                        if (!(q & 1)) continue;
                        bulk_wait_read<1>();
                        mbar_arrive(sempty + (slot ^ 1) * 8);
                        bulk_wait_read<0>();
                        mbar_arrive(sempty + slot * 8);
                    }
                    bulk_wait<0>();
                    END_MARK(jb);
                    if (flag >= 0) {
                        asm volatile("fence.release.gpu;" ::: "memory");
                        red_relaxed(g_flags + flag);
                        if (flag2 >= 0) red_relaxed(g_flags + flag2);
                    }
                }
            }
        } else {
            int jb = 0;
            for (int un = 0; (jobs[jb] >> 12) == T_P; jb++) {
                const int n = jobs[jb] >> 3, mt = (jobs[jb] & 7) * 2 + rank;
                if ((n >> 3) != 3) continue;
                wait_flags<200>(lane == 31 || (lane == 0 && mt > 0), lane == 31 ? F_GATE : F_H + max(mt - 1, 0) * 8 + (n & 7),
                                epoch1 * (lane == 31 ? GATE_COUNT : 2));
                if (lane == 0) mbar_arrive(lready + un * 8);
                un++;
            }
            if ((jobs[jb] >> 12) != T_A) {
                wait_flags<200>(lane == 0, F_GATE, epoch1 * GATE_COUNT);
                if (lane == 0) { mbar_arrive(aready); red_relaxed(g_flags + F_DONE); }
            } else {
                const int jh = jobs[jb] >> 4 & 31, jq = jobs[jb] & 15;
                wait_flags<100>(lane <= jq || lane >= 30, lane == 31 ? F_GATE : (lane == 30 ? F_Q + jh * 16 + jq : F_KV + jh * 16 + (lane & 15)),
                                epoch1 * (lane == 31 ? GATE_COUNT : 2));
                if (lane == 0) { mbar_arrive(aready); red_relaxed(g_flags + F_DONE); }
            int left = 0, nxt = jobs[jb];
            uint32_t ajob = 0;
#pragma unroll 1
            for (uint32_t astep = 0;; astep++) {
                if (left == 0) {
                    if ((nxt >> 12) != T_A) break;
                    left = (nxt & 15) + 1;
                    nxt = jobs[++jb];
                    mbar_wait(qfull + (ajob & 1) * 8, (ajob >> 1) & 1);
                    ajob++;
                }
                left--;
                mbar_wait(kfull + (astep & 1) * 8, (astep >> 1) & 1);
                named_sync(1, TURN_THREADS);
                named_sync(2, TURN_THREADS);
            }
            named_sync(1, TURN_THREADS);
            named_sync(2, TURN_THREADS);
            }
            if (jobs[jb] == (T_O << 12)) {
                mbar_wait(gatefull, 0);
                const int tile = o_state(otile, 0) >> 1;
                uint4* dst = reinterpret_cast<uint4*>(p.out) + ((tile & 7) * 256 + rank * 128) * (DM / 8) + (tile >> 3) * 32 + lane;
#pragma unroll 4
                for (int r = 0; r < 128; r++) {
                    dst[r * (DM / 8)] = make_uint4(0, 0, 0, 0);
                    if ((r & 3) == 3) __nanosleep(CLEAR_GAP_NS);
                }
                __threadfence();
                fence_async_global();
                __syncwarp();
                if (lane == 0) red_release(g_flags + F_OUT + tile * 2 + rank);
            }
        }
        } else {
            uint32_t gph = 1;
            int vrow = 0, vblk = 0;
            bool vsolo = false;
            auto load_kv = [&](uint32_t dst, uint32_t bar, int row, int blk, bool solo) INL {
                load_operand(dst, bar, &p.qkv_ld, &p.qkv_half, row, blk, rank, solo, POL_NORMAL);
            };
            auto load_v = [&](uint32_t t) INL {
                if (t == 0) mbar_wait(gempty + 24, gph);
                mbar_wait(vempty + (t & 1) * 8, ((t >> 1) & 1) ^ 1);
                load_kv(base + ((t & 1) ? OFF_V1 : OFF_V0), vfull + (t & 1) * 8, vrow, vblk, vsolo);
            };
            int jb = __ffs(__ballot_sync(0xffffffffu, lane <= MAX_JOBS && (jobs[min(lane, MAX_JOBS)] >> 12) != T_P)) - 1;
            int cur = uniform(jobs[jb]);
            auto announce = [&](uint32_t word, uint32_t v) INL {
                asm volatile("{\n.reg .pred p;\nsetp.lt.u32 p, %2, 2;\n@p red.relaxed.cluster.shared::cluster.max.u32 [%0], %1;\n}"
                             ::"r"(mapa(word, lane & 1)), "r"(v), "r"(lane) : "memory");
                __syncwarp();
            };
            uint32_t ticket = 0;
            auto draw_ticket = [&](int ojob) INL {
                asm volatile("{\n.reg .pred p;\nsetp.ne.u32 p, %2, 0;\n@p atom.relaxed.gpu.global.inc.u32 %0, [%1], 0x7fffffff;\n}"
                             : "+r"(ticket) : "l"(g_flags + F_TICKET + (ojob >> 5 & 1)), "r"((uint32_t)(rank == 0 && lane == 0)) : "memory");
                __syncwarp();
            };
            int pl = 0;
            uint32_t seen_a = 0, seen_b = 0;
            auto ask_ctx = [&]() INL {
                const uint32_t* f = g_flags + F_CTX + ((pl & 7) * 2 + rank) * 40;
                seen_a = ld_relaxed(f + lane); seen_b = ld_relaxed(f + 32 + (lane & 7));
            };
            auto open_tile = [&](int ojob) INL {
                if (rank == 0) {
                    const uint32_t t = uniform(ticket);
                    announce(otile, 2 * ((ojob & 32) ? 31 - t : t) + 1);
                }
                pl = (ojob & 32) | uniform(o_state(otile, 0) >> 1);
                ask_ctx();
            };
            const uint16_t* recs = reinterpret_cast<const uint16_t*>(rounds);
            uint32_t rec = uniform(recs[0]), nrec = uniform(recs[1]);
            int st0 = 4;
#pragma unroll 1
            for (int r = 2; rec != 0xFFFF; r++) {
                const uint32_t nnrec = recs[r];
                load_round(rec, st0, gph);
                gph ^= 1;
                st0 = 0;
                rec = nrec; nrec = uniform(nnrec);
                if (nrec == 0xFFFF || (rec & 8192)) {
                    if (nrec != 0xFFFF) {
                        prefetch_map(&p.qkv_ld); prefetch_map(&p.qkv_half);
                        if ((cur >> 12) == T_O) { prefetch_map(&p.wo_a); prefetch_map(&p.wo_b); prefetch_map(&p.out_st); }
                    } else if ((cur >> 12) == T_O) {
                        if (rec != 0xFFFF) {
                            mbar_wait(aready, 0);
                            draw_ticket(cur);
                        } else {
                            open_tile(cur);
                        }
                    }
                }
            }
            int nxt = cur;
            uint32_t astep = 0;
            if ((cur >> 12) == T_A) {
            {
                const int jh = cur >> 4 & 31, jq = cur & 15, j0 = (cur & 512) ? 0 : jq;
                mbar_wait(aready, 0);
                fence_async_global();
                mbar_wait(gempty, gph);
                load_operand(base + OFF_Q0, qfull, &p.qkv_ld, &p.qkv_ld, jq * 128, jh * 2, 0, true, POL_STREAM);
                PTRACE(17);
                mbar_wait(gempty + 8, gph);
                load_kv(base + OFF_K0, kfull, j0 * 128, 64 + jh * 2, j0 == jq && (jq & 1));
                PTRACE(16);
            }
            epoch1 = *epoch_word;
            jb++;
            nxt = uniform(jobs[jb]);
            int i = 0;
            uint32_t ajob = 1;
            bool q_issued = false;
#pragma unroll 1
            while (true) {
                const int qt = cur & 15;
                const bool last = i == qt;
                const int j = (cur & 512) ? i : qt - i, blk = (cur >> 4 & 31) * 2;
                const bool solo = j == qt && (qt & 1);
                {
                    const uint32_t sl = astep & 1;
                    if (astep == 0) {
                        mbar_wait(gempty + 16, gph);
                    } else {
                        mbar_wait(kempty + sl * 8, ((astep >> 1) & 1) ^ 1);
                        load_kv(base + (sl ? OFF_K1 : OFF_K0), kfull + sl * 8, j * 128, 64 + blk, solo);
                        if (astep == 1) PTRACE(14);
                        load_v(astep - 1);
                        if (astep == 1) PTRACE(15);
                    }
                }
                vrow = j * 128; vblk = 128 + blk; vsolo = solo;
                astep++;
                if ((nxt >> 12) != T_A) {
                    if (last) break;
                } else if (!q_issued && (last || i == 2 || (i > 2 && i >= qt - 2))) {
                    const int jh = nxt >> 4 & 31, jq = nxt & 15;
                    q_issued = wait_flags(lane <= jq || lane >= 30, lane == 31 ? F_GATE : (lane == 30 ? F_Q + jh * 16 + jq : F_KV + jh * 16 + (lane & 15)),
                                          epoch1 * (lane == 31 ? GATE_COUNT : 2), last);
                    if (q_issued) {
                        mbar_wait(qempty + (ajob & 1) * 8, ((ajob >> 1) & 1) ^ 1);
                        load_operand(base + ((ajob & 1) ? OFF_Q1 : OFF_Q0), qfull + (ajob & 1) * 8, &p.qkv_ld, &p.qkv_ld, jq * 128, jh * 2, 0, true, POL_STREAM);
                    }
                }
                i++;
                if (last) {
                    cur = nxt; jb++; nxt = uniform(jobs[jb]); i = 0; ajob++; q_issued = false;
                    if ((nxt >> 12) == T_O) { prefetch_map(&p.wo_a); prefetch_map(&p.wo_b); prefetch_map(&p.out_st); }
                }
            }
            if (nxt >= 0) draw_ticket(nxt);
            load_v(astep - 1);
            if (nxt >= 0) open_tile(nxt);
            }
            int nks = 0;
            if (nxt >= 0) {
                epoch1 = *epoch_word;
                const int m0 = (pl & 7) * 256 + rank * 128, nb = (pl >> 3 & 3) * 4 + rank * 2, part = pl >> 5 & 1;
                uint32_t ready_a = 0, ready_b = 0;
                uint32_t claim_even = 0, claim_odd = 0;
                const int head = o_head(pl), tail = o_tail(pl);
                int lim = head;
                bool known = false;
#pragma unroll 1
                for (int ks = 0;; ks++) {
                    const int st = ks & 3;
                    if (rank == 0) {
                        auto exchange = [&](uint32_t& claim) INL {
                            if (ks + 1 >= head) {
                                known = (uint32_t)uniform(claim) >= O_FLEX;
                                if (!known) lim = ks + 2;
                                announce(olim, known ? 2 * (lim + tail) + 1 : 2 * lim);
                            }
                            asm volatile("{\n.reg .pred p;\nsetp.ne.u32 p, %2, 0;\n@p atom.relaxed.gpu.global.inc.u32 %0, [%1], 0x7fffffff;\n}"
                                         : "+r"(claim) : "l"(g_flags + F_SPLIT + (pl & 31)), "r"((uint32_t)(!known && lane == 0)) : "memory");
                            __syncwarp();
                        };
                        if (!known && ks + 3 >= head) { if (ks & 1) exchange(claim_odd); else exchange(claim_even); }
                    } else if (!known && ks >= lim) {
                        const uint32_t v = uniform(o_state(olim, ks));
                        known = v & 1;
                        lim = (v >> 1) - (known ? tail : 0);
                    }
                    if (ks >= lim + tail) { nks = ks; break; }
                    if (ks == CLEAR_KS && !part) warp_arrive(gatefull);
                    int acol;
                    if (ks >= lim) acol = (part ? 64 - O_T1 : 200) + ks - lim;
                    else if (part) acol = ks < O_H1 ? O_F0 + ks : O_F0 + 2 * O_H1 + O_FLEX - 1 - ks;
                    else acol = ks < 8 ? 192 + ks : (ks < O_H0 ? ks - 8 : ks - 8 + O_H1);
                    for (uint32_t tries = 0; !(((acol < 192 ? ready_a : ready_b) >> (acol >> 1 & 31)) & 1); tries++) {
                        if (ks | tries) ask_ctx();
                        ready_a = __ballot_sync(0xffffffffu, (int32_t)(seen_a - epoch1 * 2) >= 0);
                        ready_b = __ballot_sync(0xffffffffu, (int32_t)(seen_b - epoch1 * 2) >= 0);
                        fence_acquire();
                        trap_if(tries > (1u << 22));
                    }
                    {
                        const uint32_t sa = base + st * G_STAGE;
                        if (ks < 4 && astep) mbar_wait((ks < 2 ? kempty : vempty) + ((astep - 1) & 1) * 8, ((astep - 1) >> 1) & 1);
                        else mbar_wait(gempty + st * 8, gph);
                        load_kstep(sa, sa + 16384 + rank * 16384, gfull + st * 8, G_STAGE, acol >= 192 ? &p.wo_b : &p.wo_a, acol & 63, nb,
                                   &p.qkv_half, m0, acol, 1);
                    }
                    if (st == 3) gph ^= 1;
                }
            }
            if (lane == 0) {
                if (nxt >= 0) for (int s = 0; s < 4; s++) mbar_wait(gempty + s * 8, gph ^ (s < (nks & 3)));
                else for (uint32_t t = astep; t < astep + 2; t++) {
                    mbar_wait(kempty + (t & 1) * 8, ((t >> 1) & 1) ^ 1);
                    mbar_wait(vempty + (t & 1) * 8, ((t >> 1) & 1) ^ 1);
                }
            }
        }
    }
}

typedef CUresult (*EncodeFn)(CUtensorMap*, CUtensorMapDataType, cuuint32_t, void*, const cuuint64_t*, const cuuint64_t*,
                             const cuuint32_t*, const cuuint32_t*, CUtensorMapInterleave, CUtensorMapSwizzle,
                             CUtensorMapL2promotion, CUtensorMapFloatOOBfill);

void make_map3(EncodeFn enc, CUtensorMap* m, const void* ptr, int rows, int cols, int box_rows, int box_blks, bool blocked = false) {
    cuuint64_t dims[3] = {64, (cuuint64_t)rows, (cuuint64_t)(cols / 64)};
    cuuint64_t strides[2] = {blocked ? 128 : (cuuint64_t)cols * 2, blocked ? (cuuint64_t)rows * 128 : 128};
    cuuint32_t box[3] = {64, (cuuint32_t)box_rows, (cuuint32_t)box_blks};
    cuuint32_t es[3] = {1, 1, 1};
    enc(m, CU_TENSOR_MAP_DATA_TYPE_BFLOAT16, 3, const_cast<void*>(ptr), dims, strides, box, es, CU_TENSOR_MAP_INTERLEAVE_NONE,
        CU_TENSOR_MAP_SWIZZLE_128B, CU_TENSOR_MAP_L2_PROMOTION_L2_256B, CU_TENSOR_MAP_FLOAT_OOB_FILL_NONE);
}

Params h_params;

const int16_t k_jobs[NUM_SMS][MAX_JOBS] = {
    {339,153,217,8890,8339,8802,8311,9042,8405,9008,8551,9134,8677,4128,-1,-1,-1,-1,-1,-1,-1,-1,-1,-1},
    {339,153,217,8891,8338,8803,8310,9043,8404,9009,8550,9135,8676,4128,-1,-1,-1,-1,-1,-1,-1,-1,-1,-1},
    {40,0,307,8888,8289,8720,8259,8854,8539,8898,8627,8998,8655,4128,-1,-1,-1,-1,-1,-1,-1,-1,-1,-1},
    {40,0,307,8889,8288,8721,8258,8855,8538,8899,8626,8999,8654,4128,-1,-1,-1,-1,-1,-1,-1,-1,-1,-1},
    {10,157,221,8706,8269,8820,8457,9006,8687,4128,-1,-1,-1,-1,-1,-1,-1,-1,-1,-1,-1,-1,-1,-1},
    {10,157,221,8707,8268,8821,8456,9007,8686,4128,-1,-1,-1,-1,-1,-1,-1,-1,-1,-1,-1,-1,-1,-1},
    {132,196,296,8730,8333,8940,8503,9082,8697,4128,-1,-1,-1,-1,-1,-1,-1,-1,-1,-1,-1,-1,-1,-1},
    {132,196,296,8731,8332,8941,8502,9083,8696,4128,-1,-1,-1,-1,-1,-1,-1,-1,-1,-1,-1,-1,-1,-1},
    {128,192,8758,8199,8774,8313,9026,8415,9130,8663,4128,-1,-1,-1,-1,-1,-1,-1,-1,-1,-1,-1,-1,-1},
    {128,192,8759,8198,8775,8312,9027,8414,9131,8662,4128,-1,-1,-1,-1,-1,-1,-1,-1,-1,-1,-1,-1,-1},
    {133,197,8742,8369,8704,8285,8768,8543,9022,8601,4128,-1,-1,-1,-1,-1,-1,-1,-1,-1,-1,-1,-1,-1},
    {133,197,8743,8368,8705,8284,8769,8542,9023,8600,4128,-1,-1,-1,-1,-1,-1,-1,-1,-1,-1,-1,-1,-1},
    {131,195,38,8708,8265,8932,8461,8896,8631,9076,8585,4128,-1,-1,-1,-1,-1,-1,-1,-1,-1,-1,-1,-1},
    {131,195,38,8709,8264,8933,8460,8897,8630,9077,8584,4128,-1,-1,-1,-1,-1,-1,-1,-1,-1,-1,-1,-1},
    {137,201,8750,8331,8816,8533,8912,8411,9078,8671,4128,-1,-1,-1,-1,-1,-1,-1,-1,-1,-1,-1,-1,-1},
    {137,201,8751,8330,8817,8532,8913,8410,9079,8670,4128,-1,-1,-1,-1,-1,-1,-1,-1,-1,-1,-1,-1,-1},
    {43,264,440,8744,8201,8858,8417,8954,8483,9016,8649,9152,8691,4128,-1,-1,-1,-1,-1,-1,-1,-1,-1,-1},
    {43,264,440,8745,8200,8859,8416,8955,8482,9017,8648,9153,8690,4128,-1,-1,-1,-1,-1,-1,-1,-1,-1,-1},
    {151,215,8876,8299,8964,8445,9146,8703,4128,-1,-1,-1,-1,-1,-1,-1,-1,-1,-1,-1,-1,-1,-1,-1},
    {151,215,8877,8298,8965,8444,9147,8702,4128,-1,-1,-1,-1,-1,-1,-1,-1,-1,-1,-1,-1,-1,-1,-1},
    {470,5,159,223,8772,8281,8936,8407,9066,8651,4128,-1,-1,-1,-1,-1,-1,-1,-1,-1,-1,-1,-1,-1},
    {470,5,159,223,8773,8280,8937,8406,9067,8650,4128,-1,-1,-1,-1,-1,-1,-1,-1,-1,-1,-1,-1,-1},
    {136,200,444,8760,8275,8848,8477,9040,8525,9148,8681,4128,-1,-1,-1,-1,-1,-1,-1,-1,-1,-1,-1,-1},
    {136,200,444,8761,8274,8849,8476,9041,8524,9149,8680,4128,-1,-1,-1,-1,-1,-1,-1,-1,-1,-1,-1,-1},
    {46,510,462,310,8764,8293,8862,8439,9064,8653,4128,-1,-1,-1,-1,-1,-1,-1,-1,-1,-1,-1,-1,-1},
    {46,510,462,310,8765,8292,8863,8438,9065,8652,4128,-1,-1,-1,-1,-1,-1,-1,-1,-1,-1,-1,-1,-1},
    {145,209,8894,8335,8942,8485,9098,8695,4128,-1,-1,-1,-1,-1,-1,-1,-1,-1,-1,-1,-1,-1,-1,-1},
    {145,209,8895,8334,8943,8484,9099,8694,4128,-1,-1,-1,-1,-1,-1,-1,-1,-1,-1,-1,-1,-1,-1,-1},
    {140,204,8878,8329,8934,8441,9070,8685,4128,-1,-1,-1,-1,-1,-1,-1,-1,-1,-1,-1,-1,-1,-1,-1},
    {140,204,8879,8328,8935,8440,9071,8684,4128,-1,-1,-1,-1,-1,-1,-1,-1,-1,-1,-1,-1,-1,-1,-1},
    {146,210,504,8884,8301,8966,8527,9128,8603,4128,-1,-1,-1,-1,-1,-1,-1,-1,-1,-1,-1,-1,-1,-1},
    {146,210,504,8885,8300,8967,8526,9129,8602,4128,-1,-1,-1,-1,-1,-1,-1,-1,-1,-1,-1,-1,-1,-1},
    {14,6,8868,8245,8806,8267,8938,8547,9000,8611,9108,8643,4128,-1,-1,-1,-1,-1,-1,-1,-1,-1,-1,-1},
    {14,6,8869,8244,8807,8266,8939,8546,9001,8610,9109,8642,4128,-1,-1,-1,-1,-1,-1,-1,-1,-1,-1,-1},
    {144,208,8748,8211,8836,8463,9004,8591,4128,-1,-1,-1,-1,-1,-1,-1,-1,-1,-1,-1,-1,-1,-1,-1},
    {144,208,8749,8210,8837,8462,9005,8590,4128,-1,-1,-1,-1,-1,-1,-1,-1,-1,-1,-1,-1,-1,-1,-1},
    {12,4,8740,8243,8724,8287,8930,8435,8900,8517,9086,8659,4128,-1,-1,-1,-1,-1,-1,-1,-1,-1,-1,-1},
    {12,4,8741,8242,8725,8286,8931,8434,8901,8516,9087,8658,4128,-1,-1,-1,-1,-1,-1,-1,-1,-1,-1,-1},
    {143,207,8866,8353,8752,8205,8830,8409,9056,8561,9140,8581,9104,8679,4128,-1,-1,-1,-1,-1,-1,-1,-1,-1},
    {143,207,8867,8352,8753,8204,8831,8408,9057,8560,9141,8580,9105,8678,4128,-1,-1,-1,-1,-1,-1,-1,-1,-1},
    {147,211,8872,8297,8834,8459,9030,8437,9100,8665,4128,-1,-1,-1,-1,-1,-1,-1,-1,-1,-1,-1,-1,-1},
    {147,211,8873,8296,8835,8458,9031,8436,9101,8664,4128,-1,-1,-1,-1,-1,-1,-1,-1,-1,-1,-1,-1,-1},
    {41,1,8766,8327,8828,8399,9126,8667,4128,-1,-1,-1,-1,-1,-1,-1,-1,-1,-1,-1,-1,-1,-1,-1},
    {41,1,8767,8326,8829,8398,9127,8666,4128,-1,-1,-1,-1,-1,-1,-1,-1,-1,-1,-1,-1,-1,-1,-1},
    {150,214,8882,8223,8832,8473,8980,8413,9094,8669,4128,-1,-1,-1,-1,-1,-1,-1,-1,-1,-1,-1,-1,-1},
    {150,214,8883,8222,8833,8472,8981,8412,9095,8668,4128,-1,-1,-1,-1,-1,-1,-1,-1,-1,-1,-1,-1,-1},
    {141,205,33,8726,8341,8976,8479,9024,8449,9136,8501,9144,8683,4128,-1,-1,-1,-1,-1,-1,-1,-1,-1,-1},
    {141,205,33,8727,8340,8977,8478,9025,8448,9137,8500,9145,8682,4128,-1,-1,-1,-1,-1,-1,-1,-1,-1,-1},
    {277,405,152,216,8718,8475,8902,8403,9150,8661,4128,-1,-1,-1,-1,-1,-1,-1,-1,-1,-1,-1,-1,-1},
    {277,405,152,216,8719,8474,8903,8402,9151,8660,4128,-1,-1,-1,-1,-1,-1,-1,-1,-1,-1,-1,-1,-1},
    {139,203,8886,8203,8856,8433,9032,8393,9080,8599,4128,-1,-1,-1,-1,-1,-1,-1,-1,-1,-1,-1,-1,-1},
    {139,203,8887,8202,8857,8432,9033,8392,9081,8598,4128,-1,-1,-1,-1,-1,-1,-1,-1,-1,-1,-1,-1,-1},
    {149,213,8746,8303,8982,8397,9084,8645,4128,-1,-1,-1,-1,-1,-1,-1,-1,-1,-1,-1,-1,-1,-1,-1},
    {149,213,8747,8302,8983,8396,9085,8644,4128,-1,-1,-1,-1,-1,-1,-1,-1,-1,-1,-1,-1,-1,-1,-1},
    {138,202,8870,8221,8860,8395,9060,8607,4128,-1,-1,-1,-1,-1,-1,-1,-1,-1,-1,-1,-1,-1,-1,-1},
    {138,202,8871,8220,8861,8394,9061,8606,4128,-1,-1,-1,-1,-1,-1,-1,-1,-1,-1,-1,-1,-1,-1,-1},
    {134,198,8738,8225,8728,8283,8962,8541,8992,8499,9074,8609,9124,8595,9184,8693,4128,-1,-1,-1,-1,-1,-1,-1},
    {134,198,8739,8224,8729,8282,8963,8540,8993,8498,9075,8608,9125,8594,9185,8692,4128,-1,-1,-1,-1,-1,-1,-1},
    {142,206,8874,8271,8818,8447,9068,8647,4128,-1,-1,-1,-1,-1,-1,-1,-1,-1,-1,-1,-1,-1,-1,-1},
    {142,206,8875,8270,8819,8446,9069,8646,4128,-1,-1,-1,-1,-1,-1,-1,-1,-1,-1,-1,-1,-1,-1,-1},
    {47,498,506,306,8892,8277,8784,8467,9048,8535,9020,8579,9088,8657,9186,8689,4128,-1,-1,-1,-1,-1,-1,-1},
    {47,498,506,306,8893,8276,8785,8466,9049,8534,9021,8578,9089,8656,9187,8688,4128,-1,-1,-1,-1,-1,-1,-1},
    {148,212,8762,8279,8826,8523,9002,8605,4128,-1,-1,-1,-1,-1,-1,-1,-1,-1,-1,-1,-1,-1,-1,-1},
    {148,212,8763,8278,8827,8522,9003,8604,4128,-1,-1,-1,-1,-1,-1,-1,-1,-1,-1,-1,-1,-1,-1,-1},
    {276,404,268,500,450,490,374,390,430,380,356,412,168,232,9018,8701,-1,-1,-1,-1,-1,-1,-1,-1},
    {276,404,268,500,450,490,374,390,430,380,356,412,168,232,9019,8700,-1,-1,-1,-1,-1,-1,-1,-1},
    {11,403,459,507,329,393,369,377,417,361,433,167,231,9132,8699,-1,-1,-1,-1,-1,-1,-1,-1,-1},
    {11,403,459,507,329,393,369,377,417,361,433,167,231,9133,8698,-1,-1,-1,-1,-1,-1,-1,-1,-1},
    {350,486,502,262,302,334,318,87,52,100,179,243,4096,-1,-1,-1,-1,-1,-1,-1,-1,-1,-1,-1},
    {350,486,502,262,302,334,318,87,52,100,179,243,4096,-1,-1,-1,-1,-1,-1,-1,-1,-1,-1,-1},
    {340,158,222,492,60,108,76,172,236,4096,-1,-1,-1,-1,-1,-1,-1,-1,-1,-1,-1,-1,-1,-1},
    {340,158,222,492,60,108,76,172,236,4096,-1,-1,-1,-1,-1,-1,-1,-1,-1,-1,-1,-1,-1,-1},
    {42,3,35,59,107,360,408,181,245,4096,-1,-1,-1,-1,-1,-1,-1,-1,-1,-1,-1,-1,-1,-1},
    {42,3,35,59,107,360,408,181,245,4096,-1,-1,-1,-1,-1,-1,-1,-1,-1,-1,-1,-1,-1,-1},
    {45,156,220,396,85,109,93,180,244,4096,-1,-1,-1,-1,-1,-1,-1,-1,-1,-1,-1,-1,-1,-1},
    {45,156,220,396,85,109,93,180,244,4096,-1,-1,-1,-1,-1,-1,-1,-1,-1,-1,-1,-1,-1,-1},
    {466,482,266,258,37,69,53,77,183,247,4096,-1,-1,-1,-1,-1,-1,-1,-1,-1,-1,-1,-1,-1},
    {466,482,266,258,37,69,53,77,183,247,4096,-1,-1,-1,-1,-1,-1,-1,-1,-1,-1,-1,-1,-1},
    {471,407,463,442,290,322,314,386,478,382,366,414,182,246,4096,-1,-1,-1,-1,-1,-1,-1,-1,-1},
    {471,407,463,442,290,322,314,386,478,382,366,414,182,246,4096,-1,-1,-1,-1,-1,-1,-1,-1,-1},
    {469,349,485,501,445,333,317,373,477,423,439,415,173,237,4096,-1,-1,-1,-1,-1,-1,-1,-1,-1},
    {469,349,485,501,445,333,317,373,477,423,439,415,173,237,4096,-1,-1,-1,-1,-1,-1,-1,-1,-1},
    {8,269,309,453,449,489,385,425,422,358,92,188,252,4096,-1,-1,-1,-1,-1,-1,-1,-1,-1,-1},
    {8,269,309,453,449,489,385,425,422,358,92,188,252,4096,-1,-1,-1,-1,-1,-1,-1,-1,-1,-1},
    {343,287,487,263,303,455,495,391,51,91,160,224,4096,-1,-1,-1,-1,-1,-1,-1,-1,-1,-1,-1},
    {343,287,487,263,303,455,495,391,51,91,160,224,4096,-1,-1,-1,-1,-1,-1,-1,-1,-1,-1,-1},
    {464,272,480,456,288,488,392,61,379,363,435,176,240,4096,-1,-1,-1,-1,-1,-1,-1,-1,-1,-1},
    {464,272,480,456,288,488,392,61,379,363,435,176,240,4096,-1,-1,-1,-1,-1,-1,-1,-1,-1,-1},
    {336,280,400,256,448,320,312,384,424,416,352,432,472,171,235,4096,-1,-1,-1,-1,-1,-1,-1,-1},
    {336,280,400,256,448,320,312,384,424,416,352,432,472,171,235,4096,-1,-1,-1,-1,-1,-1,-1,-1},
    {337,273,265,155,219,368,376,479,359,102,184,248,4096,-1,-1,-1,-1,-1,-1,-1,-1,-1,-1,-1},
    {337,273,265,155,219,368,376,479,359,102,184,248,4096,-1,-1,-1,-1,-1,-1,-1,-1,-1,-1,-1},
    {468,284,508,260,300,324,332,388,104,72,174,238,4096,-1,-1,-1,-1,-1,-1,-1,-1,-1,-1,-1},
    {468,284,508,260,300,324,332,388,104,72,174,238,4096,-1,-1,-1,-1,-1,-1,-1,-1,-1,-1,-1},
    {338,281,2,34,66,110,78,175,239,4096,-1,-1,-1,-1,-1,-1,-1,-1,-1,-1,-1,-1,-1,-1},
    {338,281,2,34,66,110,78,175,239,4096,-1,-1,-1,-1,-1,-1,-1,-1,-1,-1,-1,-1,-1,-1},
    {130,194,39,63,55,95,103,97,4096,-1,-1,-1,-1,-1,-1,-1,-1,-1,-1,-1,-1,-1,-1,-1},
    {130,194,39,63,55,95,103,97,4096,-1,-1,-1,-1,-1,-1,-1,-1,-1,-1,-1,-1,-1,-1,-1},
    {135,199,454,494,67,83,365,413,191,255,4096,-1,-1,-1,-1,-1,-1,-1,-1,-1,-1,-1,-1,-1},
    {135,199,454,494,67,83,365,413,191,255,4096,-1,-1,-1,-1,-1,-1,-1,-1,-1,-1,-1,-1,-1},
    {348,484,460,308,292,452,316,372,428,420,476,101,187,251,4096,-1,-1,-1,-1,-1,-1,-1,-1,-1},
    {348,484,460,308,292,452,316,372,428,420,476,101,187,251,4096,-1,-1,-1,-1,-1,-1,-1,-1,-1},
    {13,154,218,58,106,74,178,242,4096,-1,-1,-1,-1,-1,-1,-1,-1,-1,-1,-1,-1,-1,-1,-1},
    {13,154,218,58,106,74,178,242,4096,-1,-1,-1,-1,-1,-1,-1,-1,-1,-1,-1,-1,-1,-1,-1},
    {465,481,457,505,289,328,71,111,79,166,230,4096,-1,-1,-1,-1,-1,-1,-1,-1,-1,-1,-1,-1},
    {465,481,457,505,289,328,71,111,79,166,230,4096,-1,-1,-1,-1,-1,-1,-1,-1,-1,-1,-1,-1},
    {44,270,446,294,326,65,81,89,161,225,4096,-1,-1,-1,-1,-1,-1,-1,-1,-1,-1,-1,-1,-1},
    {44,270,446,294,326,65,81,89,161,225,4096,-1,-1,-1,-1,-1,-1,-1,-1,-1,-1,-1,-1,-1},
    {9,511,503,295,327,375,399,381,437,353,409,473,169,233,4096,-1,-1,-1,-1,-1,-1,-1,-1,-1},
    {9,511,503,295,327,375,399,381,437,353,409,473,169,233,4096,-1,-1,-1,-1,-1,-1,-1,-1,-1},
    {347,283,483,259,291,491,331,371,431,383,367,99,186,250,4096,-1,-1,-1,-1,-1,-1,-1,-1,-1},
    {347,283,483,259,291,491,331,371,431,383,367,99,186,250,4096,-1,-1,-1,-1,-1,-1,-1,-1,-1},
    {274,282,458,261,293,493,397,389,429,421,357,75,189,253,4096,-1,-1,-1,-1,-1,-1,-1,-1,-1},
    {274,282,458,261,293,493,397,389,429,421,357,75,189,253,4096,-1,-1,-1,-1,-1,-1,-1,-1,-1},
    {278,286,406,32,64,56,48,88,170,234,4096,-1,-1,-1,-1,-1,-1,-1,-1,-1,-1,-1,-1,-1},
    {278,286,406,32,64,56,48,88,170,234,4096,-1,-1,-1,-1,-1,-1,-1,-1,-1,-1,-1,-1,-1},
    {279,351,271,447,298,330,394,370,426,378,354,434,164,228,4096,-1,-1,-1,-1,-1,-1,-1,-1,-1},
    {279,351,271,447,298,330,394,370,426,378,354,434,164,228,4096,-1,-1,-1,-1,-1,-1,-1,-1,-1},
    {344,345,497,257,297,321,313,82,50,90,98,96,4096,-1,-1,-1,-1,-1,-1,-1,-1,-1,-1,-1},
    {344,345,497,257,297,321,313,82,50,90,98,96,4096,-1,-1,-1,-1,-1,-1,-1,-1,-1,-1,-1},
    {129,193,311,335,319,86,438,364,436,163,227,4096,-1,-1,-1,-1,-1,-1,-1,-1,-1,-1,-1,-1},
    {129,193,311,335,319,86,438,364,436,163,227,4096,-1,-1,-1,-1,-1,-1,-1,-1,-1,-1,-1,-1},
    {341,285,509,461,301,325,398,80,418,362,410,474,177,241,4096,-1,-1,-1,-1,-1,-1,-1,-1,-1},
    {341,285,509,461,301,325,398,80,418,362,410,474,177,241,4096,-1,-1,-1,-1,-1,-1,-1,-1,-1},
    {342,275,267,499,299,451,395,57,49,73,185,249,4096,-1,-1,-1,-1,-1,-1,-1,-1,-1,-1,-1},
    {342,275,267,499,299,451,395,57,49,73,185,249,4096,-1,-1,-1,-1,-1,-1,-1,-1,-1,-1,-1},
    {346,402,496,304,443,323,315,387,427,419,355,411,165,229,4096,-1,-1,-1,-1,-1,-1,-1,-1,-1},
    {346,402,496,304,443,323,315,387,427,419,355,411,165,229,4096,-1,-1,-1,-1,-1,-1,-1,-1,-1},
    {15,401,305,441,70,62,54,94,190,254,4096,-1,-1,-1,-1,-1,-1,-1,-1,-1,-1,-1,-1,-1},
    {15,401,305,441,70,62,54,94,190,254,4096,-1,-1,-1,-1,-1,-1,-1,-1,-1,-1,-1,-1,-1},
    {467,7,36,68,84,105,475,162,226,4096,-1,-1,-1,-1,-1,-1,-1,-1,-1,-1,-1,-1,-1,-1},
    {467,7,36,68,84,105,475,162,226,4096,-1,-1,-1,-1,-1,-1,-1,-1,-1,-1,-1,-1,-1,-1},
};

void build_rounds() {
    for (int c = 0; c < NUM_SMS / 2; c++) {
        const int16_t* jobs = h_params.jobs[2 * c];
        int nr = 0, prev_key = -1, last = 0;
        for (int j = 0; (jobs[j] >> 12) == T_P; j++) {
            const int n = jobs[j] >> 3, a = n >= 32, unit = n >= 16 && n < 32 ? (n >> 3) - 1 : 0, cnt = a ? 2 : 4;
            const int key = (jobs[j] & 7) | a << 3 | (unit > 0) << 4;
            const int wm = n < 16 ? 0 : (n < 32 ? 1 : n >> 4 & 1), col = n < 16 ? n : (n < 32 ? n & 7 : n & 15);
            const bool keep = key == prev_key, final_tile = (jobs[j + 1] >> 12) != T_P;
            const int k0 = keep ? last : 0;
            for (int r = 0; r < cnt; r++) {
                last = (k0 + r) % cnt;
                h_params.rounds[c][nr++] = (uint16_t)((key & 15) | wm << 4 | col << 6 | last << 10 | (keep && r == 0) << 12 | (final_tile && r == 0) << 13 | unit << 14);
            }
            prev_key = key;
        }
        while (nr < MAX_ROUNDS) h_params.rounds[c][nr++] = 0xFFFF;
        {
            const uint32_t rec = h_params.rounds[c][0], col = rec >> 6 & 15, unit = rec >> 14;
            for (uint32_t r = 0; r < 2; r++) {
                uint32_t wm[2], wb[2];
                for (uint32_t h = 0; h < 2; h++) {
                    wm[h] = 2 + ((rec & 8) ? 2 + h : ((rec >> 15) && h ? 0 : rec >> 4 & 1));
                    wb[h] = (rec & 8) ? (col + (rec & 16)) * 2
                                      : (unit == 0 ? col * 4 + h * 2 : (unit == 1 ? 16 + h * 16 + col * 2 : (h ? unit_head(col) : col) * 2));
                }
                const uint32_t am = unit ? 6 : (rec >> 3 & 1), arow = unit ? (rec & 7) * 128 + r * 64 : (rec & 7) * 256 + r * 128;
                h_params.first[2 * c + r] = make_uint2((unit ? 1 : 0) | am << 7 | wm[0] << 11 | wm[1] << 15 | arow << 20, wb[0] | wb[1] << 16);
            }
        }
    }
}

void build_schedule() {
    for (int c = 0; c < NUM_SMS; c++) {
        for (int j = 0; j < MAX_JOBS; j++) h_params.jobs[c][j] = k_jobs[c][j];
    }
    build_rounds();
}

}

extern "C" void kernel_launch(void* const* d_in, const int* in_sizes, int n_in, void* d_out, int out_size) {
    (void)in_sizes; (void)n_in; (void)out_size;
    static EncodeFn enc = nullptr;
    if (!enc) {
        cudaDriverEntryPointQueryResult qr;
        void* fn = nullptr;
        cudaGetDriverEntryPoint("cuTensorMapEncodeTiled", &fn, cudaEnableDefault, &qr);
        enc = (EncodeFn)fn;
        cudaFuncSetAttribute(fused_kernel, cudaFuncAttributeMaxDynamicSharedMemorySize, SMEM_BYTES);
        build_schedule();
    }
    void* qkv;
    cudaGetSymbolAddress(&qkv, g_qkv);
    Params& p = h_params;
    make_map3(enc, &p.amap[0], d_in[0], SEQ, DM, 128, 1);
    make_map3(enc, &p.amap[1], d_in[1], SEQ, DC, 128, 1);
    make_map3(enc, &p.wmap[0], d_in[2], DM, 4096, 64, 2);
    make_map3(enc, &p.wmap[2], d_in[3], DC, 4096, 64, 2);
    make_map3(enc, &p.wmap[3], d_in[4], DC, 4096, 64, 2);
    make_map3(enc, &p.wmap[1], d_in[7], DM, 3072, 64, 2);
    make_map3(enc, &p.wo_a, d_in[5], 4096, DM, 64, 2);
    make_map3(enc, &p.wo_b, d_in[8], DM, DM, 64, 2);
    make_map3(enc, &p.qkv_st, qkv, SEQ, QKV_W, 64, 1, true);
    make_map3(enc, &p.qkv_ld, qkv, SEQ, QKV_W, 128, 2, true);
    make_map3(enc, &p.qkv_half, qkv, SEQ, QKV_W, 128, 1, true);
    {
        cuuint64_t dims[4] = {64, SEQ / 2, 2, QKV_W / 64}, strides[3] = {256, 128, (cuuint64_t)SEQ * 128};
        cuuint32_t box[4] = {64, 64, 1, 1}, es[4] = {1, 1, 1, 1};
        enc(&p.st_par, CU_TENSOR_MAP_DATA_TYPE_BFLOAT16, 4, qkv, dims, strides, box, es, CU_TENSOR_MAP_INTERLEAVE_NONE,
            CU_TENSOR_MAP_SWIZZLE_128B, CU_TENSOR_MAP_L2_PROMOTION_L2_256B, CU_TENSOR_MAP_FLOAT_OOB_FILL_NONE);
        dims[3] = DM / 64; strides[0] = DM * 4; strides[1] = DM * 2; strides[2] = 128; box[2] = 2;
        enc(&p.x_par, CU_TENSOR_MAP_DATA_TYPE_BFLOAT16, 4, d_in[0], dims, strides, box, es, CU_TENSOR_MAP_INTERLEAVE_NONE,
            CU_TENSOR_MAP_SWIZZLE_128B, CU_TENSOR_MAP_L2_PROMOTION_L2_256B, CU_TENSOR_MAP_FLOAT_OOB_FILL_NONE);
    }
    make_map3(enc, &p.out_st, d_out, SEQ, DM, 64, 1);
    p.xp = (const __nv_bfloat16*)d_in[0];
    p.gate_w = (const __nv_bfloat16*)d_in[9];
    p.out = (__nv_bfloat16*)d_out;
    fused_kernel<<<NUM_SMS, 384, SMEM_BYTES, cudaStreamPerThread>>>(p);
}
```

```cpp
#include <cuda_runtime.h>
#include <cuda_bf16.h>
#include <cuda.h>
#include <stdint.h>

#define INL __attribute__((always_inline))

namespace {

constexpr int SEQ = 2048;
constexpr int DM = 1024;
constexpr int DC = 512;
constexpr int QKV_W = 13312;
constexpr int NUM_SMS = 132;
constexpr int GATE_DELAY_SHORT_NS = 1000, GATE_DELAY_LONG_NS = 3000;
constexpr int CLEAR_KS = 44, CLEAR_GAP_NS = 100;
constexpr float Q_SCALE = 0.08838834764831845f * 1.4426950408889634f;

__device__ __align__(1024) __nv_bfloat16 g_qkv[(size_t)SEQ * QKV_W];
__device__ float g_gate[SEQ];
__device__ uint4 g_halo[16 * 8 * 2 * 5 * 4 * 32];

constexpr int F_Q = 0;
constexpr int F_KV = 1792;
constexpr int F_H = 768;
constexpr int F_CTX = 960;
constexpr int F_GATE = 1600;
constexpr int F_DONE = 1632;
constexpr int F_SPLIT = 1664;
constexpr int F_TICKET = 1696;
constexpr int F_OUT = 1728;
constexpr int GATE_COUNT = NUM_SMS;
__device__ uint32_t g_flags[2304];

#define END_MARK(slot)
#define TRACE_MARK(k, w, i)
#define GTRACE(w)
#define KTRACE(w)
#define PTRACE(i)
#define TRACE_GATE 32
#define TRACE_TID 128

__device__ __forceinline__ uint32_t smem_u32(const void* p) { return (uint32_t)__cvta_generic_to_shared(p); }
__device__ __forceinline__ void mbar_init(uint32_t bar, uint32_t cnt) {
    asm volatile("mbarrier.init.shared::cta.b64 [%0], %1;" ::"r"(bar), "r"(cnt));
}
__device__ __forceinline__ void mbar_arrive(uint32_t bar) {
    asm volatile("mbarrier.arrive.shared::cta.b64 _, [%0];" ::"r"(bar) : "memory");
}
__device__ __forceinline__ bool elect_one() {
    uint32_t r;
    asm volatile("{\n.reg .pred p;\nelect.sync _|p, 0xffffffff;\nselp.b32 %0, 1, 0, p;\n}" : "=r"(r));
    return r != 0;
}
__device__ __forceinline__ uint32_t mapa(uint32_t addr, uint32_t cta) {
    uint32_t r;
    asm("mapa.shared::cluster.u32 %0, %1, %2;" : "=r"(r) : "r"(addr), "r"(cta));
    return r;
}
__device__ __forceinline__ void warp_arrive(uint32_t bar, bool pred = true) {
    asm volatile("{\n.reg .pred p, q;\nsetp.ne.u32 q, %1, 0;\nelect.sync _|p, 0xffffffff;\nand.pred p, p, q;\n"
                 "@p mbarrier.arrive.shared::cta.b64 _, [%0];\n}" ::"r"(bar), "r"((uint32_t)pred) : "memory");
}
__device__ __forceinline__ void warp_arrive2(uint32_t bar0, uint32_t bar1) {
    asm volatile("{\n.reg .pred p;\nelect.sync _|p, 0xffffffff;\n@p mbarrier.arrive.shared::cta.b64 _, [%0];\n"
                 "@p mbarrier.arrive.shared::cta.b64 _, [%1];\n}" ::"r"(bar0), "r"(bar1) : "memory");
}
__device__ __forceinline__ void warp_arrive_pair(uint32_t bar, uint32_t peer_bar, bool pred = true) {
    asm volatile("{\n.reg .pred p, q;\nsetp.ne.u32 q, %2, 0;\nelect.sync _|p, 0xffffffff;\nand.pred p, p, q;\n"
                 "@p mbarrier.arrive.shared::cluster.b64 _, [%1];\n@p mbarrier.arrive.shared::cta.b64 _, [%0];\n}"
                 ::"r"(bar), "r"(peer_bar), "r"((uint32_t)pred) : "memory");
}
__device__ __forceinline__ void mbar_expect_tx(uint32_t bar, uint32_t bytes) {
    asm volatile("mbarrier.arrive.expect_tx.shared::cta.b64 _, [%0], %1;" ::"r"(bar), "r"(bytes) : "memory");
}
constexpr int WAIT_HINT_NS = 20000, WAIT_TRIES = 200000;
__device__ __forceinline__ void mbar_wait(uint32_t bar, uint32_t parity) {
    asm volatile("{\n.reg .pred p;\n.reg .u32 c;\n"
                 "mbarrier.try_wait.parity.shared::cta.b64 p, [%0], %1;\n@p bra DONE;\nmov.u32 c, 0;\n"
                 "SPIN:\nmbarrier.try_wait.parity.shared::cta.b64 p, [%0], %1, %2;\n@p bra DONE;\n"
                 "add.u32 c, c, 1;\nsetp.lt.u32 p, c, %3;\n@p bra SPIN;\ntrap;\nDONE:\n}"
                 ::"r"(bar), "r"(parity), "n"(WAIT_HINT_NS), "n"(WAIT_TRIES) : "memory");
}
__device__ __forceinline__ void mbar_wait_hot(uint32_t bar, uint32_t parity) {
    asm volatile("{\n.reg .pred p, q;\n.reg .u32 c;\n.reg .u64 z;\nmov.u32 c, 0;\nmov.u64 z, 0;\n"
                 "SPIN:\nmbarrier.try_wait.parity.shared::cta.b64 p, [%0], %1;\n"
                 "add.u32 c, c, 1;\nsetp.lt.and.u32 q, c, 4194304, !p;\n@q bra SPIN;\n@!p st.global.u32 [z], c;\n}"
                 ::"r"(bar), "r"(parity) : "memory");
}
constexpr uint64_t POL_STREAM = 0x12F0000000000000ull;
constexpr uint64_t POL_NORMAL = 0x1000000000000000ull;
__device__ __forceinline__ void tma_load_3d(uint32_t dst, const CUtensorMap* map, uint32_t bar, int c0, int c1, int c2, uint64_t pol = POL_NORMAL) {
    asm volatile("cp.async.bulk.tensor.3d.shared::cluster.global.mbarrier::complete_tx::bytes.L2::cache_hint [%0], [%1, {%3, %4, %5}], [%2], %6;"
                 ::"r"(dst), "l"(map), "r"(bar), "r"(c0), "r"(c1), "r"(c2), "l"(pol) : "memory");
}
__device__ __forceinline__ void load_kstep(uint32_t sa, uint32_t sw, uint32_t bar, uint32_t bytes, const CUtensorMap* wmap, int wk, int wblk,
                                           const CUtensorMap* amap, int arow, int kc, uint32_t amode) {
    asm volatile("{\n.reg .pred p, q, r;\n.reg .b32 k;\nelect.sync _|p, 0xffffffff;\nsetp.eq.and.u32 q, %9, 1, p;\nsetp.eq.and.u32 r, %9, 2, p;\nshl.b32 k, %12, 6;\n"
                 "@p mbarrier.arrive.expect_tx.shared::cta.b64 _, [%2], %3;\n"
                 "@p cp.async.bulk.tensor.3d.shared::cluster.global.mbarrier::complete_tx::bytes.multicast::cluster.L2::cache_hint [%1], [%4, {0, k, %5}], [%2], %10, %11;\n"
                 "@q cp.async.bulk.tensor.3d.shared::cluster.global.mbarrier::complete_tx::bytes.L2::cache_hint [%0], [%6, {0, %7, %8}], [%2], %11;\n"
                 "@r cp.async.bulk.tensor.4d.shared::cluster.global.mbarrier::complete_tx::bytes.L2::cache_hint [%0], [%6, {0, %7, 0, %8}], [%2], %11;\n}"
                 ::"r"(sa), "r"(sw), "r"(bar), "r"(bytes), "l"(wmap), "r"(wblk), "l"(amap), "r"(arow), "r"(kc), "r"(amode), "h"((uint16_t)3), "l"(POL_NORMAL), "r"(wk) : "memory");
}
__device__ __forceinline__ void load_operand(uint32_t dst, uint32_t bar, const CUtensorMap* full, const CUtensorMap* half, int row, int blk,
                                             uint32_t rank, bool solo, uint64_t pol) {
    asm volatile("{\n.reg .pred p, q, r;\n.reg .b32 d, b;\nelect.sync _|p, 0xffffffff;\nsetp.ne.and.u32 q, %7, 0, p;\nsetp.eq.and.u32 r, %7, 0, p;\n"
                 "mad.lo.u32 d, %6, 16384, %0;\nadd.u32 b, %5, %6;\n"
                 "@p mbarrier.arrive.expect_tx.shared::cta.b64 _, [%1], 32768;\n"
                 "@q cp.async.bulk.tensor.3d.shared::cluster.global.mbarrier::complete_tx::bytes.L2::cache_hint [%0], [%2, {0, %4, %5}], [%1], %9;\n"
                 "@r cp.async.bulk.tensor.3d.shared::cluster.global.mbarrier::complete_tx::bytes.multicast::cluster.L2::cache_hint [d], [%3, {0, %4, b}], [%1], %8, %9;\n}"
                 ::"r"(dst), "r"(bar), "l"(full), "l"(half), "r"(row), "r"(blk), "r"(rank), "r"((uint32_t)solo), "h"((uint16_t)3), "l"(pol) : "memory");
}
__device__ __forceinline__ void tma_store_par(const CUtensorMap* map, uint32_t src, int pair, int parity, int blk) {
    asm volatile("cp.async.bulk.tensor.4d.global.shared::cta.bulk_group.L2::cache_hint [%0, {0, %2, %3, %4}], [%1], %5;"
                 ::"l"(map), "r"(src), "r"(pair), "r"(parity), "r"(blk), "l"(POL_STREAM) : "memory");
}
__device__ __forceinline__ void tma_store_3d(const CUtensorMap* map, uint32_t src, int c0, int c1, int c2, uint64_t pol) {
    asm volatile("cp.async.bulk.tensor.3d.global.shared::cta.bulk_group.L2::cache_hint [%0, {%2, %3, %4}], [%1], %5;"
                 ::"l"(map), "r"(src), "r"(c0), "r"(c1), "r"(c2), "l"(pol) : "memory");
}
__device__ __forceinline__ void tma_reduce_add_3d(const CUtensorMap* map, uint32_t src, int c0, int c1, int c2) {
    asm volatile("cp.reduce.async.bulk.tensor.3d.global.shared::cta.add.tile.bulk_group [%0, {%2, %3, %4}], [%1];"
                 ::"l"(map), "r"(src), "r"(c0), "r"(c1), "r"(c2) : "memory");
}
__device__ __forceinline__ void bulk_commit() { asm volatile("cp.async.bulk.commit_group;" ::: "memory"); }
template <int N> __device__ __forceinline__ void bulk_wait_read() { asm volatile("cp.async.bulk.wait_group.read %0;" ::"n"(N) : "memory"); }
template <int N> __device__ __forceinline__ void bulk_wait() { asm volatile("cp.async.bulk.wait_group %0;" ::"n"(N) : "memory"); }
__device__ __forceinline__ void fence_async_smem() { asm volatile("fence.proxy.async.shared::cta;" ::: "memory"); }
__device__ __forceinline__ void fence_async_global() { asm volatile("fence.proxy.async.global;" ::: "memory"); }
__device__ __forceinline__ uint32_t ld_acquire(const uint32_t* p) {
    uint32_t v;
    asm volatile("ld.acquire.gpu.global.u32 %0, [%1];" : "=r"(v) : "l"(p) : "memory");
    return v;
}
__device__ __forceinline__ uint32_t ld_relaxed(const uint32_t* p) {
    uint32_t v;
    asm volatile("ld.relaxed.gpu.global.u32 %0, [%1];" : "=r"(v) : "l"(p) : "memory");
    return v;
}
__device__ __forceinline__ void fence_acquire() { asm volatile("fence.acquire.gpu;\nfence.proxy.async.global;" ::: "memory"); }
__device__ __forceinline__ void red_release(uint32_t* p) {
    asm volatile("red.release.gpu.global.add.u32 [%0], 1;" ::"l"(p) : "memory");
}
__device__ __forceinline__ void red_relaxed(uint32_t* p) {
    asm volatile("red.relaxed.gpu.global.add.u32 [%0], 1;" ::"l"(p) : "memory");
}
__device__ __forceinline__ void prefetch_map(const CUtensorMap* map) { asm volatile("prefetch.tensormap [%0];" ::"l"(map) : "memory"); }
__device__ __forceinline__ void trap_if(bool c) { asm volatile("{\n.reg .pred p;\nsetp.ne.u32 p, %0, 0;\n@p trap;\n}" ::"r"((uint32_t)c)); }
__device__ __forceinline__ void setup_arrive() { asm volatile("barrier.cluster.arrive.relaxed.aligned;" ::: "memory"); }
__device__ __forceinline__ void setup_wait() { asm volatile("barrier.cluster.wait.aligned;" ::: "memory"); }
__device__ __forceinline__ uint32_t cluster_rank() { uint32_t r; asm("mov.u32 %0, %%cluster_ctarank;" : "=r"(r)); return r; }
__device__ __forceinline__ void named_sync(int id, int n) { asm volatile("bar.sync %0, %1;" ::"r"(id), "r"(n) : "memory"); }
__device__ __forceinline__ void named_arrive(int id, int n) { asm volatile("bar.arrive %0, %1;" ::"r"(id), "r"(n) : "memory"); }
__device__ __forceinline__ void named_sync_if(bool c, int id, int n) {
    asm volatile("{\n.reg .pred p;\nsetp.ne.u32 p, %0, 0;\n@p bar.sync %1, %2;\n}" ::"r"((uint32_t)c), "r"(id), "r"(n) : "memory");
}
__device__ __forceinline__ void named_arrive_if(bool c, int id, int n) {
    asm volatile("{\n.reg .pred p;\nsetp.ne.u32 p, %0, 0;\n@p bar.arrive %1, %2;\n}" ::"r"((uint32_t)c), "r"(id), "r"(n) : "memory");
}
template <int V> struct IC { static constexpr int v = V; };
template <int N> __device__ __forceinline__ void reg_dec() { asm volatile("setmaxnreg.dec.sync.aligned.u32 %0;" ::"n"(N)); }
template <int N> __device__ __forceinline__ void reg_inc() { asm volatile("setmaxnreg.inc.sync.aligned.u32 %0;" ::"n"(N)); }

__device__ __forceinline__ void wg_fence() { asm volatile("wgmma.fence.sync.aligned;" ::: "memory"); }
__device__ __forceinline__ void wg_commit() { asm volatile("wgmma.commit_group.sync.aligned;" ::: "memory"); }
template <int N> __device__ __forceinline__ void wg_wait() { asm volatile("wgmma.wait_group.sync.aligned %0;" ::"n"(N) : "memory"); }
template <int N> __device__ __forceinline__ void fence_regs(float (&r)[N]) {
#pragma unroll
    for (int i = 0; i < N; i++) asm volatile("" : "+f"(r[i])::"memory");
}
template <int N> __device__ __forceinline__ void fence_regs(uint32_t (&r)[N]) {
#pragma unroll
    for (int i = 0; i < N; i++) asm volatile("" : "+r"(r[i])::"memory");
}
__device__ __forceinline__ uint32_t desc_lo(uint32_t addr, uint32_t lbo) { return ((addr & 0x3FFFF) >> 4) | ((lbo >> 4) << 16); }
__device__ __forceinline__ int uniform(int v) { return __shfl_sync(0xffffffffu, v, 0); }
__device__ __forceinline__ uint32_t pack_bf16(float lo, float hi) {
    uint32_t r;
    asm("cvt.rn.bf16x2.f32 %0, %1, %2;" : "=r"(r) : "f"(hi), "f"(lo));
    return r;
}
__device__ __forceinline__ uint32_t mul_bf16x2(uint32_t x, uint32_t y) {
    uint32_t r;
    asm("mul.rn.bf16x2 %0, %1, %2;" : "=r"(r) : "r"(x), "r"(y));
    return r;
}
__device__ __forceinline__ void stmatrix_x4(uint32_t addr, uint32_t r0, uint32_t r1, uint32_t r2, uint32_t r3) {
    asm volatile("stmatrix.sync.aligned.m8n8.x4.shared.b16 [%0], {%1, %2, %3, %4};"
                 ::"r"(addr), "r"(r0), "r"(r1), "r"(r2), "r"(r3) : "memory");
}
__device__ __forceinline__ void stmatrix_x4(uint32_t addr, uint32_t r0, uint32_t r1, uint32_t r2, uint32_t r3, bool trans) {
    asm volatile("{\n.reg .pred p;\nsetp.ne.u32 p, %5, 0;\n@p stmatrix.sync.aligned.m8n8.x4.trans.shared.b16 [%0], {%1, %2, %3, %4};\n"
                 "@!p stmatrix.sync.aligned.m8n8.x4.shared.b16 [%0], {%1, %2, %3, %4};\n}"
                 ::"r"(addr), "r"(r0), "r"(r1), "r"(r2), "r"(r3), "r"((uint32_t)trans) : "memory");
}
__device__ __forceinline__ void ldmatrix_x4_t(uint32_t addr, uint32_t (&r)[4]) {
    asm volatile("ldmatrix.sync.aligned.m8n8.x4.trans.shared.b16 {%0, %1, %2, %3}, [%4];"
                 : "=r"(r[0]), "=r"(r[1]), "=r"(r[2]), "=r"(r[3]) : "r"(addr) : "memory");
}
__device__ __forceinline__ void mma_16816(float (&d)[4], uint32_t a0, uint32_t a1, uint32_t a2, uint32_t a3, uint32_t b0, uint32_t b1) {
    asm("mma.sync.aligned.m16n8k16.row.col.f32.bf16.bf16.f32 {%0, %1, %2, %3}, {%4, %5, %6, %7}, {%8, %9}, {%0, %1, %2, %3};"
        : "+f"(d[0]), "+f"(d[1]), "+f"(d[2]), "+f"(d[3]) : "r"(a0), "r"(a1), "r"(a2), "r"(a3), "r"(b0), "r"(b1));
}
__device__ __forceinline__ void order_after(float v, uint32_t scratch) {
    asm volatile("{\n.reg .pred p;\nsetp.gt.f32 p, %0, 0f70000000;\n@p st.shared.u32 [%1], 0;\n}" ::"f"(v), "r"(scratch) : "memory");
}
__device__ __forceinline__ float rcp(float x) { float y; asm("rcp.approx.ftz.f32 %0, %1;" : "=f"(y) : "f"(x)); return y; }
__device__ __forceinline__ float ex2(float x) { float y; asm("ex2.approx.ftz.f32 %0, %1;" : "=f"(y) : "f"(x)); return y; }

template <int OA, int OB>
__device__ __forceinline__ void wgmma_ss_n256(float (&d0)[64], float (&d1)[64], uint32_t da, uint32_t db) {
    asm volatile("{\n.reg .b32 ta, tb;\n.reg .b64 da, db;\nadd.u32 ta, %128, %130;\nadd.u32 tb, %129, %131;\n"
        "mov.b64 da, {ta, 0x40000040};\nmov.b64 db, {tb, 0x40000040};\n"
        "wgmma.mma_async.sync.aligned.m64n256k16.f32.bf16.bf16 {%0, %1, %2, %3, %4, %5, %6, %7, %8, %9, %10, %11, %12, %13, %14, %15, %16, %17, %18, %19, %20, %21, %22, %23, %24, %25, %26, %27, %28, %29, %30, %31, %32, %33, %34, %35, %36, %37, %38, %39, %40, %41, %42, %43, %44, %45, %46, %47, %48, %49, %50, %51, %52, %53, %54, %55, %56, %57, %58, %59, %60, %61, %62, %63, %64, %65, %66, %67, %68, %69, %70, %71, %72, %73, %74, %75, %76, %77, %78, %79, %80, %81, %82, %83, %84, %85, %86, %87, %88, %89, %90, %91, %92, %93, %94, %95, %96, %97, %98, %99, %100, %101, %102, %103, %104, %105, %106, %107, %108, %109, %110, %111, %112, %113, %114, %115, %116, %117, %118, %119, %120, %121, %122, %123, %124, %125, %126, %127}, da, db, 1, 1, 1, 0, 1;\n}\n"
        : "+f"(d0[0]), "+f"(d0[1]), "+f"(d0[2]), "+f"(d0[3]), "+f"(d0[4]), "+f"(d0[5]), "+f"(d0[6]), "+f"(d0[7]), "+f"(d0[8]), "+f"(d0[9]), "+f"(d0[10]), "+f"(d0[11]), "+f"(d0[12]), "+f"(d0[13]), "+f"(d0[14]), "+f"(d0[15]), "+f"(d0[16]), "+f"(d0[17]), "+f"(d0[18]), "+f"(d0[19]), "+f"(d0[20]), "+f"(d0[21]), "+f"(d0[22]), "+f"(d0[23]), "+f"(d0[24]), "+f"(d0[25]), "+f"(d0[26]), "+f"(d0[27]), "+f"(d0[28]), "+f"(d0[29]), "+f"(d0[30]), "+f"(d0[31]), "+f"(d0[32]), "+f"(d0[33]), "+f"(d0[34]), "+f"(d0[35]), "+f"(d0[36]), "+f"(d0[37]), "+f"(d0[38]), "+f"(d0[39]), "+f"(d0[40]), "+f"(d0[41]), "+f"(d0[42]), "+f"(d0[43]), "+f"(d0[44]), "+f"(d0[45]), "+f"(d0[46]), "+f"(d0[47]), "+f"(d0[48]), "+f"(d0[49]), "+f"(d0[50]), "+f"(d0[51]), "+f"(d0[52]), "+f"(d0[53]), "+f"(d0[54]), "+f"(d0[55]), "+f"(d0[56]), "+f"(d0[57]), "+f"(d0[58]), "+f"(d0[59]), "+f"(d0[60]), "+f"(d0[61]), "+f"(d0[62]), "+f"(d0[63]), "+f"(d1[0]), "+f"(d1[1]), "+f"(d1[2]), "+f"(d1[3]), "+f"(d1[4]), "+f"(d1[5]), "+f"(d1[6]), "+f"(d1[7]), "+f"(d1[8]), "+f"(d1[9]), "+f"(d1[10]), "+f"(d1[11]), "+f"(d1[12]), "+f"(d1[13]), "+f"(d1[14]), "+f"(d1[15]), "+f"(d1[16]), "+f"(d1[17]), "+f"(d1[18]), "+f"(d1[19]), "+f"(d1[20]), "+f"(d1[21]), "+f"(d1[22]), "+f"(d1[23]), "+f"(d1[24]), "+f"(d1[25]), "+f"(d1[26]), "+f"(d1[27]), "+f"(d1[28]), "+f"(d1[29]), "+f"(d1[30]), "+f"(d1[31]), "+f"(d1[32]), "+f"(d1[33]), "+f"(d1[34]), "+f"(d1[35]), "+f"(d1[36]), "+f"(d1[37]), "+f"(d1[38]), "+f"(d1[39]), "+f"(d1[40]), "+f"(d1[41]), "+f"(d1[42]), "+f"(d1[43]), "+f"(d1[44]), "+f"(d1[45]), "+f"(d1[46]), "+f"(d1[47]), "+f"(d1[48]), "+f"(d1[49]), "+f"(d1[50]), "+f"(d1[51]), "+f"(d1[52]), "+f"(d1[53]), "+f"(d1[54]), "+f"(d1[55]), "+f"(d1[56]), "+f"(d1[57]), "+f"(d1[58]), "+f"(d1[59]), "+f"(d1[60]), "+f"(d1[61]), "+f"(d1[62]), "+f"(d1[63])
        : "r"(da), "r"(db), "n"(OA), "n"(OB));
}

__device__ __forceinline__ void wgmma_ss_n256_init(float (&d0)[64], float (&d1)[64], uint32_t da, uint32_t db) {
    asm volatile("{\n.reg .b64 da, db;\n"
        "mov.b64 da, {%128, 0x40000040};\nmov.b64 db, {%129, 0x40000040};\n"
        "wgmma.mma_async.sync.aligned.m64n256k16.f32.bf16.bf16 {%0, %1, %2, %3, %4, %5, %6, %7, %8, %9, %10, %11, %12, %13, %14, %15, %16, %17, %18, %19, %20, %21, %22, %23, %24, %25, %26, %27, %28, %29, %30, %31, %32, %33, %34, %35, %36, %37, %38, %39, %40, %41, %42, %43, %44, %45, %46, %47, %48, %49, %50, %51, %52, %53, %54, %55, %56, %57, %58, %59, %60, %61, %62, %63, %64, %65, %66, %67, %68, %69, %70, %71, %72, %73, %74, %75, %76, %77, %78, %79, %80, %81, %82, %83, %84, %85, %86, %87, %88, %89, %90, %91, %92, %93, %94, %95, %96, %97, %98, %99, %100, %101, %102, %103, %104, %105, %106, %107, %108, %109, %110, %111, %112, %113, %114, %115, %116, %117, %118, %119, %120, %121, %122, %123, %124, %125, %126, %127}, da, db, 0, 1, 1, 0, 1;\n}\n"
        : "=f"(d0[0]), "=f"(d0[1]), "=f"(d0[2]), "=f"(d0[3]), "=f"(d0[4]), "=f"(d0[5]), "=f"(d0[6]), "=f"(d0[7]), "=f"(d0[8]), "=f"(d0[9]), "=f"(d0[10]), "=f"(d0[11]), "=f"(d0[12]), "=f"(d0[13]), "=f"(d0[14]), "=f"(d0[15]), "=f"(d0[16]), "=f"(d0[17]), "=f"(d0[18]), "=f"(d0[19]), "=f"(d0[20]), "=f"(d0[21]), "=f"(d0[22]), "=f"(d0[23]), "=f"(d0[24]), "=f"(d0[25]), "=f"(d0[26]), "=f"(d0[27]), "=f"(d0[28]), "=f"(d0[29]), "=f"(d0[30]), "=f"(d0[31]), "=f"(d0[32]), "=f"(d0[33]), "=f"(d0[34]), "=f"(d0[35]), "=f"(d0[36]), "=f"(d0[37]), "=f"(d0[38]), "=f"(d0[39]), "=f"(d0[40]), "=f"(d0[41]), "=f"(d0[42]), "=f"(d0[43]), "=f"(d0[44]), "=f"(d0[45]), "=f"(d0[46]), "=f"(d0[47]), "=f"(d0[48]), "=f"(d0[49]), "=f"(d0[50]), "=f"(d0[51]), "=f"(d0[52]), "=f"(d0[53]), "=f"(d0[54]), "=f"(d0[55]), "=f"(d0[56]), "=f"(d0[57]), "=f"(d0[58]), "=f"(d0[59]), "=f"(d0[60]), "=f"(d0[61]), "=f"(d0[62]), "=f"(d0[63]), "=f"(d1[0]), "=f"(d1[1]), "=f"(d1[2]), "=f"(d1[3]), "=f"(d1[4]), "=f"(d1[5]), "=f"(d1[6]), "=f"(d1[7]), "=f"(d1[8]), "=f"(d1[9]), "=f"(d1[10]), "=f"(d1[11]), "=f"(d1[12]), "=f"(d1[13]), "=f"(d1[14]), "=f"(d1[15]), "=f"(d1[16]), "=f"(d1[17]), "=f"(d1[18]), "=f"(d1[19]), "=f"(d1[20]), "=f"(d1[21]), "=f"(d1[22]), "=f"(d1[23]), "=f"(d1[24]), "=f"(d1[25]), "=f"(d1[26]), "=f"(d1[27]), "=f"(d1[28]), "=f"(d1[29]), "=f"(d1[30]), "=f"(d1[31]), "=f"(d1[32]), "=f"(d1[33]), "=f"(d1[34]), "=f"(d1[35]), "=f"(d1[36]), "=f"(d1[37]), "=f"(d1[38]), "=f"(d1[39]), "=f"(d1[40]), "=f"(d1[41]), "=f"(d1[42]), "=f"(d1[43]), "=f"(d1[44]), "=f"(d1[45]), "=f"(d1[46]), "=f"(d1[47]), "=f"(d1[48]), "=f"(d1[49]), "=f"(d1[50]), "=f"(d1[51]), "=f"(d1[52]), "=f"(d1[53]), "=f"(d1[54]), "=f"(d1[55]), "=f"(d1[56]), "=f"(d1[57]), "=f"(d1[58]), "=f"(d1[59]), "=f"(d1[60]), "=f"(d1[61]), "=f"(d1[62]), "=f"(d1[63])
        : "r"(da), "r"(db));
}

template <int TB, int OA, int OB>
__device__ __forceinline__ void wgmma_ss_n128_init(float (&d)[64], uint32_t da, uint32_t db) {
    asm volatile("{\n.reg .b32 ta, tb;\n.reg .b64 da, db;\nadd.u32 ta, %64, %66;\nadd.u32 tb, %65, %67;\n"
        "mov.b64 da, {ta, 0x40000040};\nmov.b64 db, {tb, 0x40000040};\n"
        "wgmma.mma_async.sync.aligned.m64n128k16.f32.bf16.bf16 {%0, %1, %2, %3, %4, %5, %6, %7, %8, %9, %10, %11, %12, %13, %14, %15, %16, %17, %18, %19, %20, %21, %22, %23, %24, %25, %26, %27, %28, %29, %30, %31, %32, %33, %34, %35, %36, %37, %38, %39, %40, %41, %42, %43, %44, %45, %46, %47, %48, %49, %50, %51, %52, %53, %54, %55, %56, %57, %58, %59, %60, %61, %62, %63}, da, db, 0, 1, 1, 0, %68;\n}\n"
        : "=f"(d[0]), "=f"(d[1]), "=f"(d[2]), "=f"(d[3]), "=f"(d[4]), "=f"(d[5]), "=f"(d[6]), "=f"(d[7]), "=f"(d[8]), "=f"(d[9]), "=f"(d[10]), "=f"(d[11]), "=f"(d[12]), "=f"(d[13]), "=f"(d[14]), "=f"(d[15]), "=f"(d[16]), "=f"(d[17]), "=f"(d[18]), "=f"(d[19]), "=f"(d[20]), "=f"(d[21]), "=f"(d[22]), "=f"(d[23]), "=f"(d[24]), "=f"(d[25]), "=f"(d[26]), "=f"(d[27]), "=f"(d[28]), "=f"(d[29]), "=f"(d[30]), "=f"(d[31]), "=f"(d[32]), "=f"(d[33]), "=f"(d[34]), "=f"(d[35]), "=f"(d[36]), "=f"(d[37]), "=f"(d[38]), "=f"(d[39]), "=f"(d[40]), "=f"(d[41]), "=f"(d[42]), "=f"(d[43]), "=f"(d[44]), "=f"(d[45]), "=f"(d[46]), "=f"(d[47]), "=f"(d[48]), "=f"(d[49]), "=f"(d[50]), "=f"(d[51]), "=f"(d[52]), "=f"(d[53]), "=f"(d[54]), "=f"(d[55]), "=f"(d[56]), "=f"(d[57]), "=f"(d[58]), "=f"(d[59]), "=f"(d[60]), "=f"(d[61]), "=f"(d[62]), "=f"(d[63])
        : "r"(da), "r"(db), "n"(OA), "n"(OB), "n"(TB));
}

template <int OA, int OB>
__device__ __forceinline__ void wgmma_ss_n128_tb0(float (&d)[64], uint32_t da, uint32_t db, int scale_d) {
    asm volatile("{\n.reg .pred p;\n.reg .b32 ta, tb;\n.reg .b64 da, db;\nsetp.ne.b32 p, %66, 0;\nadd.u32 ta, %64, %67;\nadd.u32 tb, %65, %68;\n"
        "mov.b64 da, {ta, 0x40000040};\nmov.b64 db, {tb, 0x40000040};\n"
        "wgmma.mma_async.sync.aligned.m64n128k16.f32.bf16.bf16 "
        "{%0, %1, %2, %3, %4, %5, %6, %7, %8, %9, %10, %11, %12, %13, %14, %15, %16, %17, %18, %19, %20, %21, %22, %23, %24, %25, %26, %27, %28, %29, %30, %31, %32, %33, %34, %35, %36, %37, %38, %39, %40, %41, %42, %43, %44, %45, %46, %47, %48, %49, %50, %51, %52, %53, %54, %55, %56, %57, %58, %59, %60, %61, %62, %63}, da, db, p, 1, 1, 0, 0;\n}\n"
        : "+f"(d[0]), "+f"(d[1]), "+f"(d[2]), "+f"(d[3]), "+f"(d[4]), "+f"(d[5]), "+f"(d[6]), "+f"(d[7]), "+f"(d[8]), "+f"(d[9]), "+f"(d[10]), "+f"(d[11]), "+f"(d[12]), "+f"(d[13]), "+f"(d[14]), "+f"(d[15]), "+f"(d[16]), "+f"(d[17]), "+f"(d[18]), "+f"(d[19]), "+f"(d[20]), "+f"(d[21]), "+f"(d[22]), "+f"(d[23]), "+f"(d[24]), "+f"(d[25]), "+f"(d[26]), "+f"(d[27]), "+f"(d[28]), "+f"(d[29]), "+f"(d[30]), "+f"(d[31]), "+f"(d[32]), "+f"(d[33]), "+f"(d[34]), "+f"(d[35]), "+f"(d[36]), "+f"(d[37]), "+f"(d[38]), "+f"(d[39]), "+f"(d[40]), "+f"(d[41]), "+f"(d[42]), "+f"(d[43]), "+f"(d[44]), "+f"(d[45]), "+f"(d[46]), "+f"(d[47]), "+f"(d[48]), "+f"(d[49]), "+f"(d[50]), "+f"(d[51]), "+f"(d[52]), "+f"(d[53]), "+f"(d[54]), "+f"(d[55]), "+f"(d[56]), "+f"(d[57]), "+f"(d[58]), "+f"(d[59]), "+f"(d[60]), "+f"(d[61]), "+f"(d[62]), "+f"(d[63])
        : "r"(da), "r"(db), "r"(scale_d), "n"(OA), "n"(OB));
}

template <int OB>
__device__ __forceinline__ void wgmma_rs_n128_tb1(float (&d)[64], uint32_t a0, uint32_t a1, uint32_t a2, uint32_t a3, uint32_t db, int scale_d) {
    asm volatile("{\n.reg .pred p;\n.reg .b32 tb;\n.reg .b64 db;\nsetp.ne.b32 p, %69, 0;\nadd.u32 tb, %68, %70;\n"
        "mov.b64 db, {tb, 0x40000040};\n"
        "wgmma.mma_async.sync.aligned.m64n128k16.f32.bf16.bf16 "
        "{%0, %1, %2, %3, %4, %5, %6, %7, %8, %9, %10, %11, %12, %13, %14, %15, %16, %17, %18, %19, %20, %21, %22, %23, %24, %25, %26, %27, %28, %29, %30, %31, %32, %33, %34, %35, %36, %37, %38, %39, %40, %41, %42, %43, %44, %45, %46, %47, %48, %49, %50, %51, %52, %53, %54, %55, %56, %57, %58, %59, %60, %61, %62, %63}, {%64, %65, %66, %67}, db, p, 1, 1, 1;\n}\n"
        : "+f"(d[0]), "+f"(d[1]), "+f"(d[2]), "+f"(d[3]), "+f"(d[4]), "+f"(d[5]), "+f"(d[6]), "+f"(d[7]), "+f"(d[8]), "+f"(d[9]), "+f"(d[10]), "+f"(d[11]), "+f"(d[12]), "+f"(d[13]), "+f"(d[14]), "+f"(d[15]), "+f"(d[16]), "+f"(d[17]), "+f"(d[18]), "+f"(d[19]), "+f"(d[20]), "+f"(d[21]), "+f"(d[22]), "+f"(d[23]), "+f"(d[24]), "+f"(d[25]), "+f"(d[26]), "+f"(d[27]), "+f"(d[28]), "+f"(d[29]), "+f"(d[30]), "+f"(d[31]), "+f"(d[32]), "+f"(d[33]), "+f"(d[34]), "+f"(d[35]), "+f"(d[36]), "+f"(d[37]), "+f"(d[38]), "+f"(d[39]), "+f"(d[40]), "+f"(d[41]), "+f"(d[42]), "+f"(d[43]), "+f"(d[44]), "+f"(d[45]), "+f"(d[46]), "+f"(d[47]), "+f"(d[48]), "+f"(d[49]), "+f"(d[50]), "+f"(d[51]), "+f"(d[52]), "+f"(d[53]), "+f"(d[54]), "+f"(d[55]), "+f"(d[56]), "+f"(d[57]), "+f"(d[58]), "+f"(d[59]), "+f"(d[60]), "+f"(d[61]), "+f"(d[62]), "+f"(d[63])
        : "r"(a0), "r"(a1), "r"(a2), "r"(a3), "r"(db), "r"(scale_d), "n"(OB));
}

__device__ __forceinline__ uint32_t stage_addr(uint32_t block, int warp, int lane) {
    return block + (warp * 16 + (lane & 7) + ((lane >> 3) & 1) * 8) * 128 + (((lane >> 4) ^ (lane & 7)) << 4);
}
template <int OFF, int N>
__device__ __forceinline__ void stage_packed_64x64(uint32_t a0, int off, const uint32_t (&v)[N]) {
#pragma unroll
    for (int j = 0; j < 8; j += 2) {
        uint32_t a = a0;
        if (j) asm volatile("xor.b32 %0, %1, %2;" : "=r"(a) : "r"(a0), "r"(j << 4));
        stmatrix_x4(a + off, v[OFF + j * 2], v[OFF + j * 2 + 1], v[OFF + j * 2 + 2], v[OFF + j * 2 + 3]);
    }
}

template <int OFF, int N>
__device__ __forceinline__ void stage_packed_64x64(const uint32_t (&a)[4], int off, const uint32_t (&v)[N]) {
#pragma unroll
    for (int j = 0; j < 4; j++) stmatrix_x4(a[j] + off, v[OFF + j * 4], v[OFF + j * 4 + 1], v[OFF + j * 4 + 2], v[OFF + j * 4 + 3]);
}

template <int OFF, int N>
__device__ __forceinline__ void stage_packed_64x64(const uint32_t (&a)[4], int off, const uint32_t (&v)[N], bool trans) {
#pragma unroll
    for (int j = 0; j < 4; j++) stmatrix_x4(a[j] + off, v[OFF + j * 4], v[OFF + j * 4 + 1], v[OFF + j * 4 + 2], v[OFF + j * 4 + 3], trans);
}

constexpr int MAX_JOBS = 24;
constexpr int MAX_ROUNDS = 44;
constexpr int T_P = 0, T_O = 1, T_A = 2;
constexpr int HQ_A = 4, HQ_B = 28;
__host__ __device__ constexpr int unit_head(int g) { return g + (g < 4 ? HQ_A : HQ_B - 4); }
constexpr int G_STAGE = 49152;
constexpr int OFF_Q0 = 0, OFF_K0 = 32768, OFF_Q1 = 65536, OFF_K1 = 98304, OFF_V0 = 131072, OFF_V1 = 163840;
constexpr int OFF_STG = 196608;
constexpr int OFF_BAR = 229376;
constexpr int SMEM_BYTES = OFF_BAR + 640;
constexpr int TURN_THREADS = 288;

struct Params {
    CUtensorMap amap[2];
    CUtensorMap wmap[4];
    CUtensorMap x_par, wo_a, wo_b, qkv_st, qkv_ld, qkv_half, st_par, out_st;
    const __nv_bfloat16* xp;
    const __nv_bfloat16* gate_w;
    __nv_bfloat16* out;
    uint2 first[NUM_SMS];
    int16_t jobs[NUM_SMS][MAX_JOBS];
    uint16_t rounds[NUM_SMS / 2][MAX_ROUNDS];
};

constexpr int O_STAGGER = 4;
constexpr int O_F0 = 35, O_H1 = 5;
constexpr int O_FLEX = 16, O_H0 = O_F0 + 8, O_T0 = 8, O_T1 = 64 - O_F0 - O_FLEX - O_H1;
__device__ __forceinline__ int o_head(int job) { return (job & 32) ? O_H1 : O_H0; }
__device__ __forceinline__ int o_tail(int job) { return (job & 32) ? O_T1 : O_T0; }
__device__ __forceinline__ uint32_t o_state(uint32_t word, int have) {
    uint32_t v;
    asm volatile("{\n.reg .pred p, q;\n.reg .u32 c, t;\nmov.u32 c, 0;\n"
                 "SPIN:\nld.volatile.shared.u32 %0, [%1];\nand.b32 t, %0, 1;\nsetp.ne.u32 q, t, 0;\nsetp.gt.or.u32 p, %0, %2, q;\n@p bra DONE;\n"
                 "add.u32 c, c, 1;\nsetp.lt.u32 q, c, 16777216;\n@q bra SPIN;\ntrap;\nDONE:\n}"
                 : "=r"(v) : "r"(word), "r"(2 * have + 1) : "memory");
    return v;
}

template <class T> __device__ __forceinline__ T* page_ptr(int off) {
    extern __shared__ __align__(1024) uint8_t smem_raw[];
    return *reinterpret_cast<T* volatile*>(smem_raw + OFF_BAR + off);
}
template <int SLEEP_NS = 0>
__device__ __forceinline__ bool wait_flags(bool active, int idx, uint32_t target, bool block = true) {
    for (uint32_t tries = 0;; tries++) {
        const bool ok = !active | ((int32_t)(ld_acquire(g_flags + idx) - target) >= 0);
        if (__all_sync(0xffffffffu, ok)) break;
        if (!block) return false;
        if (SLEEP_NS) __nanosleep(SLEEP_NS);
        trap_if(tries > (1u << 22));
    }
    fence_async_global();
    return true;
}

__global__ void __cluster_dims__(2, 1, 1) __launch_bounds__(384, 1)
fused_kernel(const __grid_constant__ Params p) {
    extern __shared__ __align__(1024) uint8_t smem_raw[];
    const uint32_t base = smem_u32(smem_raw);
    const uint32_t bars = base + OFF_BAR;
    const uint32_t gfull = bars, gempty = bars + 32, sfull = bars + 64, sempty = bars + 96;
    const uint32_t qfull = bars + 128, qempty = bars + 144, kfull = bars + 160, kempty = bars + 176;
    const uint32_t vfull = bars + 192, vempty = bars + 208, lready = bars + 224, hout = bars + 240;
    const uint32_t tfull = bars + 256, aready = bars + 272, gatefull = bars + 280;
    const uint32_t otile = bars + 528;
    const uint32_t olim = bars + 504;
    const uint32_t stg = base + OFF_STG;
    uint32_t* rounds = reinterpret_cast<uint32_t*>(smem_raw + OFF_BAR + 416);
    const uint32_t rank = cluster_rank();
    int* jobs = reinterpret_cast<int*>(smem_raw + OFF_BAR + 312);
    auto w_map = [&](uint32_t rec, uint32_t half) INL { return &p.wmap[(rec & 8) ? 2 + half : ((rec >> 15) && half ? 0 : rec >> 4 & 1)]; };
    auto w_blk = [&](uint32_t rec, uint32_t half) INL -> int {
        const int col = rec >> 6 & 15;
        if (rec & 8) return (col + (rec & 16)) * 2;
        return rec >> 14 == 0 ? col * 4 + half * 2 : (rec >> 14 == 1 ? 16 + half * 16 + col * 2 : (half ? unit_head(col) : col) * 2);
    };
    auto load_round = [&](uint32_t rec, int st0, uint32_t parity) INL {
        const CUtensorMap* wm = w_map(rec, rank);
        const CUtensorMap* am = rec >> 14 ? &p.x_par : &p.amap[rec >> 3 & 1];
        const int wb = w_blk(rec, rank), kc0 = (rec >> 10 & 3) * 4, arow = ((rec & 7) * 256 + rank * 128) >> (rec >> 14 ? 1 : 0);
        const uint32_t bytes = (rec & 4096) ? G_STAGE - 16384 : G_STAGE, amode = (rec & 4096) ? 0 : (rec >> 14 ? 2 : 1);
#pragma unroll 1
        for (int st = st0; st < 4; st++) {
            const uint32_t sa = base + st * G_STAGE;
            mbar_wait(gempty + st * 8, parity);
            load_kstep(sa, sa + 16384 + rank * 16384, gfull + st * 8, bytes, wm, kc0 + st, wb, am, arow, kc0 + st, amode);
        }
    };
    if (threadIdx.x < 32) {
        if (elect_one()) {
            const uint2 r = p.first[blockIdx.x];
            mbar_init(gfull, 1);
            fence_async_smem();
            const char* maps;
            asm("mov.b64 %0, %1;" : "=l"(maps) : "l"(&p.amap[0]));
            asm volatile("{\n.reg .pred q;\nsetp.eq.u32 q, %8, 0;\n"
                         "mbarrier.arrive.expect_tx.shared::cta.b64 _, [%1], 49152;\n"
                         "cp.async.bulk.tensor.3d.shared::cluster.global.mbarrier::complete_tx::bytes.L2::cache_hint [%9], [%3, {0, 0, %6}], [%1], %11;\n"
                         "cp.async.bulk.tensor.3d.shared::cluster.global.mbarrier::complete_tx::bytes.L2::cache_hint [%10], [%4, {0, 0, %7}], [%1], %11;\n"
                         "@q cp.async.bulk.tensor.3d.shared::cluster.global.mbarrier::complete_tx::bytes.L2::cache_hint [%0], [%2, {0, %5, 0}], [%1], %11;\n"
                         "@!q cp.async.bulk.tensor.4d.shared::cluster.global.mbarrier::complete_tx::bytes.L2::cache_hint [%0], [%2, {0, %5, 0, 0}], [%1], %11;\n}"
                         ::"r"(base), "r"(gfull), "l"(maps + (r.x & 0x780)), "l"(maps + (r.x >> 4 & 0x780)), "l"(maps + (r.x >> 8 & 0x780)),
                           "r"(r.x >> 20), "r"(r.y & 0xffff), "r"(r.y >> 16), "r"(r.x & 1), "r"(base + 16384), "r"(base + 32768), "l"(POL_NORMAL) : "memory");
            asm volatile("fence.mbarrier_init.release.cluster;" ::: "memory");
        }
        __syncwarp();
    }
    const int tid = threadIdx.x, warp = uniform(tid >> 5), lane = tid & 31, wg = warp >> 2;
    if (warp == 1) {
        if (elect_one()) {
#pragma unroll
            for (int i = 1; i < 39; i++)
                mbar_init(bars + i * 8, (0x0CC000F0ull >> i & 1) ? 16 : ((0x300000F00ull >> i & 1) ? 4 : ((0xC0000ull >> i & 1) ? 8 : 1)));
            asm volatile("fence.mbarrier_init.release.cluster;" ::: "memory");
            fence_async_smem();
        }
        __syncwarp();
    }
    setup_arrive();
    if (warp > 3) {
        reg_inc<232>();
        named_sync(0, 352);
        const int w = wg - 1, wwarp = warp & 3;
        const uint32_t slot_a = stage_addr(stg + w * 16384, wwarp, lane);
        const uint32_t bars_peer = uniform(mapa(bars, rank ^ 1));
        auto arrive_pair = [&](uint32_t bar, bool pred = true) INL { warp_arrive_pair(bar, bars_peer + (bar - bars), pred); };
        uint32_t gph = 0;
        uint32_t sph = 1;
        int jb = 0;
        int job = uniform(jobs[0]);
        auto next_job = [&]() INL { jb++; job = uniform(jobs[jb]); };
        auto slot_wait = [&](int q) INL { mbar_wait(sempty + (w * 2 + (q & 1)) * 8, (q >> 1) ^ sph ^ 1); };
        auto signal = [&](int q) INL {
            __syncwarp();
            warp_arrive(sfull + (w * 2 + (q & 1)) * 8);
        };
        uint32_t pk[64];
        float O[64];
        float oscale1 = 1.f;
        uint32_t slot4[4];
        bool ptrans = false;
        auto stage_quarter = [&](const int Q) INL {
            slot_wait(Q);
            if (Q == 0) stage_packed_64x64<0>(slot4, 0, pk, ptrans);
            if (Q == 1) stage_packed_64x64<16>(slot4, 8192, pk, ptrans);
            if (Q == 2) stage_packed_64x64<32>(slot4, 0, pk);
            if (Q == 3) stage_packed_64x64<48>(slot4, 8192, pk);
        };
        auto stage_pair = [&]() INL {
            slot_wait(1);
            stage_packed_64x64<0>(slot4, 0, pk, ptrans);
            stage_packed_64x64<16>(slot4, 8192, pk, ptrans);
        };
        auto signal_both = [&]() INL {
            __syncwarp();
            warp_arrive2(sfull + w * 16, sfull + w * 16 + 8);
        };
        uint32_t un = 0;
        auto lane_id = [&]() INL { uint32_t ln; asm volatile("mov.u32 %0, %%laneid;" : "=r"(ln)); return ln; };
        auto v_addr = [&](uint32_t ln) INL { return stg + w * 16384 + (wwarp * 16 + (ln & 7)) * 128 + (((ln >> 3) ^ (ln & 7)) << 4); };
        auto v_off = [&](uint32_t a, const int h) INL { return (a ^ ((h & 1) * 64)) + (h >> 1) * 8192; };
        auto halo_ptr = [&](int mt, int g, int slot, uint32_t ln) INL { return page_ptr<uint4>(512) + (((mt * 8 + g) * 2 + w) * 5 + slot) * 128 + ln; };
        auto pack_k = [&](const float (&acc)[64]) INL {
#pragma unroll
            for (int j = 0; j < 16; j++) { pk[j] = pack_bf16(acc[4 * j], acc[4 * j + 1]); pk[16 + j] = pack_bf16(acc[4 * j + 2], acc[4 * j + 3]); }
        };
        auto unit_export = [&](int cur) INL {
            const uint32_t ln = lane_id();
            uint4* dst = halo_ptr((cur & 7) * 2 + rank, cur >> 3 & 7, wwarp, ln);
            slot_wait(1);
            stage_packed_64x64<32>(slot4, 0, pk);
            stage_packed_64x64<48>(slot4, 8192, pk);
#pragma unroll
            for (int h = 0; h < 4; h++) __stcg(dst + h * 32, make_uint4(pk[16 + h * 4], pk[17 + h * 4], pk[18 + h * 4], pk[19 + h * 4]));
            __syncwarp();
            if (wwarp == 3) {
                const uint32_t va = v_addr(ln) + 1024;
#pragma unroll
                for (int h = 0; h < 4; h++) {
                    uint32_t t[4];
                    ldmatrix_x4_t(v_off(va, h), t);
                    pk[32 + h * 4] = t[0]; pk[33 + h * 4] = t[1]; pk[34 + h * 4] = t[2]; pk[35 + h * 4] = t[3];
                }
#pragma unroll
                for (int h = 0; h < 4; h++) __stcg(dst + 128 + h * 32, make_uint4(pk[32 + h * 4], pk[33 + h * 4], pk[34 + h * 4], pk[35 + h * 4]));
                __syncwarp();
                warp_arrive(hout + w * 8);
            }
        };
        auto unit_import = [&](int cur) INL {
            const uint32_t ln = lane_id();
            const int mt = (cur & 7) * 2 + rank;
            mbar_wait(lready + un * 8, 0);
            un++;
            const uint4* src = halo_ptr(wwarp ? mt : max(mt - 1, 0), cur >> 3 & 7, (wwarp + 3) & 3, ln);
#pragma unroll
            for (int h = 0; h < 4; h++) {
                const uint4 t = __ldcg(src + h * 32);
                pk[32 + h * 4] = t.x; pk[33 + h * 4] = t.y; pk[34 + h * 4] = t.z; pk[35 + h * 4] = t.w;
            }
            if (wwarp) {
                const uint32_t va = v_addr(ln) - 1024;
#pragma unroll
                for (int h = 0; h < 4; h++) {
                    uint32_t t[4];
                    ldmatrix_x4_t(v_off(va, h), t);
                    pk[48 + h * 4] = t[0]; pk[49 + h * 4] = t[1]; pk[50 + h * 4] = t[2]; pk[51 + h * 4] = t[3];
                }
            } else {
#pragma unroll
                for (int h = 0; h < 4; h++) {
                    const uint4 t = __ldcg(src + 128 + h * 32);
                    pk[48 + h * 4] = t.x; pk[49 + h * 4] = t.y; pk[50 + h * 4] = t.z; pk[51 + h * 4] = t.w;
                }
            }
        };
        auto unit_attend = [&](const float (&q)[64], int cur) INL {
            const float cs = 0.17677669529663687f * 1.4426950408889634f;
            const uint32_t ln = lane_id();
            const int g = ln >> 2, c2 = (ln & 3) * 2, mt = (cur & 7) * 2 + rank;
            uint32_t qf[32], vo[8][4];
#pragma unroll
            for (int i = 0; i < 32; i++) qf[i] = pack_bf16(q[2 * i], q[2 * i + 1]);
            fence_regs(qf);
            const float* gp = page_ptr<float>(520) + mt * 128 + wwarp * 32 + g * 2 + w;
            const float lg0 = 1.f - __ldcg(gp), lg1 = 1.f - __ldcg(gp + 16);
            const uint32_t va = stg + w * 16384 + (wwarp * 16 + (ln & 7) + (ln >> 4) * 8) * 128 + ((((ln >> 3) & 1) ^ (ln & 7)) << 4);
#pragma unroll
            for (int i = 0; i < 8; i++) ldmatrix_x4_t((va ^ ((i & 3) * 32)) + (i >> 2) * 8192, vo[i]);
            const bool m0 = c2 > g, m1 = c2 + 1 > g, first = mt + wwarp == 0;
            const uint32_t mk = (m0 ? 0xffffu : 0u) | (m1 ? 0xffff0000u : 0u);
#pragma unroll
            for (int h = 0; h < 4; h++) {
                float s[3][4] = {};
#pragma unroll
                for (int k = 0; k < 2; k++) {
                    const int i = h * 8 + k * 4, j = h * 4 + k * 2;
                    mma_16816(s[0], qf[i], qf[i + 1], qf[i + 2], qf[i + 3], pk[32 + j], pk[33 + j]);
                    mma_16816(s[1], qf[i], qf[i + 1], qf[i + 2], qf[i + 3], pk[j], pk[j + 1]);
                    mma_16816(s[2], qf[i], qf[i + 1], qf[i + 2], qf[i + 3], pk[16 + j], pk[17 + j]);
                }
                if (first) s[0][0] = s[0][1] = -INFINITY;
                float u0 = m0 ? s[0][0] : s[1][0], u1 = m1 ? s[0][1] : s[1][1], v0 = m0 ? s[1][2] : s[2][2], v1 = m1 ? s[1][3] : s[2][3];
                float mu = fmaxf(u0, u1), mv = fmaxf(v0, v1);
                mu = fmaxf(mu, __shfl_xor_sync(0xffffffffu, mu, 1)); mv = fmaxf(mv, __shfl_xor_sync(0xffffffffu, mv, 1));
                mu = fmaxf(mu, __shfl_xor_sync(0xffffffffu, mu, 2)); mv = fmaxf(mv, __shfl_xor_sync(0xffffffffu, mv, 2));
                mu *= -cs; mv *= -cs;
                u0 = ex2(fmaf(u0, cs, mu)); u1 = ex2(fmaf(u1, cs, mu)); v0 = ex2(fmaf(v0, cs, mv)); v1 = ex2(fmaf(v1, cs, mv));
                float lu = u0 + u1, lv = v0 + v1;
                lu += __shfl_xor_sync(0xffffffffu, lu, 1); lv += __shfl_xor_sync(0xffffffffu, lv, 1);
                lu += __shfl_xor_sync(0xffffffffu, lu, 2); lv += __shfl_xor_sync(0xffffffffu, lv, 2);
                const float su = lg0 * rcp(lu), sv = lg1 * rcp(lv);
                const uint32_t pu = pack_bf16(u0 * su, u1 * su), pv = pack_bf16(v0 * sv, v1 * sv);
#pragma unroll
                for (int d = 0; d < 2; d++) {
                    const uint32_t (&vv)[4] = vo[h * 2 + d];
                    float oa[4] = {}, ob[4] = {};
                    mma_16816(oa, pk[48 + h * 4 + d * 2], pk[49 + h * 4 + d * 2], vv[0], vv[1], pu & mk, pu & ~mk);
                    mma_16816(ob, vv[0], vv[1], vv[2], vv[3], pv & mk, pv & ~mk);
                    qf[h * 8 + d * 4] = pack_bf16(oa[0], oa[1]); qf[h * 8 + d * 4 + 1] = pack_bf16(ob[0], ob[1]);
                    qf[h * 8 + d * 4 + 2] = pack_bf16(oa[2], oa[3]); qf[h * 8 + d * 4 + 3] = pack_bf16(ob[2], ob[3]);
                }
            }
#pragma unroll
            for (int i = 0; i < 32; i++) pk[i] = qf[i];
            named_sync(3 + w, 128);
        };
        auto pack_half = [&](const float (&acc)[64], const int OFF, float scale) INL {
#pragma unroll
            for (int i = 0; i < 32; i++) pk[OFF + i] = pack_bf16(acc[2 * i] * scale, acc[2 * i + 1] * scale);
        };
        auto gemm_run = [&]() INL {
                float acc0[64], acc1[64];
#pragma unroll
                for (int i = 0; i < 64; i++) pk[i] = 0;
#pragma unroll
                for (int j = 0; j < 4; j++) asm volatile("xor.b32 %0, %1, %2;" : "=r"(slot4[j]) : "r"(slot_a), "r"(j << 5));
                const uint32_t dA = desc_lo(base + w * 8192, 0), dB = desc_lo(base + 16384, 8192);
                auto wait_full = [&](int st) INL { mbar_wait_hot(gfull + st * 8, gph); };
                auto release = [&](int st) INL { arrive_pair(gempty + st * 8); };
                bool pend = false;
                auto kstep = [&](auto st_, const int Q, bool ending = false) INL {
                    constexpr int st = decltype(st_)::v, OA = st * (G_STAGE >> 4);
                    const bool held = st == 2 && ending && w;
                    if (st == 2 && __builtin_expect(held, 0)) {
                        wg_wait<0>();
                        release(1);
                        named_sync(6, 256);
                    }
                    wait_full(st);
                    wg_fence();
                    wgmma_ss_n256<OA, OA>(acc0, acc1, dA, dB);
                    wg_commit();
                    wg_wait<1>();
                    arrive_pair(gempty + ((st + 3) & 3) * 8, !held);
                    wg_fence();
                    wgmma_ss_n256<OA + 2, OA + 128>(acc0, acc1, dA, dB);
                    wgmma_ss_n256<OA + 4, OA + 256>(acc0, acc1, dA, dB);
                    if (st == 3) named_arrive_if(ending && !w, 6, 256);
                    wgmma_ss_n256<OA + 6, OA + 384>(acc0, acc1, dA, dB);
                    wg_commit();
                    if (Q >= 0) { stage_quarter(Q); signal(Q); }
                    KTRACE(w);
                };
                wait_full(0);
                GTRACE(w);
                while (true) {
                    wg_fence();
                    wgmma_ss_n256_init(acc0, acc1, dA, dB);
                    wgmma_ss_n256<2, 128>(acc0, acc1, dA, dB);
                    wgmma_ss_n256<4, 256>(acc0, acc1, dA, dB);
                    wgmma_ss_n256<6, 384>(acc0, acc1, dA, dB);
                    wg_commit();
                    KTRACE(w);
                    const int cur = job;
                    const bool is_o = cur >= (T_O << 12), unit2 = (cur >> 6) == 3;
                    const int tail = o_tail(cur);
                    int lim = is_o ? o_head(cur) + tail : (cur < 256 ? 16 : 8);
                    int left = unit2 ? 11 : lim - (is_o ? O_STAGGER + 1 : 1);
                    bool imp = unit2;
                    next_job();
                    if (__builtin_expect(unit2, 0)) { if (tid == TRACE_TID) PTRACE(4); unit_export(cur); if (tid == TRACE_TID) PTRACE(5); }
                    if (pend) {
                        kstep(IC<1>{}, 0);
                        kstep(IC<2>{}, -1);
                        kstep(IC<3>{}, 1);
                        GTRACE(w);
                        gph ^= 1;
                        kstep(IC<0>{}, -1);
                        kstep(IC<1>{}, 2);
                        kstep(IC<2>{}, 3, left == 7);
                        kstep(IC<3>{}, -1, left == 7);
                        GTRACE(w);
                        gph ^= 1;
                        left -= 7;
                        if (left > 0) { kstep(IC<0>{}, -1); left--; }
                    }
                    int last_st = 3;
#pragma unroll 1
                    while (left > 0) {
                        auto ends = [&]() INL -> bool {
                            if (__builtin_expect(--left > 0, 1)) return false;
                            if (is_o) {
                                const uint32_t v = uniform(o_state(olim, lim - tail));
                                const int n = (v >> 1) + ((v & 1) ? 0 : tail);
                                left = n - lim; lim = n;
                            }
                            return left == 0;
                        };
                        kstep(IC<1>{}, -1);
                        if (ends()) { last_st = 1; break; }
                        kstep(IC<2>{}, -1, left == 2 && !is_o && !imp);
                        if (ends()) { last_st = 2; break; }
                        kstep(IC<3>{}, -1, left == 1 && !is_o && !imp);
                        GTRACE(w);
                        gph ^= 1;
                        if (ends()) {
                            if (!imp) break;
                            if (tid == TRACE_TID) PTRACE(6);
                            unit_import(cur);
                            if (tid == TRACE_TID) PTRACE(7);
                            imp = false; left = 4;
                        }
                        kstep(IC<0>{}, -1);
                        if (ends()) { last_st = 0; break; }
                    }
                    if (is_o) {
                        if (w) {
                            wg_wait<0>();
                            release(last_st);
                            named_sync(6, 256);
                        }
#pragma unroll 1
                        for (int i = 1; i <= O_STAGGER; i++) {
                            const int st = (last_st + i) & 3;
                            if (i > 1 && st == 0) gph ^= 1;
                            wait_full(st);
                            const uint32_t a = dA + st * (G_STAGE >> 4), b = dB + st * (G_STAGE >> 4);
                            wg_fence();
                            wgmma_ss_n256<0, 0>(acc0, acc1, a, b);
                            wgmma_ss_n256<2, 128>(acc0, acc1, a, b);
                            wgmma_ss_n256<4, 256>(acc0, acc1, a, b);
                            wgmma_ss_n256<6, 384>(acc0, acc1, a, b);
                            wg_commit();
                            named_arrive_if(!w && i == O_STAGGER, 6, 256);
                            wg_wait<1>();
                            arrive_pair(gempty + last_st * 8, i == 1 && !w);
                        }
                        slot_wait(1);
                        wg_wait<0>();
                        fence_regs(acc0);
                        fence_regs(acc1);
                        auto put = [&](const float (&acc)[64], const int Q, int off) INL {
#pragma unroll
                            for (int j = 0; j < 4; j++) {
                                const float* o = acc + Q * 32 + j * 8;
                                stmatrix_x4(slot4[j] + off, pack_bf16(o[0], o[1]), pack_bf16(o[2], o[3]), pack_bf16(o[4], o[5]), pack_bf16(o[6], o[7]));
                            }
                        };
                        put(acc0, 0, 0);
                        signal(0);
                        put(acc0, 1, 8192);
                        signal(1);
                        put(acc1, 0, -OFF_STG - w * 8192);
                        put(acc1, 1, G_STAGE - OFF_STG - w * 8192);
                        __syncwarp();
                        warp_arrive(tfull + w * 8);
#pragma unroll
                        for (int i = 1; i <= O_STAGGER; i++) release((last_st + i) & 3);
                        GTRACE(w);
#pragma unroll
                        for (int i = 0; i < 64; i++) O[i] = 0.f;
                        break;
                    }
                    if (tid == 128 && !is_o) PTRACE(12);
                    oscale1 = cur < 128 || unit2 ? Q_SCALE : 1.f;
                    ptrans = unit2;
                    if (tid == TRACE_TID && unit2) PTRACE(1);
                    named_arrive_if(w && job >= (T_A << 12), 1, TURN_THREADS);
                    wg_wait<0>();
                    fence_regs(acc0);
                    fence_regs(acc1);
                    release(3);
                    if (tid == TRACE_TID && unit2) PTRACE(2);
                    if (__builtin_expect(unit2, 0)) { unit_attend(acc0, cur); if (tid == TRACE_TID) PTRACE(3); }
                    else if (__builtin_expect((cur >> 6) == 2, 0)) pack_k(acc0);
                    else if (cur < 128) pack_half(acc0, 0, Q_SCALE);
                    else pack_half(acc0, 0, 1.f);
                    if (job >= (T_A << 12)) {
                        stage_pair();
                        signal_both();
#pragma unroll
                        for (int i = 0; i < 64; i++) asm volatile("mul.f32 %0, %1, %2;" : "=f"(O[i]) : "f"(acc1[i]), "f"(oscale1));
                        break;
                    }
                    if (cur < 128 || unit2) pack_half(acc1, 32, Q_SCALE);
                    else pack_half(acc1, 32, 1.f);
                    fence_regs(pk);
                    wait_full(0);
                    pend = (cur >> 6) != 2;
                }
        };
        setup_wait();
#pragma unroll 1
        while (true) {
        gemm_run();
        if (job < 0) break;
        if (tid == 128) PTRACE(11);
        GTRACE(w);
        {
            {
                sph ^= 1;
                uint32_t step = ~0u, ajob = ~0u;
                const int r0 = w * 64 + wwarp * 16 + (lane >> 2);
                float S[64];
                uint32_t P[32] = {};
                fence_regs(P);
                float m0 = 0.f, m1 = 0.f, l0 = 0.25f, l1 = 0.25f, g0 = 1.f, g1 = 1.f, e0 = 0.f, e1 = 0.f;
                constexpr float SUM_MAX = 1.1529215e18f;
                float sum_max = SUM_MAX;
                float sum_min = (lane & 3) == 0 ? 8.6736174e-19f : -1.f;
                asm volatile("" : "+f"(sum_min));
                int rem = 0;
                int maskrem = 0;
                uint32_t starts = 1;
                auto issue_S = [&]() INL {
                    const uint32_t da = desc_lo(base + OFF_Q0 + w * 8192, 0) + (ajob & 1) * ((OFF_Q1 - OFF_Q0) >> 4);
                    const uint32_t db = desc_lo(base + OFF_K0, 0) + (step & 1) * ((OFF_K1 - OFF_K0) >> 4);
                    wg_fence();
                    wgmma_ss_n128_init<0, 0, 0>(S, da, db);
                    wgmma_ss_n128_tb0<2, 2>(S, da, db, 1);
                    wgmma_ss_n128_tb0<4, 4>(S, da, db, 1);
                    wgmma_ss_n128_tb0<6, 6>(S, da, db, 1);
                    wgmma_ss_n128_tb0<1024, 1024>(S, da, db, 1);
                    wgmma_ss_n128_tb0<1026, 1026>(S, da, db, 1);
                    wgmma_ss_n128_tb0<1028, 1028>(S, da, db, 1);
                    wgmma_ss_n128_tb0<1030, 1030>(S, da, db, 1);
                    wg_commit();
                };
                auto issue_PV = [&](uint32_t t, int pass) INL {
                    const uint32_t db = desc_lo(base + OFF_V0, 16384) + (t & 1) * ((OFF_V1 - OFF_V0) >> 4);
                    mbar_wait_hot(vfull + (t & 1) * 8, (t >> 1) & 1);
                    wg_fence();
                    wgmma_rs_n128_tb1<0>(O, P[0], P[1], P[2], P[3], db, !(starts & 2));
                    wgmma_rs_n128_tb1<128>(O, P[4], P[5], P[6], P[7], db, 1);
                    wgmma_rs_n128_tb1<256>(O, P[8], P[9], P[10], P[11], db, 1);
                    wgmma_rs_n128_tb1<384>(O, P[12], P[13], P[14], P[15], db, 1);
                    if (pass) named_arrive(pass, TURN_THREADS);
                    wgmma_rs_n128_tb1<512>(O, P[16], P[17], P[18], P[19], db, 1);
                    wgmma_rs_n128_tb1<640>(O, P[20], P[21], P[22], P[23], db, 1);
                    wgmma_rs_n128_tb1<768>(O, P[24], P[25], P[26], P[27], db, 1);
                    wgmma_rs_n128_tb1<896>(O, P[28], P[29], P[30], P[31], db, 1);
                    wg_commit();
                };
                auto pv_done = [&](uint32_t t) INL {
                    wg_wait<0>();
                    fence_regs(O);
                    arrive_pair(vempty + (t & 1) * 8, t != ~0u);
                };
                auto row_max = [&](float& a0, float& a1) INL {
                    a0 = fmaxf(S[0], S[1]); a1 = fmaxf(S[2], S[3]);
#pragma unroll
                    for (int j = 1; j < 16; j++) {
                        a0 = fmaxf(a0, fmaxf(S[j * 4], S[j * 4 + 1]));
                        a1 = fmaxf(a1, fmaxf(S[j * 4 + 2], S[j * 4 + 3]));
                    }
                    a0 = fmaxf(a0, __shfl_xor_sync(0xffffffffu, a0, 1));
                    a1 = fmaxf(a1, __shfl_xor_sync(0xffffffffu, a1, 1));
                    a0 = fmaxf(a0, __shfl_xor_sync(0xffffffffu, a0, 2));
                    a1 = fmaxf(a1, __shfl_xor_sync(0xffffffffu, a1, 2));
                };
                auto mask_diag = [&]() INL {
                    const int d = (r0 & 63) - (lane & 3) * 2;
                    auto mask_block = [&](const int J0) INL {
                        bool up0 = false, up1 = false;
#pragma unroll
                        for (int j = 0; j < 8; j++) {
                            const bool c0 = j * 8 > d, c1 = j * 8 + 1 > d;
                            if (c0) S[(J0 + j) * 4] = -INFINITY;
                            if (c1) S[(J0 + j) * 4 + 1] = -INFINITY;
                            if (up0) S[(J0 + j) * 4 + 2] = -INFINITY;
                            if (up1) S[(J0 + j) * 4 + 3] = -INFINITY;
                            up0 = c0; up1 = c1;
                        }
                    };
                    if (w) {
                        mask_block(8);
                    } else {
                        mask_block(0);
#pragma unroll
                        for (int i = 32; i < 64; i++) S[i] = -INFINITY;
                    }
                };
                auto exp_part = [&](float& t0, float& t1, const int J0, const int J1, const bool SUB) INL {
#pragma unroll
                    for (int j = J0; j < J1; j++) {
                        const float e0 = ex2(SUB ? S[j * 4] - m0 : S[j * 4]), e1 = ex2(SUB ? S[j * 4 + 1] - m0 : S[j * 4 + 1]);
                        const float e2 = ex2(SUB ? S[j * 4 + 2] - m1 : S[j * 4 + 2]), e3 = ex2(SUB ? S[j * 4 + 3] - m1 : S[j * 4 + 3]);
                        t0 = (j ? t0 : l0) + (e0 + e1);
                        t1 = (j ? t1 : l1) + (e2 + e3);
                        P[j * 2] = pack_bf16(e0, e1);
                        P[j * 2 + 1] = pack_bf16(e2, e3);
                    }
                };
                auto exp_head = [&](float& t0, float& t1, auto j1_) INL {
                    constexpr int J1 = decltype(j1_)::v;
                    float E[J1 * 4];
#pragma unroll
                    for (int j = 0; j < J1; j++) {
#pragma unroll
                        for (int e = 0; e < 4; e++) E[j * 4 + e] = ex2(S[j * 4 + e]);
                        t0 = (j ? t0 : l0) + (E[j * 4] + E[j * 4 + 1]);
                        t1 = (j ? t1 : l1) + (E[j * 4 + 2] + E[j * 4 + 3]);
                    }
                    order_after(t0 + t1, bars + 508);
                    pv_done(step - 1);
                    fence_regs(P);
                    fence_regs(S);
                    fence_regs(E);
#pragma unroll
                    for (int i = 0; i < J1 * 2; i++) P[i] = pack_bf16(E[i * 2], E[i * 2 + 1]);
                };
                auto close_job = [&]() INL {
                    l0 += __shfl_xor_sync(0xffffffffu, l0, 1); l1 += __shfl_xor_sync(0xffffffffu, l1, 1);
                    l0 += __shfl_xor_sync(0xffffffffu, l0, 2); l1 += __shfl_xor_sync(0xffffffffu, l1, 2);
                    e0 = g0 * rcp(l0); e1 = g1 * rcp(l1);
                };
                auto put_O = [&]() INL {
                    mbar_wait_hot(sempty + (w * 2 + 1) * 8, sph ^ 1);
                    uint32_t a[4];
#pragma unroll
                    for (int j = 0; j < 4; j++) asm volatile("xor.b32 %0, %1, %2;" : "=r"(a[j]) : "r"(slot_a), "r"(j << 5));
                    const uint32_t h0 = pack_bf16(e0, e0), h1 = pack_bf16(e1, e1);
#pragma unroll
                    for (int q = 0; q < 8; q++) {
                        const float* o = O + q * 8;
                        stmatrix_x4(a[q & 3] + (q >> 2) * 8192, mul_bf16x2(pack_bf16(o[0], o[1]), h0), mul_bf16x2(pack_bf16(o[2], o[3]), h1),
                                    mul_bf16x2(pack_bf16(o[4], o[5]), h0), mul_bf16x2(pack_bf16(o[6], o[7]), h1));
                    }
                    sph ^= 1;
                    signal_both();
                };
                auto exp_plain = [&](float& t0, float& t1) INL {
                    exp_head(t0, t1, IC<5>{});
                    exp_part(t0, t1, 5, 16, false);
                    fence_regs(P);
                };
                auto exp_diag = [&](float& t0, float& t1) INL {
                    const int d = warp - 4, dd = (r0 & 7) - (int)(slot_a >> 6 & 6);
                    auto tri = [&](const int B) INL {
                        if (0 > dd) S[8 * B] = S[8 * B + 6] = -INFINITY;
                        if (1 > dd) S[8 * B + 1] = S[8 * B + 7] = -INFINITY;
                        S[8 * B + 4] = S[8 * B + 5] = -INFINITY;
                        asm volatile("" ::: "memory");
                    };
                    auto blocks = [&](const int B) INL {
                        auto zero = [&](const int B0) INL {
#pragma unroll
                            for (int i = 4 * B0; i < 4 * B + 12; i++) P[i] = 0;
                            asm volatile("" ::: "memory");
                        };
                        auto block = [&](const int B0) INL { exp_part(t0, t1, 2 * B0, 2 * B0 + 2, false); asm volatile("" ::: "memory"); };
                        if (d < B) zero(B);
                        else {
                            block(B);
                            if (d < B + 1) zero(B + 1);
                            else {
                                block(B + 1);
                                if (d < B + 2) zero(B + 2); else block(B + 2);
                            }
                        }
                    };
                    if (d > 3) {
                        if (d < 6) { if (d == 4) tri(4); else tri(5); } else { if (d == 6) tri(6); else tri(7); }
                        exp_head(t0, t1, IC<5>{});
                        exp_part(t0, t1, 5, 10, false);
                        blocks(5);
                    } else {
                        if (d < 2) { if (d == 0) tri(0); else tri(1); } else { if (d == 2) tri(2); else tri(3); }
                        exp_head(t0, t1, IC<2>{});
#pragma unroll
                        for (int i = 16; i < 32; i++) P[i] = 0;
                        blocks(1);
                    }
                    fence_regs(P);
                };
                auto unsafe_tile = [&](float t0, float t1) INL -> bool {
                    const bool unsafe = !(t0 + t1 <= sum_max) | !(fminf(t0, t1) >= sum_min);
                    return __any_sync(0xffffffffu, unsafe);
                };
                auto redo_tile = [&](float& t0, float& t1, bool fresh) INL {
                    wg_wait<0>();
                    fence_regs(O);
                    if (rem == maskrem) mask_diag();
                    float a0, a1;
                    row_max(a0, a1);
                    if (!fresh) { a0 = fmaxf(a0, m0); a1 = fmaxf(a1, m1); }
                    const float c0 = fresh ? 1.f : ex2(m0 - a0), c1 = fresh ? 1.f : ex2(m1 - a1);
                    m0 = a0; m1 = a1; sum_max = -1.f;
                    l0 *= c0; l1 *= c1;
#pragma unroll
                    for (int j = 0; j < 16; j++) { O[j * 4] *= c0; O[j * 4 + 1] *= c0; O[j * 4 + 2] *= c1; O[j * 4 + 3] *= c1; }
                    exp_part(t0, t1, 0, 16, true);
                };
                auto finish = [&]() INL {
                    if (starts & 2) put_O();
                    named_sync(1 + w, TURN_THREADS);
                    TRACE_MARK(0, w, step + 1);
                    issue_PV(step, w == 0 ? 2 : 0);
                    close_job();
                    pv_done(step);
                    put_O();
                };
                int njob;
                auto open_job = [&]() INL {
                    ajob++; rem = (job & 15) + 1; maskrem = (job & 512) ? 0 : job & 15;
                    njob = jobs[jb + 1];
                };
                auto do_step = [&]() INL -> bool {
                    float t0, t1;
                    const bool fresh = starts & 1, pending = starts & 2;
                    rem--; step++;
                    named_sync(1 + w, TURN_THREADS);
                    TRACE_MARK(0, w, step);
                    issue_S();
                    if (__builtin_expect(pending || fresh, 0)) {
                        if (pending) put_O();
                        if (fresh) {
                            close_job();
                            g0 = __ldcg(g_gate + (job & 15) * 128 + r0); g1 = __ldcg(g_gate + (job & 15) * 128 + r0 + 8);
                            l0 = 0.f; l1 = 0.f; m0 = 0.f; m1 = 0.f; sum_max = SUM_MAX;
                            if (step == 0) {
                                wg_fence();
                                wg_commit();
                                named_arrive(2 - w, TURN_THREADS);
                                goto issued;
                            }
                        }
                    }
                    issue_PV(step - 1, 2 - w);
                issued:
                    starts = (starts << 1 & 2) | (rem == 0);
                    TRACE_MARK(1, w, step);
                    wg_wait<1>();
                    fence_regs(S);
                    arrive_pair(kempty + (step & 1) * 8);
                    TRACE_MARK(2, w, step);
                    warp_arrive(qempty + (ajob & 1) * 8, rem == 0);
                    bool bad;
                    if (__builtin_expect(rem != maskrem, 1)) {
                        exp_plain(t0, t1);
                        bad = unsafe_tile(t0, t1);
                        if (__builtin_expect(!bad && rem != 0, 1)) {
                            l0 = t0; l1 = t1;
                            TRACE_MARK(3, w, step);
                            return true;
                        }
                    } else {
                        exp_diag(t0, t1);
                        bad = unsafe_tile(t0, t1);
                    }
                    if (bad) redo_tile(t0, t1, fresh);
                    l0 = t0; l1 = t1;
                    TRACE_MARK(3, w, step);
                    if (rem == 0) {
                        jb++;
                        job = uniform(njob);
                        if ((job >> 12) != T_A) return false;
                        open_job();
                    }
                    return true;
                };
                open_job();
#pragma unroll 1
                while (do_step()) {}
                finish();
            }
        }
        GTRACE(w);
        jb = uniform(jb); job = uniform(job); sph = uniform(sph); gph = uniform(gph);
        if (job < 0) break;
        }
    } else {
        reg_dec<40>();
        if (base & 1023) __trap();
        if (warp == 0) {
            const uint2 r = p.first[blockIdx.x];
            const char* maps = reinterpret_cast<const char*>(&p.amap[0]);
            const CUtensorMap* wm = reinterpret_cast<const CUtensorMap*>(maps + (r.x >> (rank ? 8 : 4) & 0x780));
            const CUtensorMap* am = reinterpret_cast<const CUtensorMap*>(maps + (r.x & 0x780));
            const int wb = rank ? r.y >> 16 : r.y & 0xffff;
            setup_wait();
#pragma unroll 1
            for (int st = 1; st < 4; st++) {
                const uint32_t sa = base + st * G_STAGE;
                load_kstep(sa, sa + 16384 + rank * 16384, gfull + st * 8, G_STAGE, wm, st, wb, am, r.x >> 20, st, 1 + (r.x & 1));
            }
            named_sync(7, 96);
        } else {
            if (warp == 2) {
                const int jl = lane < MAX_JOBS ? p.jobs[blockIdx.x][lane] : -1;
                if (lane <= MAX_JOBS) jobs[lane] = jl;
                if ((jl >> 12) == T_O) *reinterpret_cast<volatile uint32_t*>(smem_raw + OFF_BAR + 504) = 2 * o_head(jl);
                if (lane == 31) *reinterpret_cast<volatile uint32_t*>(smem_raw + OFF_BAR + 528) = 0;
            } else if (warp == 3) {
                if (lane == 31) *reinterpret_cast<ulonglong2*>(smem_raw + OFF_BAR + 512) = make_ulonglong2((uint64_t)g_halo, (uint64_t)g_gate);
                if (lane < MAX_ROUNDS / 2) rounds[lane] = reinterpret_cast<const uint32_t*>(p.rounds[blockIdx.x >> 1])[lane];
            }
            named_arrive_if(warp > 1, 7, 96);
            named_sync(0, 352);
            setup_wait();
        }
        volatile uint32_t* epoch_word = reinterpret_cast<volatile uint32_t*>(smem_raw + OFF_BAR + 532);
        uint32_t epoch1 = 0;
        if (warp > 0) {
        if (warp == 3) { epoch1 = uniform(ld_acquire(g_flags + F_DONE)) / NUM_SMS + 1; if (lane == 0) *epoch_word = epoch1; }
        {
            if (warp == 1 && elect_one()) {
#pragma unroll
                for (int i = 0; i < 7; i++) prefetch_map(&p.amap[0] + i);
            }
            __syncwarp();
            if (warp < 3) __nanosleep(jobs[0] < 256 ? GATE_DELAY_LONG_NS : GATE_DELAY_SHORT_NS);
            if (tid == TRACE_GATE) PTRACE(10);
            float* gate_vals = reinterpret_cast<float*>(smem_raw + OFF_BAR + 576);
            if (warp == 3) {
                if (blockIdx.x == 0) g_flags[F_SPLIT + lane] = g_flags[F_TICKET + lane] = 0;
                named_sync(5, 96);
                if (lane < 16 && blockIdx.x + lane * NUM_SMS < SEQ) g_gate[blockIdx.x + lane * NUM_SMS] = 1.f / (1.f + __expf(-gate_vals[lane]));
                if (tid == TRACE_GATE) PTRACE(9);
                __threadfence();
                __syncwarp();
                if (lane == 0) red_release(g_flags + F_GATE);
            } else {
                const uint32_t bar = gatefull + (warp - 1) * 16;
                auto fetch = [&](int r) INL {
                    if (lane == 0) mbar_expect_tx(bar + (r & 2) * 4, 4096);
                    __syncwarp();
                    if (lane < 2) asm volatile("cp.async.bulk.shared::cluster.global.mbarrier::complete_tx::bytes [%0], [%1], 2048, [%2];"
                                               ::"r"(stg + ((warp - 1) * 8 + r + lane) * 2048), "l"(p.xp + (size_t)min((int)blockIdx.x + ((warp - 1) * 8 + r + lane) * NUM_SMS, SEQ - 1) * DM), "r"(bar + (r & 2) * 4) : "memory");
                };
                fetch(0); fetch(2);
                uint32_t gw[16];
#pragma unroll
                for (int i = 0; i < 4; i++) {
                    const uint4 t = __ldg(reinterpret_cast<const uint4*>(p.gate_w) + i * 32 + lane);
                    gw[i * 4] = t.x; gw[i * 4 + 1] = t.y; gw[i * 4 + 2] = t.z; gw[i * 4 + 3] = t.w;
                }
#pragma unroll 1
                for (int r = 0; r < 8; r += 2) {
                    mbar_wait(bar + (r & 2) * 4, r >> 2);
                    if (r < 4) fetch(r + 4);
                    fence_regs(gw);
                    float acc0 = 0.f, acc1 = 0.f;
                    uint32_t ln;
                    asm volatile("mov.u32 %0, %%laneid;" : "=r"(ln));
#pragma unroll
                    for (int i = 0; i < 4; i++) {
                        const uint4* xr = reinterpret_cast<const uint4*>(smem_raw + OFF_STG + ((warp - 1) * 8 + r) * 2048) + i * 32 + ln;
                        const uint4 a = xr[0], c = xr[128];
                        const uint32_t av[4] = {a.x, a.y, a.z, a.w}, cv[4] = {c.x, c.y, c.z, c.w};
#pragma unroll
                        for (int e = 0; e < 4; e++) {
                            const float lo = __uint_as_float(gw[i * 4 + e] << 16), hi = __uint_as_float(gw[i * 4 + e] & 0xffff0000u);
                            acc0 = fmaf(__uint_as_float(av[e] << 16), lo, acc0);
                            acc1 = fmaf(__uint_as_float(cv[e] << 16), lo, acc1);
                            acc0 = fmaf(__uint_as_float(av[e] & 0xffff0000u), hi, acc0);
                            acc1 = fmaf(__uint_as_float(cv[e] & 0xffff0000u), hi, acc1);
                        }
                    }
                    float t = (lane < 16 ? acc0 : acc1) + __shfl_xor_sync(0xffffffffu, lane < 16 ? acc1 : acc0, 16);
#pragma unroll
                    for (int o = 8; o > 0; o >>= 1) t += __shfl_xor_sync(0xffffffffu, t, o);
                    if ((lane & 15) == 0) gate_vals[(warp - 1) * 8 + r + (lane >> 4)] = t;
                }
                uint32_t t2;
                asm volatile("mov.u32 %0, %%tid.x;" : "=r"(t2));
                warp_arrive2(sempty - 16 + (t2 >> 5) * 16, sempty - 8 + (t2 >> 5) * 16);
                named_arrive(5, 96);
                if (tid == TRACE_GATE) PTRACE(9);
            }
            if (tid == TRACE_GATE) PTRACE(8);
        }
        if (warp < 3) {
            if (elect_one()) {
                const int w = warp - 1;
                uint32_t qn = 0, un = 0;
                prefetch_map(&p.qkv_st); prefetch_map(&p.st_par);
                for (int jb = 0; jb < MAX_JOBS; jb++) {
                    const int job = jobs[jb];
                    if (job < 0) break;
                    const int type = job >> 12, pl = type == T_O ? o_state(otile, 0) >> 1 : job & 0xFFF;
                    const CUtensorMap* map = &p.qkv_st;
                    int nq = 4, mt, ob0, ob1, flag, flag2 = -1;
                    bool par = false;
                    if (type <= T_O) {
                        const int n = pl >> 3;
                        mt = (pl & 7) * 2 + rank;
                        if (type == T_O)  {
                            map = &p.out_st; ob0 = (n & 3) * 4; ob1 = ob0 + 2; flag = -1;
                            for (uint32_t tries = 0; (int32_t)(ld_acquire(g_flags + F_OUT + pl * 2 + rank) - *epoch_word) < 0; tries++) {
                                __nanosleep(300);
                                if (tries > (1u << 22)) __trap();
                            }
                            fence_async_global();
                        }
                        else if (n < 16)  { ob0 = n * 4; ob1 = ob0 + 2; flag = F_Q + n * 32 + mt; flag2 = flag + 16; }
                        else if (n < 24)  {
                            mbar_wait(hout + w * 8, un++ & 1);
                            nq = ob0 = ob1 = 0; flag = F_H + mt * 8 + (n & 7);
                        } else if (n < 32) {
                            par = true; ob0 = 192 + (n & 7) * 2; ob1 = unit_head(n & 7) * 2;
                            flag = F_CTX + mt * 40 + 32 + (n & 7); flag2 = F_Q + ob1 * 8 + mt;
                        } else            { ob0 = n * 2; ob1 = ob0 + 64; flag = F_KV + (n - 32) * 16 + mt; }
                    } else {
                        nq = 2; mt = pl & 15; ob0 = ob1 = ((pl >> 4) & 31) * 2; flag = F_CTX + mt * 40 + ((pl >> 4) & 31);
                    }
                    for (int q = 0; q < nq; q++, qn++) {
                        const uint32_t slot = w * 2 + (qn & 1);
                        const int blk = (q < 2 ? ob0 : ob1) + (q & 1);
                        if (type == T_O && q == 2) {
                            mbar_wait(tfull + w * 8, 0);
                            fence_async_smem();
                            tma_reduce_add_3d(map, base + w * 8192, 0, mt * 128 + w * 64, ob1);
                            tma_reduce_add_3d(map, base + G_STAGE + w * 8192, 0, mt * 128 + w * 64, ob1 + 1);
                            bulk_commit();
                            break;
                        }
                        mbar_wait(sfull + slot * 8, (qn >> 1) & 1);
                        fence_async_smem();
                        if (type == T_O) {
                            tma_reduce_add_3d(map, stg + slot * 8192, 0, mt * 128 + w * 64, blk);
                        } else if (par) {
                            tma_store_par(&p.st_par, stg + slot * 8192, mt * 64, w, blk);
                        } else {
                            tma_store_3d(map, stg + slot * 8192, 0, mt * 128 + w * 64, blk, POL_STREAM);
                        }
                        bulk_commit();
                        if (type == T_O) continue;
                        if (!(q & 1)) continue;
                        bulk_wait_read<1>();
                        mbar_arrive(sempty + (slot ^ 1) * 8);
                        bulk_wait_read<0>();
                        mbar_arrive(sempty + slot * 8);
                    }
                    bulk_wait<0>();
                    END_MARK(jb);
                    if (flag >= 0) {
                        asm volatile("fence.release.gpu;" ::: "memory");
                        red_relaxed(g_flags + flag);
                        if (flag2 >= 0) red_relaxed(g_flags + flag2);
                    }
                }
            }
        } else {
            int jb = 0;
            for (int un = 0; (jobs[jb] >> 12) == T_P; jb++) {
                const int n = jobs[jb] >> 3, mt = (jobs[jb] & 7) * 2 + rank;
                if ((n >> 3) != 3) continue;
                wait_flags<200>(lane == 31 || (lane == 0 && mt > 0), lane == 31 ? F_GATE : F_H + max(mt - 1, 0) * 8 + (n & 7),
                                epoch1 * (lane == 31 ? GATE_COUNT : 2));
                if (lane == 0) mbar_arrive(lready + un * 8);
                un++;
            }
            if ((jobs[jb] >> 12) != T_A) {
                wait_flags<200>(lane == 0, F_GATE, epoch1 * GATE_COUNT);
                if (lane == 0) { mbar_arrive(aready); red_relaxed(g_flags + F_DONE); }
            } else {
                const int jh = jobs[jb] >> 4 & 31, jq = jobs[jb] & 15;
                wait_flags<100>(lane <= jq || lane >= 30, lane == 31 ? F_GATE : (lane == 30 ? F_Q + jh * 16 + jq : F_KV + jh * 16 + (lane & 15)),
                                epoch1 * (lane == 31 ? GATE_COUNT : 2));
                if (lane == 0) { mbar_arrive(aready); red_relaxed(g_flags + F_DONE); }
            int left = 0, nxt = jobs[jb];
            uint32_t ajob = 0;
#pragma unroll 1
            for (uint32_t astep = 0;; astep++) {
                if (left == 0) {
                    if ((nxt >> 12) != T_A) break;
                    left = (nxt & 15) + 1;
                    nxt = jobs[++jb];
                    mbar_wait(qfull + (ajob & 1) * 8, (ajob >> 1) & 1);
                    ajob++;
                }
                left--;
                mbar_wait(kfull + (astep & 1) * 8, (astep >> 1) & 1);
                named_sync(1, TURN_THREADS);
                named_sync(2, TURN_THREADS);
            }
            named_sync(1, TURN_THREADS);
            named_sync(2, TURN_THREADS);
            }
            if (jobs[jb] == (T_O << 12)) {
                mbar_wait(gatefull, 0);
                const int tile = o_state(otile, 0) >> 1;
                uint4* dst = reinterpret_cast<uint4*>(p.out) + ((tile & 7) * 256 + rank * 128) * (DM / 8) + (tile >> 3) * 32 + lane;
#pragma unroll 4
                for (int r = 0; r < 128; r++) {
                    dst[r * (DM / 8)] = make_uint4(0, 0, 0, 0);
                    if ((r & 3) == 3) __nanosleep(CLEAR_GAP_NS);
                }
                __threadfence();
                fence_async_global();
                __syncwarp();
                if (lane == 0) red_release(g_flags + F_OUT + tile * 2 + rank);
            }
        }
        } else {
            uint32_t gph = 1;
            int vrow = 0, vblk = 0;
            bool vsolo = false;
            auto load_kv = [&](uint32_t dst, uint32_t bar, int row, int blk, bool solo) INL {
                load_operand(dst, bar, &p.qkv_ld, &p.qkv_half, row, blk, rank, solo, POL_NORMAL);
            };
            auto load_v = [&](uint32_t t) INL {
                if (t == 0) mbar_wait(gempty + 24, gph);
                mbar_wait(vempty + (t & 1) * 8, ((t >> 1) & 1) ^ 1);
                load_kv(base + ((t & 1) ? OFF_V1 : OFF_V0), vfull + (t & 1) * 8, vrow, vblk, vsolo);
            };
            int jb = __ffs(__ballot_sync(0xffffffffu, lane <= MAX_JOBS && (jobs[min(lane, MAX_JOBS)] >> 12) != T_P)) - 1;
            int cur = uniform(jobs[jb]);
            auto announce = [&](uint32_t word, uint32_t v) INL {
                asm volatile("{\n.reg .pred p;\nsetp.lt.u32 p, %2, 2;\n@p red.relaxed.cluster.shared::cluster.max.u32 [%0], %1;\n}"
                             ::"r"(mapa(word, lane & 1)), "r"(v), "r"(lane) : "memory");
                __syncwarp();
            };
            uint32_t ticket = 0;
            auto draw_ticket = [&](int ojob) INL {
                asm volatile("{\n.reg .pred p;\nsetp.ne.u32 p, %2, 0;\n@p atom.relaxed.gpu.global.inc.u32 %0, [%1], 0x7fffffff;\n}"
                             : "+r"(ticket) : "l"(g_flags + F_TICKET + (ojob >> 5 & 1)), "r"((uint32_t)(rank == 0 && lane == 0)) : "memory");
                __syncwarp();
            };
            int pl = 0;
            uint32_t seen_a = 0, seen_b = 0;
            auto ask_ctx = [&]() INL {
                const uint32_t* f = g_flags + F_CTX + ((pl & 7) * 2 + rank) * 40;
                seen_a = ld_relaxed(f + lane); seen_b = ld_relaxed(f + 32 + (lane & 7));
            };
            auto open_tile = [&](int ojob) INL {
                if (rank == 0) {
                    const uint32_t t = uniform(ticket);
                    announce(otile, 2 * ((ojob & 32) ? 31 - t : t) + 1);
                }
                pl = (ojob & 32) | uniform(o_state(otile, 0) >> 1);
                ask_ctx();
            };
            const uint16_t* recs = reinterpret_cast<const uint16_t*>(rounds);
            uint32_t rec = uniform(recs[0]), nrec = uniform(recs[1]);
            int st0 = 4;
#pragma unroll 1
            for (int r = 2; rec != 0xFFFF; r++) {
                const uint32_t nnrec = recs[r];
                load_round(rec, st0, gph);
                gph ^= 1;
                st0 = 0;
                rec = nrec; nrec = uniform(nnrec);
                if (nrec == 0xFFFF || (rec & 8192)) {
                    if (nrec != 0xFFFF) {
                        prefetch_map(&p.qkv_ld); prefetch_map(&p.qkv_half);
                        if ((cur >> 12) == T_O) { prefetch_map(&p.wo_a); prefetch_map(&p.wo_b); prefetch_map(&p.out_st); }
                    } else if ((cur >> 12) == T_O) {
                        if (rec != 0xFFFF) {
                            mbar_wait(aready, 0);
                            draw_ticket(cur);
                        } else {
                            open_tile(cur);
                        }
                    }
                }
            }
            int nxt = cur;
            uint32_t astep = 0;
            if ((cur >> 12) == T_A) {
            {
                const int jh = cur >> 4 & 31, jq = cur & 15, j0 = (cur & 512) ? 0 : jq;
                mbar_wait(aready, 0);
                fence_async_global();
                mbar_wait(gempty, gph);
                load_operand(base + OFF_Q0, qfull, &p.qkv_ld, &p.qkv_ld, jq * 128, jh * 2, 0, true, POL_STREAM);
                PTRACE(17);
                mbar_wait(gempty + 8, gph);
                load_kv(base + OFF_K0, kfull, j0 * 128, 64 + jh * 2, j0 == jq && (jq & 1));
                PTRACE(16);
            }
            epoch1 = *epoch_word;
            jb++;
            nxt = uniform(jobs[jb]);
            int i = 0;
            uint32_t ajob = 1;
            bool q_issued = false;
#pragma unroll 1
            while (true) {
                const int qt = cur & 15;
                const bool last = i == qt;
                const int j = (cur & 512) ? i : qt - i, blk = (cur >> 4 & 31) * 2;
                const bool solo = j == qt && (qt & 1);
                {
                    const uint32_t sl = astep & 1;
                    if (astep == 0) {
                        mbar_wait(gempty + 16, gph);
                    } else {
                        mbar_wait(kempty + sl * 8, ((astep >> 1) & 1) ^ 1);
                        load_kv(base + (sl ? OFF_K1 : OFF_K0), kfull + sl * 8, j * 128, 64 + blk, solo);
                        if (astep == 1) PTRACE(14);
                        load_v(astep - 1);
                        if (astep == 1) PTRACE(15);
                    }
                }
                vrow = j * 128; vblk = 128 + blk; vsolo = solo;
                astep++;
                if ((nxt >> 12) != T_A) {
                    if (last) break;
                } else if (!q_issued && (last || i == 2 || (i > 2 && i >= qt - 2))) {
                    const int jh = nxt >> 4 & 31, jq = nxt & 15;
                    q_issued = wait_flags(lane <= jq || lane >= 30, lane == 31 ? F_GATE : (lane == 30 ? F_Q + jh * 16 + jq : F_KV + jh * 16 + (lane & 15)),
                                          epoch1 * (lane == 31 ? GATE_COUNT : 2), last);
                    if (q_issued) {
                        mbar_wait(qempty + (ajob & 1) * 8, ((ajob >> 1) & 1) ^ 1);
                        load_operand(base + ((ajob & 1) ? OFF_Q1 : OFF_Q0), qfull + (ajob & 1) * 8, &p.qkv_ld, &p.qkv_ld, jq * 128, jh * 2, 0, true, POL_STREAM);
                    }
                }
                i++;
                if (last) {
                    cur = nxt; jb++; nxt = uniform(jobs[jb]); i = 0; ajob++; q_issued = false;
                    if ((nxt >> 12) == T_O) { prefetch_map(&p.wo_a); prefetch_map(&p.wo_b); prefetch_map(&p.out_st); }
                }
            }
            if (nxt >= 0) draw_ticket(nxt);
            load_v(astep - 1);
            if (nxt >= 0) open_tile(nxt);
            }
            int nks = 0;
            if (nxt >= 0) {
                epoch1 = *epoch_word;
                const int m0 = (pl & 7) * 256 + rank * 128, nb = (pl >> 3 & 3) * 4 + rank * 2, part = pl >> 5 & 1;
                uint32_t ready_a = 0, ready_b = 0;
                uint32_t claim_even = 0, claim_odd = 0;
                const int head = o_head(pl), tail = o_tail(pl);
                int lim = head;
                bool known = false;
#pragma unroll 1
                for (int ks = 0;; ks++) {
                    const int st = ks & 3;
                    if (rank == 0) {
                        auto exchange = [&](uint32_t& claim) INL {
                            if (ks + 1 >= head) {
                                known = (uint32_t)uniform(claim) >= O_FLEX;
                                if (!known) lim = ks + 2;
                                announce(olim, known ? 2 * (lim + tail) + 1 : 2 * lim);
                            }
                            asm volatile("{\n.reg .pred p;\nsetp.ne.u32 p, %2, 0;\n@p atom.relaxed.gpu.global.inc.u32 %0, [%1], 0x7fffffff;\n}"
                                         : "+r"(claim) : "l"(g_flags + F_SPLIT + (pl & 31)), "r"((uint32_t)(!known && lane == 0)) : "memory");
                            __syncwarp();
                        };
                        if (!known && ks + 3 >= head) { if (ks & 1) exchange(claim_odd); else exchange(claim_even); }
                    } else if (!known && ks >= lim) {
                        const uint32_t v = uniform(o_state(olim, ks));
                        known = v & 1;
                        lim = (v >> 1) - (known ? tail : 0);
                    }
                    if (ks >= lim + tail) { nks = ks; break; }
                    if (ks == CLEAR_KS && !part) warp_arrive(gatefull);
                    int acol;
                    if (ks >= lim) acol = (part ? 64 - O_T1 : 200) + ks - lim;
                    else if (part) acol = ks < O_H1 ? O_F0 + ks : O_F0 + 2 * O_H1 + O_FLEX - 1 - ks;
                    else acol = ks < 8 ? 192 + ks : (ks < O_H0 ? ks - 8 : ks - 8 + O_H1);
                    for (uint32_t tries = 0; !(((acol < 192 ? ready_a : ready_b) >> (acol >> 1 & 31)) & 1); tries++) {
                        if (ks | tries) ask_ctx();
                        ready_a = __ballot_sync(0xffffffffu, (int32_t)(seen_a - epoch1 * 2) >= 0);
                        ready_b = __ballot_sync(0xffffffffu, (int32_t)(seen_b - epoch1 * 2) >= 0);
                        fence_acquire();
                        trap_if(tries > (1u << 22));
                    }
                    {
                        const uint32_t sa = base + st * G_STAGE;
                        if (ks < 4 && astep) mbar_wait((ks < 2 ? kempty : vempty) + ((astep - 1) & 1) * 8, ((astep - 1) >> 1) & 1);
                        else mbar_wait(gempty + st * 8, gph);
                        load_kstep(sa, sa + 16384 + rank * 16384, gfull + st * 8, G_STAGE, acol >= 192 ? &p.wo_b : &p.wo_a, acol & 63, nb,
                                   &p.qkv_half, m0, acol, 1);
                    }
                    if (st == 3) gph ^= 1;
                }
            }
            if (lane == 0) {
                if (nxt >= 0) for (int s = 0; s < 4; s++) mbar_wait(gempty + s * 8, gph ^ (s < (nks & 3)));
                else for (uint32_t t = astep; t < astep + 2; t++) {
                    mbar_wait(kempty + (t & 1) * 8, ((t >> 1) & 1) ^ 1);
                    mbar_wait(vempty + (t & 1) * 8, ((t >> 1) & 1) ^ 1);
                }
            }
        }
    }
}

typedef CUresult (*EncodeFn)(CUtensorMap*, CUtensorMapDataType, cuuint32_t, void*, const cuuint64_t*, const cuuint64_t*,
                             const cuuint32_t*, const cuuint32_t*, CUtensorMapInterleave, CUtensorMapSwizzle,
                             CUtensorMapL2promotion, CUtensorMapFloatOOBfill);

void make_map3(EncodeFn enc, CUtensorMap* m, const void* ptr, int rows, int cols, int box_rows, int box_blks, bool blocked = false) {
    cuuint64_t dims[3] = {64, (cuuint64_t)rows, (cuuint64_t)(cols / 64)};
    cuuint64_t strides[2] = {blocked ? 128 : (cuuint64_t)cols * 2, blocked ? (cuuint64_t)rows * 128 : 128};
    cuuint32_t box[3] = {64, (cuuint32_t)box_rows, (cuuint32_t)box_blks};
    cuuint32_t es[3] = {1, 1, 1};
    enc(m, CU_TENSOR_MAP_DATA_TYPE_BFLOAT16, 3, const_cast<void*>(ptr), dims, strides, box, es, CU_TENSOR_MAP_INTERLEAVE_NONE,
        CU_TENSOR_MAP_SWIZZLE_128B, CU_TENSOR_MAP_L2_PROMOTION_L2_256B, CU_TENSOR_MAP_FLOAT_OOB_FILL_NONE);
}

Params h_params;

const int16_t k_jobs[NUM_SMS][MAX_JOBS] = {
    {339,153,217,8890,8339,8802,8311,9042,8405,9008,8551,9134,8677,4128,-1,-1,-1,-1,-1,-1,-1,-1,-1,-1},
    {339,153,217,8891,8338,8803,8310,9043,8404,9009,8550,9135,8676,4128,-1,-1,-1,-1,-1,-1,-1,-1,-1,-1},
    {40,0,307,8888,8289,8720,8259,8854,8539,8898,8627,8998,8655,4128,-1,-1,-1,-1,-1,-1,-1,-1,-1,-1},
    {40,0,307,8889,8288,8721,8258,8855,8538,8899,8626,8999,8654,4128,-1,-1,-1,-1,-1,-1,-1,-1,-1,-1},
    {10,157,221,8706,8269,8820,8457,9006,8687,4128,-1,-1,-1,-1,-1,-1,-1,-1,-1,-1,-1,-1,-1,-1},
    {10,157,221,8707,8268,8821,8456,9007,8686,4128,-1,-1,-1,-1,-1,-1,-1,-1,-1,-1,-1,-1,-1,-1},
    {132,196,296,8730,8333,8940,8503,9082,8697,4128,-1,-1,-1,-1,-1,-1,-1,-1,-1,-1,-1,-1,-1,-1},
    {132,196,296,8731,8332,8941,8502,9083,8696,4128,-1,-1,-1,-1,-1,-1,-1,-1,-1,-1,-1,-1,-1,-1},
    {128,192,8758,8199,8774,8313,9026,8415,9130,8663,4128,-1,-1,-1,-1,-1,-1,-1,-1,-1,-1,-1,-1,-1},
    {128,192,8759,8198,8775,8312,9027,8414,9131,8662,4128,-1,-1,-1,-1,-1,-1,-1,-1,-1,-1,-1,-1,-1},
    {133,197,8742,8369,8704,8285,8768,8543,9022,8601,4128,-1,-1,-1,-1,-1,-1,-1,-1,-1,-1,-1,-1,-1},
    {133,197,8743,8368,8705,8284,8769,8542,9023,8600,4128,-1,-1,-1,-1,-1,-1,-1,-1,-1,-1,-1,-1,-1},
    {131,195,38,8708,8265,8932,8461,8896,8631,9076,8585,4128,-1,-1,-1,-1,-1,-1,-1,-1,-1,-1,-1,-1},
    {131,195,38,8709,8264,8933,8460,8897,8630,9077,8584,4128,-1,-1,-1,-1,-1,-1,-1,-1,-1,-1,-1,-1},
    {137,201,8750,8331,8816,8533,8912,8411,9078,8671,4128,-1,-1,-1,-1,-1,-1,-1,-1,-1,-1,-1,-1,-1},
    {137,201,8751,8330,8817,8532,8913,8410,9079,8670,4128,-1,-1,-1,-1,-1,-1,-1,-1,-1,-1,-1,-1,-1},
    {43,264,440,8744,8201,8858,8417,8954,8483,9016,8649,9152,8691,4128,-1,-1,-1,-1,-1,-1,-1,-1,-1,-1},
    {43,264,440,8745,8200,8859,8416,8955,8482,9017,8648,9153,8690,4128,-1,-1,-1,-1,-1,-1,-1,-1,-1,-1},
    {151,215,8876,8299,8964,8445,9146,8703,4128,-1,-1,-1,-1,-1,-1,-1,-1,-1,-1,-1,-1,-1,-1,-1},
    {151,215,8877,8298,8965,8444,9147,8702,4128,-1,-1,-1,-1,-1,-1,-1,-1,-1,-1,-1,-1,-1,-1,-1},
    {470,5,159,223,8772,8281,8936,8407,9066,8651,4128,-1,-1,-1,-1,-1,-1,-1,-1,-1,-1,-1,-1,-1},
    {470,5,159,223,8773,8280,8937,8406,9067,8650,4128,-1,-1,-1,-1,-1,-1,-1,-1,-1,-1,-1,-1,-1},
    {136,200,444,8760,8275,8848,8477,9040,8525,9148,8681,4128,-1,-1,-1,-1,-1,-1,-1,-1,-1,-1,-1,-1},
    {136,200,444,8761,8274,8849,8476,9041,8524,9149,8680,4128,-1,-1,-1,-1,-1,-1,-1,-1,-1,-1,-1,-1},
    {46,510,462,310,8764,8293,8862,8439,9064,8653,4128,-1,-1,-1,-1,-1,-1,-1,-1,-1,-1,-1,-1,-1},
    {46,510,462,310,8765,8292,8863,8438,9065,8652,4128,-1,-1,-1,-1,-1,-1,-1,-1,-1,-1,-1,-1,-1},
    {145,209,8894,8335,8942,8485,9098,8695,4128,-1,-1,-1,-1,-1,-1,-1,-1,-1,-1,-1,-1,-1,-1,-1},
    {145,209,8895,8334,8943,8484,9099,8694,4128,-1,-1,-1,-1,-1,-1,-1,-1,-1,-1,-1,-1,-1,-1,-1},
    {140,204,8878,8329,8934,8441,9070,8685,4128,-1,-1,-1,-1,-1,-1,-1,-1,-1,-1,-1,-1,-1,-1,-1},
    {140,204,8879,8328,8935,8440,9071,8684,4128,-1,-1,-1,-1,-1,-1,-1,-1,-1,-1,-1,-1,-1,-1,-1},
    {146,210,504,8884,8301,8966,8527,9128,8603,4128,-1,-1,-1,-1,-1,-1,-1,-1,-1,-1,-1,-1,-1,-1},
    {146,210,504,8885,8300,8967,8526,9129,8602,4128,-1,-1,-1,-1,-1,-1,-1,-1,-1,-1,-1,-1,-1,-1},
    {14,6,8868,8245,8806,8267,8938,8547,9000,8611,9108,8643,4128,-1,-1,-1,-1,-1,-1,-1,-1,-1,-1,-1},
    {14,6,8869,8244,8807,8266,8939,8546,9001,8610,9109,8642,4128,-1,-1,-1,-1,-1,-1,-1,-1,-1,-1,-1},
    {144,208,8748,8211,8836,8463,9004,8591,4128,-1,-1,-1,-1,-1,-1,-1,-1,-1,-1,-1,-1,-1,-1,-1},
    {144,208,8749,8210,8837,8462,9005,8590,4128,-1,-1,-1,-1,-1,-1,-1,-1,-1,-1,-1,-1,-1,-1,-1},
    {12,4,8740,8243,8724,8287,8930,8435,8900,8517,9086,8659,4128,-1,-1,-1,-1,-1,-1,-1,-1,-1,-1,-1},
    {12,4,8741,8242,8725,8286,8931,8434,8901,8516,9087,8658,4128,-1,-1,-1,-1,-1,-1,-1,-1,-1,-1,-1},
    {143,207,8866,8353,8752,8205,8830,8409,9056,8561,9140,8581,9104,8679,4128,-1,-1,-1,-1,-1,-1,-1,-1,-1},
    {143,207,8867,8352,8753,8204,8831,8408,9057,8560,9141,8580,9105,8678,4128,-1,-1,-1,-1,-1,-1,-1,-1,-1},
    {147,211,8872,8297,8834,8459,9030,8437,9100,8665,4128,-1,-1,-1,-1,-1,-1,-1,-1,-1,-1,-1,-1,-1},
    {147,211,8873,8296,8835,8458,9031,8436,9101,8664,4128,-1,-1,-1,-1,-1,-1,-1,-1,-1,-1,-1,-1,-1},
    {41,1,8766,8327,8828,8399,9126,8667,4128,-1,-1,-1,-1,-1,-1,-1,-1,-1,-1,-1,-1,-1,-1,-1},
    {41,1,8767,8326,8829,8398,9127,8666,4128,-1,-1,-1,-1,-1,-1,-1,-1,-1,-1,-1,-1,-1,-1,-1},
    {150,214,8882,8223,8832,8473,8980,8413,9094,8669,4128,-1,-1,-1,-1,-1,-1,-1,-1,-1,-1,-1,-1,-1},
    {150,214,8883,8222,8833,8472,8981,8412,9095,8668,4128,-1,-1,-1,-1,-1,-1,-1,-1,-1,-1,-1,-1,-1},
    {141,205,33,8726,8341,8976,8479,9024,8449,9136,8501,9144,8683,4128,-1,-1,-1,-1,-1,-1,-1,-1,-1,-1},
    {141,205,33,8727,8340,8977,8478,9025,8448,9137,8500,9145,8682,4128,-1,-1,-1,-1,-1,-1,-1,-1,-1,-1},
    {277,405,152,216,8718,8475,8902,8403,9150,8661,4128,-1,-1,-1,-1,-1,-1,-1,-1,-1,-1,-1,-1,-1},
    {277,405,152,216,8719,8474,8903,8402,9151,8660,4128,-1,-1,-1,-1,-1,-1,-1,-1,-1,-1,-1,-1,-1},
    {139,203,8886,8203,8856,8433,9032,8393,9080,8599,4128,-1,-1,-1,-1,-1,-1,-1,-1,-1,-1,-1,-1,-1},
    {139,203,8887,8202,8857,8432,9033,8392,9081,8598,4128,-1,-1,-1,-1,-1,-1,-1,-1,-1,-1,-1,-1,-1},
    {149,213,8746,8303,8982,8397,9084,8645,4128,-1,-1,-1,-1,-1,-1,-1,-1,-1,-1,-1,-1,-1,-1,-1},
    {149,213,8747,8302,8983,8396,9085,8644,4128,-1,-1,-1,-1,-1,-1,-1,-1,-1,-1,-1,-1,-1,-1,-1},
    {138,202,8870,8221,8860,8395,9060,8607,4128,-1,-1,-1,-1,-1,-1,-1,-1,-1,-1,-1,-1,-1,-1,-1},
    {138,202,8871,8220,8861,8394,9061,8606,4128,-1,-1,-1,-1,-1,-1,-1,-1,-1,-1,-1,-1,-1,-1,-1},
    {134,198,8738,8225,8728,8283,8962,8541,8992,8499,9074,8609,9124,8595,9184,8693,4128,-1,-1,-1,-1,-1,-1,-1},
    {134,198,8739,8224,8729,8282,8963,8540,8993,8498,9075,8608,9125,8594,9185,8692,4128,-1,-1,-1,-1,-1,-1,-1},
    {142,206,8874,8271,8818,8447,9068,8647,4128,-1,-1,-1,-1,-1,-1,-1,-1,-1,-1,-1,-1,-1,-1,-1},
    {142,206,8875,8270,8819,8446,9069,8646,4128,-1,-1,-1,-1,-1,-1,-1,-1,-1,-1,-1,-1,-1,-1,-1},
    {47,498,506,306,8892,8277,8784,8467,9048,8535,9020,8579,9088,8657,9186,8689,4128,-1,-1,-1,-1,-1,-1,-1},
    {47,498,506,306,8893,8276,8785,8466,9049,8534,9021,8578,9089,8656,9187,8688,4128,-1,-1,-1,-1,-1,-1,-1},
    {148,212,8762,8279,8826,8523,9002,8605,4128,-1,-1,-1,-1,-1,-1,-1,-1,-1,-1,-1,-1,-1,-1,-1},
    {148,212,8763,8278,8827,8522,9003,8604,4128,-1,-1,-1,-1,-1,-1,-1,-1,-1,-1,-1,-1,-1,-1,-1},
    {276,404,268,500,450,490,374,390,430,380,356,412,168,232,9018,8701,-1,-1,-1,-1,-1,-1,-1,-1},
    {276,404,268,500,450,490,374,390,430,380,356,412,168,232,9019,8700,-1,-1,-1,-1,-1,-1,-1,-1},
    {11,403,459,507,329,393,369,377,417,361,433,167,231,9132,8699,-1,-1,-1,-1,-1,-1,-1,-1,-1},
    {11,403,459,507,329,393,369,377,417,361,433,167,231,9133,8698,-1,-1,-1,-1,-1,-1,-1,-1,-1},
    {350,486,502,262,302,334,318,87,52,100,179,243,4096,-1,-1,-1,-1,-1,-1,-1,-1,-1,-1,-1},
    {350,486,502,262,302,334,318,87,52,100,179,243,4096,-1,-1,-1,-1,-1,-1,-1,-1,-1,-1,-1},
    {340,158,222,492,60,108,76,172,236,4096,-1,-1,-1,-1,-1,-1,-1,-1,-1,-1,-1,-1,-1,-1},
    {340,158,222,492,60,108,76,172,236,4096,-1,-1,-1,-1,-1,-1,-1,-1,-1,-1,-1,-1,-1,-1},
    {42,3,35,59,107,360,408,181,245,4096,-1,-1,-1,-1,-1,-1,-1,-1,-1,-1,-1,-1,-1,-1},
    {42,3,35,59,107,360,408,181,245,4096,-1,-1,-1,-1,-1,-1,-1,-1,-1,-1,-1,-1,-1,-1},
    {45,156,220,396,85,109,93,180,244,4096,-1,-1,-1,-1,-1,-1,-1,-1,-1,-1,-1,-1,-1,-1},
    {45,156,220,396,85,109,93,180,244,4096,-1,-1,-1,-1,-1,-1,-1,-1,-1,-1,-1,-1,-1,-1},
    {466,482,266,258,37,69,53,77,183,247,4096,-1,-1,-1,-1,-1,-1,-1,-1,-1,-1,-1,-1,-1},
    {466,482,266,258,37,69,53,77,183,247,4096,-1,-1,-1,-1,-1,-1,-1,-1,-1,-1,-1,-1,-1},
    {471,407,463,442,290,322,314,386,478,382,366,414,182,246,4096,-1,-1,-1,-1,-1,-1,-1,-1,-1},
    {471,407,463,442,290,322,314,386,478,382,366,414,182,246,4096,-1,-1,-1,-1,-1,-1,-1,-1,-1},
    {469,349,485,501,445,333,317,373,477,423,439,415,173,237,4096,-1,-1,-1,-1,-1,-1,-1,-1,-1},
    {469,349,485,501,445,333,317,373,477,423,439,415,173,237,4096,-1,-1,-1,-1,-1,-1,-1,-1,-1},
    {8,269,309,453,449,489,385,425,422,358,92,188,252,4096,-1,-1,-1,-1,-1,-1,-1,-1,-1,-1},
    {8,269,309,453,449,489,385,425,422,358,92,188,252,4096,-1,-1,-1,-1,-1,-1,-1,-1,-1,-1},
    {343,287,487,263,303,455,495,391,51,91,160,224,4096,-1,-1,-1,-1,-1,-1,-1,-1,-1,-1,-1},
    {343,287,487,263,303,455,495,391,51,91,160,224,4096,-1,-1,-1,-1,-1,-1,-1,-1,-1,-1,-1},
    {464,272,480,456,288,488,392,61,379,363,435,176,240,4096,-1,-1,-1,-1,-1,-1,-1,-1,-1,-1},
    {464,272,480,456,288,488,392,61,379,363,435,176,240,4096,-1,-1,-1,-1,-1,-1,-1,-1,-1,-1},
    {336,280,400,256,448,320,312,384,424,416,352,432,472,171,235,4096,-1,-1,-1,-1,-1,-1,-1,-1},
    {336,280,400,256,448,320,312,384,424,416,352,432,472,171,235,4096,-1,-1,-1,-1,-1,-1,-1,-1},
    {337,273,265,155,219,368,376,479,359,102,184,248,4096,-1,-1,-1,-1,-1,-1,-1,-1,-1,-1,-1},
    {337,273,265,155,219,368,376,479,359,102,184,248,4096,-1,-1,-1,-1,-1,-1,-1,-1,-1,-1,-1},
    {468,284,508,260,300,324,332,388,104,72,174,238,4096,-1,-1,-1,-1,-1,-1,-1,-1,-1,-1,-1},
    {468,284,508,260,300,324,332,388,104,72,174,238,4096,-1,-1,-1,-1,-1,-1,-1,-1,-1,-1,-1},
    {338,281,2,34,66,110,78,175,239,4096,-1,-1,-1,-1,-1,-1,-1,-1,-1,-1,-1,-1,-1,-1},
    {338,281,2,34,66,110,78,175,239,4096,-1,-1,-1,-1,-1,-1,-1,-1,-1,-1,-1,-1,-1,-1},
    {130,194,39,63,55,95,103,97,4096,-1,-1,-1,-1,-1,-1,-1,-1,-1,-1,-1,-1,-1,-1,-1},
    {130,194,39,63,55,95,103,97,4096,-1,-1,-1,-1,-1,-1,-1,-1,-1,-1,-1,-1,-1,-1,-1},
    {135,199,454,494,67,83,365,413,191,255,4096,-1,-1,-1,-1,-1,-1,-1,-1,-1,-1,-1,-1,-1},
    {135,199,454,494,67,83,365,413,191,255,4096,-1,-1,-1,-1,-1,-1,-1,-1,-1,-1,-1,-1,-1},
    {348,484,460,308,292,452,316,372,428,420,476,101,187,251,4096,-1,-1,-1,-1,-1,-1,-1,-1,-1},
    {348,484,460,308,292,452,316,372,428,420,476,101,187,251,4096,-1,-1,-1,-1,-1,-1,-1,-1,-1},
    {13,154,218,58,106,74,178,242,4096,-1,-1,-1,-1,-1,-1,-1,-1,-1,-1,-1,-1,-1,-1,-1},
    {13,154,218,58,106,74,178,242,4096,-1,-1,-1,-1,-1,-1,-1,-1,-1,-1,-1,-1,-1,-1,-1},
    {465,481,457,505,289,328,71,111,79,166,230,4096,-1,-1,-1,-1,-1,-1,-1,-1,-1,-1,-1,-1},
    {465,481,457,505,289,328,71,111,79,166,230,4096,-1,-1,-1,-1,-1,-1,-1,-1,-1,-1,-1,-1},
    {44,270,446,294,326,65,81,89,161,225,4096,-1,-1,-1,-1,-1,-1,-1,-1,-1,-1,-1,-1,-1},
    {44,270,446,294,326,65,81,89,161,225,4096,-1,-1,-1,-1,-1,-1,-1,-1,-1,-1,-1,-1,-1},
    {9,511,503,295,327,375,399,381,437,353,409,473,169,233,4096,-1,-1,-1,-1,-1,-1,-1,-1,-1},
    {9,511,503,295,327,375,399,381,437,353,409,473,169,233,4096,-1,-1,-1,-1,-1,-1,-1,-1,-1},
    {347,283,483,259,291,491,331,371,431,383,367,99,186,250,4096,-1,-1,-1,-1,-1,-1,-1,-1,-1},
    {347,283,483,259,291,491,331,371,431,383,367,99,186,250,4096,-1,-1,-1,-1,-1,-1,-1,-1,-1},
    {274,282,458,261,293,493,397,389,429,421,357,75,189,253,4096,-1,-1,-1,-1,-1,-1,-1,-1,-1},
    {274,282,458,261,293,493,397,389,429,421,357,75,189,253,4096,-1,-1,-1,-1,-1,-1,-1,-1,-1},
    {278,286,406,32,64,56,48,88,170,234,4096,-1,-1,-1,-1,-1,-1,-1,-1,-1,-1,-1,-1,-1},
    {278,286,406,32,64,56,48,88,170,234,4096,-1,-1,-1,-1,-1,-1,-1,-1,-1,-1,-1,-1,-1},
    {279,351,271,447,298,330,394,370,426,378,354,434,164,228,4096,-1,-1,-1,-1,-1,-1,-1,-1,-1},
    {279,351,271,447,298,330,394,370,426,378,354,434,164,228,4096,-1,-1,-1,-1,-1,-1,-1,-1,-1},
    {344,345,497,257,297,321,313,82,50,90,98,96,4096,-1,-1,-1,-1,-1,-1,-1,-1,-1,-1,-1},
    {344,345,497,257,297,321,313,82,50,90,98,96,4096,-1,-1,-1,-1,-1,-1,-1,-1,-1,-1,-1},
    {129,193,311,335,319,86,438,364,436,163,227,4096,-1,-1,-1,-1,-1,-1,-1,-1,-1,-1,-1,-1},
    {129,193,311,335,319,86,438,364,436,163,227,4096,-1,-1,-1,-1,-1,-1,-1,-1,-1,-1,-1,-1},
    {341,285,509,461,301,325,398,80,418,362,410,474,177,241,4096,-1,-1,-1,-1,-1,-1,-1,-1,-1},
    {341,285,509,461,301,325,398,80,418,362,410,474,177,241,4096,-1,-1,-1,-1,-1,-1,-1,-1,-1},
    {342,275,267,499,299,451,395,57,49,73,185,249,4096,-1,-1,-1,-1,-1,-1,-1,-1,-1,-1,-1},
    {342,275,267,499,299,451,395,57,49,73,185,249,4096,-1,-1,-1,-1,-1,-1,-1,-1,-1,-1,-1},
    {346,402,496,304,443,323,315,387,427,419,355,411,165,229,4096,-1,-1,-1,-1,-1,-1,-1,-1,-1},
    {346,402,496,304,443,323,315,387,427,419,355,411,165,229,4096,-1,-1,-1,-1,-1,-1,-1,-1,-1},
    {15,401,305,441,70,62,54,94,190,254,4096,-1,-1,-1,-1,-1,-1,-1,-1,-1,-1,-1,-1,-1},
    {15,401,305,441,70,62,54,94,190,254,4096,-1,-1,-1,-1,-1,-1,-1,-1,-1,-1,-1,-1,-1},
    {467,7,36,68,84,105,475,162,226,4096,-1,-1,-1,-1,-1,-1,-1,-1,-1,-1,-1,-1,-1,-1},
    {467,7,36,68,84,105,475,162,226,4096,-1,-1,-1,-1,-1,-1,-1,-1,-1,-1,-1,-1,-1,-1},
};

void build_rounds() {
    for (int c = 0; c < NUM_SMS / 2; c++) {
        const int16_t* jobs = h_params.jobs[2 * c];
        int nr = 0, prev_key = -1, last = 0;
        for (int j = 0; (jobs[j] >> 12) == T_P; j++) {
            const int n = jobs[j] >> 3, a = n >= 32, unit = n >= 16 && n < 32 ? (n >> 3) - 1 : 0, cnt = a ? 2 : 4;
            const int key = (jobs[j] & 7) | a << 3 | (unit > 0) << 4;
            const int wm = n < 16 ? 0 : (n < 32 ? 1 : n >> 4 & 1), col = n < 16 ? n : (n < 32 ? n & 7 : n & 15);
            const bool keep = key == prev_key, final_tile = (jobs[j + 1] >> 12) != T_P;
            const int k0 = keep ? last : 0;
            for (int r = 0; r < cnt; r++) {
                last = (k0 + r) % cnt;
                h_params.rounds[c][nr++] = (uint16_t)((key & 15) | wm << 4 | col << 6 | last << 10 | (keep && r == 0) << 12 | (final_tile && r == 0) << 13 | unit << 14);
            }
            prev_key = key;
        }
        while (nr < MAX_ROUNDS) h_params.rounds[c][nr++] = 0xFFFF;
        {
            const uint32_t rec = h_params.rounds[c][0], col = rec >> 6 & 15, unit = rec >> 14;
            for (uint32_t r = 0; r < 2; r++) {
                uint32_t wm[2], wb[2];
                for (uint32_t h = 0; h < 2; h++) {
                    wm[h] = 2 + ((rec & 8) ? 2 + h : ((rec >> 15) && h ? 0 : rec >> 4 & 1));
                    wb[h] = (rec & 8) ? (col + (rec & 16)) * 2
                                      : (unit == 0 ? col * 4 + h * 2 : (unit == 1 ? 16 + h * 16 + col * 2 : (h ? unit_head(col) : col) * 2));
                }
                const uint32_t am = unit ? 6 : (rec >> 3 & 1), arow = unit ? (rec & 7) * 128 + r * 64 : (rec & 7) * 256 + r * 128;
                h_params.first[2 * c + r] = make_uint2((unit ? 1 : 0) | am << 7 | wm[0] << 11 | wm[1] << 15 | arow << 20, wb[0] | wb[1] << 16);
            }
        }
    }
}

void build_schedule() {
    for (int c = 0; c < NUM_SMS; c++) {
        for (int j = 0; j < MAX_JOBS; j++) h_params.jobs[c][j] = k_jobs[c][j];
    }
    build_rounds();
}

}

extern "C" void kernel_launch(void* const* d_in, const int* in_sizes, int n_in, void* d_out, int out_size) {
    (void)in_sizes; (void)n_in; (void)out_size;
    static EncodeFn enc = nullptr;
    if (!enc) {
        cudaDriverEntryPointQueryResult qr;
        void* fn = nullptr;
        cudaGetDriverEntryPoint("cuTensorMapEncodeTiled", &fn, cudaEnableDefault, &qr);
        enc = (EncodeFn)fn;
        cudaFuncSetAttribute(fused_kernel, cudaFuncAttributeMaxDynamicSharedMemorySize, SMEM_BYTES);
        build_schedule();
    }
    void* qkv;
    cudaGetSymbolAddress(&qkv, g_qkv);
    Params& p = h_params;
    make_map3(enc, &p.amap[0], d_in[0], SEQ, DM, 128, 1);
    make_map3(enc, &p.amap[1], d_in[1], SEQ, DC, 128, 1);
    make_map3(enc, &p.wmap[0], d_in[2], DM, 4096, 64, 2);
    make_map3(enc, &p.wmap[2], d_in[3], DC, 4096, 64, 2);
    make_map3(enc, &p.wmap[3], d_in[4], DC, 4096, 64, 2);
    make_map3(enc, &p.wmap[1], d_in[7], DM, 3072, 64, 2);
    make_map3(enc, &p.wo_a, d_in[5], 4096, DM, 64, 2);
    make_map3(enc, &p.wo_b, d_in[8], DM, DM, 64, 2);
    make_map3(enc, &p.qkv_st, qkv, SEQ, QKV_W, 64, 1, true);
    make_map3(enc, &p.qkv_ld, qkv, SEQ, QKV_W, 128, 2, true);
    make_map3(enc, &p.qkv_half, qkv, SEQ, QKV_W, 128, 1, true);
    {
        cuuint64_t dims[4] = {64, SEQ / 2, 2, QKV_W / 64}, strides[3] = {256, 128, (cuuint64_t)SEQ * 128};
        cuuint32_t box[4] = {64, 64, 1, 1}, es[4] = {1, 1, 1, 1};
        enc(&p.st_par, CU_TENSOR_MAP_DATA_TYPE_BFLOAT16, 4, qkv, dims, strides, box, es, CU_TENSOR_MAP_INTERLEAVE_NONE,
            CU_TENSOR_MAP_SWIZZLE_128B, CU_TENSOR_MAP_L2_PROMOTION_L2_256B, CU_TENSOR_MAP_FLOAT_OOB_FILL_NONE);
        dims[3] = DM / 64; strides[0] = DM * 4; strides[1] = DM * 2; strides[2] = 128; box[2] = 2;
        enc(&p.x_par, CU_TENSOR_MAP_DATA_TYPE_BFLOAT16, 4, d_in[0], dims, strides, box, es, CU_TENSOR_MAP_INTERLEAVE_NONE,
            CU_TENSOR_MAP_SWIZZLE_128B, CU_TENSOR_MAP_L2_PROMOTION_L2_256B, CU_TENSOR_MAP_FLOAT_OOB_FILL_NONE);
    }
    make_map3(enc, &p.out_st, d_out, SEQ, DM, 64, 1);
    p.xp = (const __nv_bfloat16*)d_in[0];
    p.gate_w = (const __nv_bfloat16*)d_in[9];
    p.out = (__nv_bfloat16*)d_out;
    fused_kernel<<<NUM_SMS, 384, SMEM_BYTES, cudaStreamPerThread>>>(p);
}
```

```cpp
#include <cuda_runtime.h>
#include <cuda_bf16.h>
#include <cuda.h>
#include <stdint.h>

#define INL __attribute__((always_inline))

namespace {

constexpr int SEQ = 2048;
constexpr int DM = 1024;
constexpr int DC = 512;
constexpr int QKV_W = 13312;
constexpr int NUM_SMS = 132;
constexpr int GATE_DELAY_SHORT_NS = 1000, GATE_DELAY_LONG_NS = 3000;
constexpr int CLEAR_KS = 44, CLEAR_GAP_NS = 100;
constexpr float Q_SCALE = 0.08838834764831845f * 1.4426950408889634f;

__device__ __align__(1024) __nv_bfloat16 g_qkv[(size_t)SEQ * QKV_W];
__device__ float g_gate[SEQ];
__device__ uint4 g_halo[16 * 8 * 2 * 5 * 4 * 32];

constexpr int F_Q = 0;
constexpr int F_KV = 1792;
constexpr int F_H = 768;
constexpr int F_CTX = 960;
constexpr int F_GATE = 1600;
constexpr int F_DONE = 1632;
constexpr int F_SPLIT = 1664;
constexpr int F_TICKET = 1696;
constexpr int F_OUT = 1728;
constexpr int GATE_COUNT = NUM_SMS;
__device__ uint32_t g_flags[2304];

#define END_MARK(slot)
#define TRACE_MARK(k, w, i)
#define GTRACE(w)
#define KTRACE(w)
#define PTRACE(i)
#define TRACE_GATE 32
#define TRACE_TID 128

__device__ __forceinline__ uint32_t smem_u32(const void* p) { return (uint32_t)__cvta_generic_to_shared(p); }
__device__ __forceinline__ void mbar_init(uint32_t bar, uint32_t cnt) {
    asm volatile("mbarrier.init.shared::cta.b64 [%0], %1;" ::"r"(bar), "r"(cnt));
}
__device__ __forceinline__ void mbar_arrive(uint32_t bar) {
    asm volatile("mbarrier.arrive.shared::cta.b64 _, [%0];" ::"r"(bar) : "memory");
}
__device__ __forceinline__ bool elect_one() {
    uint32_t r;
    asm volatile("{\n.reg .pred p;\nelect.sync _|p, 0xffffffff;\nselp.b32 %0, 1, 0, p;\n}" : "=r"(r));
    return r != 0;
}
__device__ __forceinline__ uint32_t mapa(uint32_t addr, uint32_t cta) {
    uint32_t r;
    asm("mapa.shared::cluster.u32 %0, %1, %2;" : "=r"(r) : "r"(addr), "r"(cta));
    return r;
}
__device__ __forceinline__ void warp_arrive(uint32_t bar, bool pred = true) {
    asm volatile("{\n.reg .pred p, q;\nsetp.ne.u32 q, %1, 0;\nelect.sync _|p, 0xffffffff;\nand.pred p, p, q;\n"
                 "@p mbarrier.arrive.shared::cta.b64 _, [%0];\n}" ::"r"(bar), "r"((uint32_t)pred) : "memory");
}
__device__ __forceinline__ void warp_arrive2(uint32_t bar0, uint32_t bar1) {
    asm volatile("{\n.reg .pred p;\nelect.sync _|p, 0xffffffff;\n@p mbarrier.arrive.shared::cta.b64 _, [%0];\n"
                 "@p mbarrier.arrive.shared::cta.b64 _, [%1];\n}" ::"r"(bar0), "r"(bar1) : "memory");
}
__device__ __forceinline__ void warp_arrive_pair(uint32_t bar, uint32_t peer_bar, bool pred = true) {
    asm volatile("{\n.reg .pred p, q;\nsetp.ne.u32 q, %2, 0;\nelect.sync _|p, 0xffffffff;\nand.pred p, p, q;\n"
                 "@p mbarrier.arrive.shared::cluster.b64 _, [%1];\n@p mbarrier.arrive.shared::cta.b64 _, [%0];\n}"
                 ::"r"(bar), "r"(peer_bar), "r"((uint32_t)pred) : "memory");
}
__device__ __forceinline__ void mbar_expect_tx(uint32_t bar, uint32_t bytes) {
    asm volatile("mbarrier.arrive.expect_tx.shared::cta.b64 _, [%0], %1;" ::"r"(bar), "r"(bytes) : "memory");
}
constexpr int WAIT_HINT_NS = 20000, WAIT_TRIES = 200000;
__device__ __forceinline__ void mbar_wait(uint32_t bar, uint32_t parity) {
    asm volatile("{\n.reg .pred p;\n.reg .u32 c;\n"
                 "mbarrier.try_wait.parity.shared::cta.b64 p, [%0], %1;\n@p bra DONE;\nmov.u32 c, 0;\n"
                 "SPIN:\nmbarrier.try_wait.parity.shared::cta.b64 p, [%0], %1, %2;\n@p bra DONE;\n"
                 "add.u32 c, c, 1;\nsetp.lt.u32 p, c, %3;\n@p bra SPIN;\ntrap;\nDONE:\n}"
                 ::"r"(bar), "r"(parity), "n"(WAIT_HINT_NS), "n"(WAIT_TRIES) : "memory");
}
__device__ __forceinline__ void mbar_wait_hot(uint32_t bar, uint32_t parity) {
    asm volatile("{\n.reg .pred p, q;\n.reg .u32 c;\n.reg .u64 z;\nmov.u32 c, 0;\nmov.u64 z, 0;\n"
                 "SPIN:\nmbarrier.try_wait.parity.shared::cta.b64 p, [%0], %1;\n"
                 "add.u32 c, c, 1;\nsetp.lt.and.u32 q, c, 4194304, !p;\n@q bra SPIN;\n@!p st.global.u32 [z], c;\n}"
                 ::"r"(bar), "r"(parity) : "memory");
}
constexpr uint64_t POL_STREAM = 0x12F0000000000000ull;
constexpr uint64_t POL_NORMAL = 0x1000000000000000ull;
__device__ __forceinline__ void tma_load_3d(uint32_t dst, const CUtensorMap* map, uint32_t bar, int c0, int c1, int c2, uint64_t pol = POL_NORMAL) {
    asm volatile("cp.async.bulk.tensor.3d.shared::cluster.global.mbarrier::complete_tx::bytes.L2::cache_hint [%0], [%1, {%3, %4, %5}], [%2], %6;"
                 ::"r"(dst), "l"(map), "r"(bar), "r"(c0), "r"(c1), "r"(c2), "l"(pol) : "memory");
}
__device__ __forceinline__ void load_kstep(uint32_t sa, uint32_t sw, uint32_t bar, uint32_t bytes, const CUtensorMap* wmap, int wk, int wblk,
                                           const CUtensorMap* amap, int arow, int kc, uint32_t amode) {
    asm volatile("{\n.reg .pred p, q, r;\n.reg .b32 k;\nelect.sync _|p, 0xffffffff;\nsetp.eq.and.u32 q, %9, 1, p;\nsetp.eq.and.u32 r, %9, 2, p;\nshl.b32 k, %12, 6;\n"
                 "@p mbarrier.arrive.expect_tx.shared::cta.b64 _, [%2], %3;\n"
                 "@p cp.async.bulk.tensor.3d.shared::cluster.global.mbarrier::complete_tx::bytes.multicast::cluster.L2::cache_hint [%1], [%4, {0, k, %5}], [%2], %10, %11;\n"
                 "@q cp.async.bulk.tensor.3d.shared::cluster.global.mbarrier::complete_tx::bytes.L2::cache_hint [%0], [%6, {0, %7, %8}], [%2], %11;\n"
                 "@r cp.async.bulk.tensor.4d.shared::cluster.global.mbarrier::complete_tx::bytes.L2::cache_hint [%0], [%6, {0, %7, 0, %8}], [%2], %11;\n}"
                 ::"r"(sa), "r"(sw), "r"(bar), "r"(bytes), "l"(wmap), "r"(wblk), "l"(amap), "r"(arow), "r"(kc), "r"(amode), "h"((uint16_t)3), "l"(POL_NORMAL), "r"(wk) : "memory");
}
__device__ __forceinline__ void load_operand(uint32_t dst, uint32_t bar, const CUtensorMap* full, const CUtensorMap* half, int row, int blk,
                                             uint32_t rank, bool solo, uint64_t pol) {
    asm volatile("{\n.reg .pred p, q, r;\n.reg .b32 d, b;\nelect.sync _|p, 0xffffffff;\nsetp.ne.and.u32 q, %7, 0, p;\nsetp.eq.and.u32 r, %7, 0, p;\n"
                 "mad.lo.u32 d, %6, 16384, %0;\nadd.u32 b, %5, %6;\n"
                 "@p mbarrier.arrive.expect_tx.shared::cta.b64 _, [%1], 32768;\n"
                 "@q cp.async.bulk.tensor.3d.shared::cluster.global.mbarrier::complete_tx::bytes.L2::cache_hint [%0], [%2, {0, %4, %5}], [%1], %9;\n"
                 "@r cp.async.bulk.tensor.3d.shared::cluster.global.mbarrier::complete_tx::bytes.multicast::cluster.L2::cache_hint [d], [%3, {0, %4, b}], [%1], %8, %9;\n}"
                 ::"r"(dst), "r"(bar), "l"(full), "l"(half), "r"(row), "r"(blk), "r"(rank), "r"((uint32_t)solo), "h"((uint16_t)3), "l"(pol) : "memory");
}
__device__ __forceinline__ void tma_store_par(const CUtensorMap* map, uint32_t src, int pair, int parity, int blk) {
    asm volatile("cp.async.bulk.tensor.4d.global.shared::cta.bulk_group.L2::cache_hint [%0, {0, %2, %3, %4}], [%1], %5;"
                 ::"l"(map), "r"(src), "r"(pair), "r"(parity), "r"(blk), "l"(POL_STREAM) : "memory");
}
__device__ __forceinline__ void tma_store_3d(const CUtensorMap* map, uint32_t src, int c0, int c1, int c2, uint64_t pol) {
    asm volatile("cp.async.bulk.tensor.3d.global.shared::cta.bulk_group.L2::cache_hint [%0, {%2, %3, %4}], [%1], %5;"
                 ::"l"(map), "r"(src), "r"(c0), "r"(c1), "r"(c2), "l"(pol) : "memory");
}
__device__ __forceinline__ void tma_reduce_add_3d(const CUtensorMap* map, uint32_t src, int c0, int c1, int c2) {
    asm volatile("cp.reduce.async.bulk.tensor.3d.global.shared::cta.add.tile.bulk_group [%0, {%2, %3, %4}], [%1];"
                 ::"l"(map), "r"(src), "r"(c0), "r"(c1), "r"(c2) : "memory");
}
__device__ __forceinline__ void bulk_commit() { asm volatile("cp.async.bulk.commit_group;" ::: "memory"); }
template <int N> __device__ __forceinline__ void bulk_wait_read() { asm volatile("cp.async.bulk.wait_group.read %0;" ::"n"(N) : "memory"); }
template <int N> __device__ __forceinline__ void bulk_wait() { asm volatile("cp.async.bulk.wait_group %0;" ::"n"(N) : "memory"); }
__device__ __forceinline__ void fence_async_smem() { asm volatile("fence.proxy.async.shared::cta;" ::: "memory"); }
__device__ __forceinline__ void fence_async_global() { asm volatile("fence.proxy.async.global;" ::: "memory"); }
__device__ __forceinline__ uint32_t ld_acquire(const uint32_t* p) {
    uint32_t v;
    asm volatile("ld.acquire.gpu.global.u32 %0, [%1];" : "=r"(v) : "l"(p) : "memory");
    return v;
}
__device__ __forceinline__ uint32_t ld_relaxed(const uint32_t* p) {
    uint32_t v;
    asm volatile("ld.relaxed.gpu.global.u32 %0, [%1];" : "=r"(v) : "l"(p) : "memory");
    return v;
}
__device__ __forceinline__ void fence_acquire() { asm volatile("fence.acquire.gpu;\nfence.proxy.async.global;" ::: "memory"); }
__device__ __forceinline__ void red_release(uint32_t* p) {
    asm volatile("red.release.gpu.global.add.u32 [%0], 1;" ::"l"(p) : "memory");
}
__device__ __forceinline__ void red_relaxed(uint32_t* p) {
    asm volatile("red.relaxed.gpu.global.add.u32 [%0], 1;" ::"l"(p) : "memory");
}
__device__ __forceinline__ void prefetch_map(const CUtensorMap* map) { asm volatile("prefetch.tensormap [%0];" ::"l"(map) : "memory"); }
__device__ __forceinline__ void trap_if(bool c) { asm volatile("{\n.reg .pred p;\nsetp.ne.u32 p, %0, 0;\n@p trap;\n}" ::"r"((uint32_t)c)); }
__device__ __forceinline__ void setup_arrive() { asm volatile("barrier.cluster.arrive.relaxed.aligned;" ::: "memory"); }
__device__ __forceinline__ void setup_wait() { asm volatile("barrier.cluster.wait.aligned;" ::: "memory"); }
__device__ __forceinline__ uint32_t cluster_rank() { uint32_t r; asm("mov.u32 %0, %%cluster_ctarank;" : "=r"(r)); return r; }
__device__ __forceinline__ void named_sync(int id, int n) { asm volatile("bar.sync %0, %1;" ::"r"(id), "r"(n) : "memory"); }
__device__ __forceinline__ void named_arrive(int id, int n) { asm volatile("bar.arrive %0, %1;" ::"r"(id), "r"(n) : "memory"); }
__device__ __forceinline__ void named_sync_if(bool c, int id, int n) {
    asm volatile("{\n.reg .pred p;\nsetp.ne.u32 p, %0, 0;\n@p bar.sync %1, %2;\n}" ::"r"((uint32_t)c), "r"(id), "r"(n) : "memory");
}
__device__ __forceinline__ void named_arrive_if(bool c, int id, int n) {
    asm volatile("{\n.reg .pred p;\nsetp.ne.u32 p, %0, 0;\n@p bar.arrive %1, %2;\n}" ::"r"((uint32_t)c), "r"(id), "r"(n) : "memory");
}
template <int V> struct IC { static constexpr int v = V; };
template <int N> __device__ __forceinline__ void reg_dec() { asm volatile("setmaxnreg.dec.sync.aligned.u32 %0;" ::"n"(N)); }
template <int N> __device__ __forceinline__ void reg_inc() { asm volatile("setmaxnreg.inc.sync.aligned.u32 %0;" ::"n"(N)); }

__device__ __forceinline__ void wg_fence() { asm volatile("wgmma.fence.sync.aligned;" ::: "memory"); }
__device__ __forceinline__ void wg_commit() { asm volatile("wgmma.commit_group.sync.aligned;" ::: "memory"); }
template <int N> __device__ __forceinline__ void wg_wait() { asm volatile("wgmma.wait_group.sync.aligned %0;" ::"n"(N) : "memory"); }
template <int N> __device__ __forceinline__ void fence_regs(float (&r)[N]) {
#pragma unroll
    for (int i = 0; i < N; i++) asm volatile("" : "+f"(r[i])::"memory");
}
template <int N> __device__ __forceinline__ void fence_regs(uint32_t (&r)[N]) {
#pragma unroll
    for (int i = 0; i < N; i++) asm volatile("" : "+r"(r[i])::"memory");
}
__device__ __forceinline__ uint32_t desc_lo(uint32_t addr, uint32_t lbo) { return ((addr & 0x3FFFF) >> 4) | ((lbo >> 4) << 16); }
__device__ __forceinline__ int uniform(int v) { return __shfl_sync(0xffffffffu, v, 0); }
__device__ __forceinline__ uint32_t pack_bf16(float lo, float hi) {
    uint32_t r;
    asm("cvt.rn.bf16x2.f32 %0, %1, %2;" : "=r"(r) : "f"(hi), "f"(lo));
    return r;
}
__device__ __forceinline__ uint32_t mul_bf16x2(uint32_t x, uint32_t y) {
    uint32_t r;
    asm("mul.rn.bf16x2 %0, %1, %2;" : "=r"(r) : "r"(x), "r"(y));
    return r;
}
__device__ __forceinline__ void stmatrix_x4(uint32_t addr, uint32_t r0, uint32_t r1, uint32_t r2, uint32_t r3) {
    asm volatile("stmatrix.sync.aligned.m8n8.x4.shared.b16 [%0], {%1, %2, %3, %4};"
                 ::"r"(addr), "r"(r0), "r"(r1), "r"(r2), "r"(r3) : "memory");
}
__device__ __forceinline__ void stmatrix_x4(uint32_t addr, uint32_t r0, uint32_t r1, uint32_t r2, uint32_t r3, bool trans) {
    asm volatile("{\n.reg .pred p;\nsetp.ne.u32 p, %5, 0;\n@p stmatrix.sync.aligned.m8n8.x4.trans.shared.b16 [%0], {%1, %2, %3, %4};\n"
                 "@!p stmatrix.sync.aligned.m8n8.x4.shared.b16 [%0], {%1, %2, %3, %4};\n}"
                 ::"r"(addr), "r"(r0), "r"(r1), "r"(r2), "r"(r3), "r"((uint32_t)trans) : "memory");
}
__device__ __forceinline__ void ldmatrix_x4_t(uint32_t addr, uint32_t (&r)[4]) {
    asm volatile("ldmatrix.sync.aligned.m8n8.x4.trans.shared.b16 {%0, %1, %2, %3}, [%4];"
                 : "=r"(r[0]), "=r"(r[1]), "=r"(r[2]), "=r"(r[3]) : "r"(addr) : "memory");
}
__device__ __forceinline__ void mma_16816(float (&d)[4], uint32_t a0, uint32_t a1, uint32_t a2, uint32_t a3, uint32_t b0, uint32_t b1) {
    asm("mma.sync.aligned.m16n8k16.row.col.f32.bf16.bf16.f32 {%0, %1, %2, %3}, {%4, %5, %6, %7}, {%8, %9}, {%0, %1, %2, %3};"
        : "+f"(d[0]), "+f"(d[1]), "+f"(d[2]), "+f"(d[3]) : "r"(a0), "r"(a1), "r"(a2), "r"(a3), "r"(b0), "r"(b1));
}
__device__ __forceinline__ void order_after(float v, uint32_t scratch) {
    asm volatile("{\n.reg .pred p;\nsetp.gt.f32 p, %0, 0f70000000;\n@p st.shared.u32 [%1], 0;\n}" ::"f"(v), "r"(scratch) : "memory");
}
__device__ __forceinline__ float rcp(float x) { float y; asm("rcp.approx.ftz.f32 %0, %1;" : "=f"(y) : "f"(x)); return y; }
__device__ __forceinline__ float ex2(float x) { float y; asm("ex2.approx.ftz.f32 %0, %1;" : "=f"(y) : "f"(x)); return y; }

template <int OA, int OB>
__device__ __forceinline__ void wgmma_ss_n256(float (&d0)[64], float (&d1)[64], uint32_t da, uint32_t db) {
    asm volatile("{\n.reg .b32 ta, tb;\n.reg .b64 da, db;\nadd.u32 ta, %128, %130;\nadd.u32 tb, %129, %131;\n"
        "mov.b64 da, {ta, 0x40000040};\nmov.b64 db, {tb, 0x40000040};\n"
        "wgmma.mma_async.sync.aligned.m64n256k16.f32.bf16.bf16 {%0, %1, %2, %3, %4, %5, %6, %7, %8, %9, %10, %11, %12, %13, %14, %15, %16, %17, %18, %19, %20, %21, %22, %23, %24, %25, %26, %27, %28, %29, %30, %31, %32, %33, %34, %35, %36, %37, %38, %39, %40, %41, %42, %43, %44, %45, %46, %47, %48, %49, %50, %51, %52, %53, %54, %55, %56, %57, %58, %59, %60, %61, %62, %63, %64, %65, %66, %67, %68, %69, %70, %71, %72, %73, %74, %75, %76, %77, %78, %79, %80, %81, %82, %83, %84, %85, %86, %87, %88, %89, %90, %91, %92, %93, %94, %95, %96, %97, %98, %99, %100, %101, %102, %103, %104, %105, %106, %107, %108, %109, %110, %111, %112, %113, %114, %115, %116, %117, %118, %119, %120, %121, %122, %123, %124, %125, %126, %127}, da, db, 1, 1, 1, 0, 1;\n}\n"
        : "+f"(d0[0]), "+f"(d0[1]), "+f"(d0[2]), "+f"(d0[3]), "+f"(d0[4]), "+f"(d0[5]), "+f"(d0[6]), "+f"(d0[7]), "+f"(d0[8]), "+f"(d0[9]), "+f"(d0[10]), "+f"(d0[11]), "+f"(d0[12]), "+f"(d0[13]), "+f"(d0[14]), "+f"(d0[15]), "+f"(d0[16]), "+f"(d0[17]), "+f"(d0[18]), "+f"(d0[19]), "+f"(d0[20]), "+f"(d0[21]), "+f"(d0[22]), "+f"(d0[23]), "+f"(d0[24]), "+f"(d0[25]), "+f"(d0[26]), "+f"(d0[27]), "+f"(d0[28]), "+f"(d0[29]), "+f"(d0[30]), "+f"(d0[31]), "+f"(d0[32]), "+f"(d0[33]), "+f"(d0[34]), "+f"(d0[35]), "+f"(d0[36]), "+f"(d0[37]), "+f"(d0[38]), "+f"(d0[39]), "+f"(d0[40]), "+f"(d0[41]), "+f"(d0[42]), "+f"(d0[43]), "+f"(d0[44]), "+f"(d0[45]), "+f"(d0[46]), "+f"(d0[47]), "+f"(d0[48]), "+f"(d0[49]), "+f"(d0[50]), "+f"(d0[51]), "+f"(d0[52]), "+f"(d0[53]), "+f"(d0[54]), "+f"(d0[55]), "+f"(d0[56]), "+f"(d0[57]), "+f"(d0[58]), "+f"(d0[59]), "+f"(d0[60]), "+f"(d0[61]), "+f"(d0[62]), "+f"(d0[63]), "+f"(d1[0]), "+f"(d1[1]), "+f"(d1[2]), "+f"(d1[3]), "+f"(d1[4]), "+f"(d1[5]), "+f"(d1[6]), "+f"(d1[7]), "+f"(d1[8]), "+f"(d1[9]), "+f"(d1[10]), "+f"(d1[11]), "+f"(d1[12]), "+f"(d1[13]), "+f"(d1[14]), "+f"(d1[15]), "+f"(d1[16]), "+f"(d1[17]), "+f"(d1[18]), "+f"(d1[19]), "+f"(d1[20]), "+f"(d1[21]), "+f"(d1[22]), "+f"(d1[23]), "+f"(d1[24]), "+f"(d1[25]), "+f"(d1[26]), "+f"(d1[27]), "+f"(d1[28]), "+f"(d1[29]), "+f"(d1[30]), "+f"(d1[31]), "+f"(d1[32]), "+f"(d1[33]), "+f"(d1[34]), "+f"(d1[35]), "+f"(d1[36]), "+f"(d1[37]), "+f"(d1[38]), "+f"(d1[39]), "+f"(d1[40]), "+f"(d1[41]), "+f"(d1[42]), "+f"(d1[43]), "+f"(d1[44]), "+f"(d1[45]), "+f"(d1[46]), "+f"(d1[47]), "+f"(d1[48]), "+f"(d1[49]), "+f"(d1[50]), "+f"(d1[51]), "+f"(d1[52]), "+f"(d1[53]), "+f"(d1[54]), "+f"(d1[55]), "+f"(d1[56]), "+f"(d1[57]), "+f"(d1[58]), "+f"(d1[59]), "+f"(d1[60]), "+f"(d1[61]), "+f"(d1[62]), "+f"(d1[63])
        : "r"(da), "r"(db), "n"(OA), "n"(OB));
}

__device__ __forceinline__ void wgmma_ss_n256_init(float (&d0)[64], float (&d1)[64], uint32_t da, uint32_t db) {
    asm volatile("{\n.reg .b64 da, db;\n"
        "mov.b64 da, {%128, 0x40000040};\nmov.b64 db, {%129, 0x40000040};\n"
        "wgmma.mma_async.sync.aligned.m64n256k16.f32.bf16.bf16 {%0, %1, %2, %3, %4, %5, %6, %7, %8, %9, %10, %11, %12, %13, %14, %15, %16, %17, %18, %19, %20, %21, %22, %23, %24, %25, %26, %27, %28, %29, %30, %31, %32, %33, %34, %35, %36, %37, %38, %39, %40, %41, %42, %43, %44, %45, %46, %47, %48, %49, %50, %51, %52, %53, %54, %55, %56, %57, %58, %59, %60, %61, %62, %63, %64, %65, %66, %67, %68, %69, %70, %71, %72, %73, %74, %75, %76, %77, %78, %79, %80, %81, %82, %83, %84, %85, %86, %87, %88, %89, %90, %91, %92, %93, %94, %95, %96, %97, %98, %99, %100, %101, %102, %103, %104, %105, %106, %107, %108, %109, %110, %111, %112, %113, %114, %115, %116, %117, %118, %119, %120, %121, %122, %123, %124, %125, %126, %127}, da, db, 0, 1, 1, 0, 1;\n}\n"
        : "=f"(d0[0]), "=f"(d0[1]), "=f"(d0[2]), "=f"(d0[3]), "=f"(d0[4]), "=f"(d0[5]), "=f"(d0[6]), "=f"(d0[7]), "=f"(d0[8]), "=f"(d0[9]), "=f"(d0[10]), "=f"(d0[11]), "=f"(d0[12]), "=f"(d0[13]), "=f"(d0[14]), "=f"(d0[15]), "=f"(d0[16]), "=f"(d0[17]), "=f"(d0[18]), "=f"(d0[19]), "=f"(d0[20]), "=f"(d0[21]), "=f"(d0[22]), "=f"(d0[23]), "=f"(d0[24]), "=f"(d0[25]), "=f"(d0[26]), "=f"(d0[27]), "=f"(d0[28]), "=f"(d0[29]), "=f"(d0[30]), "=f"(d0[31]), "=f"(d0[32]), "=f"(d0[33]), "=f"(d0[34]), "=f"(d0[35]), "=f"(d0[36]), "=f"(d0[37]), "=f"(d0[38]), "=f"(d0[39]), "=f"(d0[40]), "=f"(d0[41]), "=f"(d0[42]), "=f"(d0[43]), "=f"(d0[44]), "=f"(d0[45]), "=f"(d0[46]), "=f"(d0[47]), "=f"(d0[48]), "=f"(d0[49]), "=f"(d0[50]), "=f"(d0[51]), "=f"(d0[52]), "=f"(d0[53]), "=f"(d0[54]), "=f"(d0[55]), "=f"(d0[56]), "=f"(d0[57]), "=f"(d0[58]), "=f"(d0[59]), "=f"(d0[60]), "=f"(d0[61]), "=f"(d0[62]), "=f"(d0[63]), "=f"(d1[0]), "=f"(d1[1]), "=f"(d1[2]), "=f"(d1[3]), "=f"(d1[4]), "=f"(d1[5]), "=f"(d1[6]), "=f"(d1[7]), "=f"(d1[8]), "=f"(d1[9]), "=f"(d1[10]), "=f"(d1[11]), "=f"(d1[12]), "=f"(d1[13]), "=f"(d1[14]), "=f"(d1[15]), "=f"(d1[16]), "=f"(d1[17]), "=f"(d1[18]), "=f"(d1[19]), "=f"(d1[20]), "=f"(d1[21]), "=f"(d1[22]), "=f"(d1[23]), "=f"(d1[24]), "=f"(d1[25]), "=f"(d1[26]), "=f"(d1[27]), "=f"(d1[28]), "=f"(d1[29]), "=f"(d1[30]), "=f"(d1[31]), "=f"(d1[32]), "=f"(d1[33]), "=f"(d1[34]), "=f"(d1[35]), "=f"(d1[36]), "=f"(d1[37]), "=f"(d1[38]), "=f"(d1[39]), "=f"(d1[40]), "=f"(d1[41]), "=f"(d1[42]), "=f"(d1[43]), "=f"(d1[44]), "=f"(d1[45]), "=f"(d1[46]), "=f"(d1[47]), "=f"(d1[48]), "=f"(d1[49]), "=f"(d1[50]), "=f"(d1[51]), "=f"(d1[52]), "=f"(d1[53]), "=f"(d1[54]), "=f"(d1[55]), "=f"(d1[56]), "=f"(d1[57]), "=f"(d1[58]), "=f"(d1[59]), "=f"(d1[60]), "=f"(d1[61]), "=f"(d1[62]), "=f"(d1[63])
        : "r"(da), "r"(db));
}

template <int TB, int OA, int OB>
__device__ __forceinline__ void wgmma_ss_n128_init(float (&d)[64], uint32_t da, uint32_t db) {
    asm volatile("{\n.reg .b32 ta, tb;\n.reg .b64 da, db;\nadd.u32 ta, %64, %66;\nadd.u32 tb, %65, %67;\n"
        "mov.b64 da, {ta, 0x40000040};\nmov.b64 db, {tb, 0x40000040};\n"
        "wgmma.mma_async.sync.aligned.m64n128k16.f32.bf16.bf16 {%0, %1, %2, %3, %4, %5, %6, %7, %8, %9, %10, %11, %12, %13, %14, %15, %16, %17, %18, %19, %20, %21, %22, %23, %24, %25, %26, %27, %28, %29, %30, %31, %32, %33, %34, %35, %36, %37, %38, %39, %40, %41, %42, %43, %44, %45, %46, %47, %48, %49, %50, %51, %52, %53, %54, %55, %56, %57, %58, %59, %60, %61, %62, %63}, da, db, 0, 1, 1, 0, %68;\n}\n"
        : "=f"(d[0]), "=f"(d[1]), "=f"(d[2]), "=f"(d[3]), "=f"(d[4]), "=f"(d[5]), "=f"(d[6]), "=f"(d[7]), "=f"(d[8]), "=f"(d[9]), "=f"(d[10]), "=f"(d[11]), "=f"(d[12]), "=f"(d[13]), "=f"(d[14]), "=f"(d[15]), "=f"(d[16]), "=f"(d[17]), "=f"(d[18]), "=f"(d[19]), "=f"(d[20]), "=f"(d[21]), "=f"(d[22]), "=f"(d[23]), "=f"(d[24]), "=f"(d[25]), "=f"(d[26]), "=f"(d[27]), "=f"(d[28]), "=f"(d[29]), "=f"(d[30]), "=f"(d[31]), "=f"(d[32]), "=f"(d[33]), "=f"(d[34]), "=f"(d[35]), "=f"(d[36]), "=f"(d[37]), "=f"(d[38]), "=f"(d[39]), "=f"(d[40]), "=f"(d[41]), "=f"(d[42]), "=f"(d[43]), "=f"(d[44]), "=f"(d[45]), "=f"(d[46]), "=f"(d[47]), "=f"(d[48]), "=f"(d[49]), "=f"(d[50]), "=f"(d[51]), "=f"(d[52]), "=f"(d[53]), "=f"(d[54]), "=f"(d[55]), "=f"(d[56]), "=f"(d[57]), "=f"(d[58]), "=f"(d[59]), "=f"(d[60]), "=f"(d[61]), "=f"(d[62]), "=f"(d[63])
        : "r"(da), "r"(db), "n"(OA), "n"(OB), "n"(TB));
}

template <int OA, int OB>
__device__ __forceinline__ void wgmma_ss_n128_tb0(float (&d)[64], uint32_t da, uint32_t db, int scale_d) {
    asm volatile("{\n.reg .pred p;\n.reg .b32 ta, tb;\n.reg .b64 da, db;\nsetp.ne.b32 p, %66, 0;\nadd.u32 ta, %64, %67;\nadd.u32 tb, %65, %68;\n"
        "mov.b64 da, {ta, 0x40000040};\nmov.b64 db, {tb, 0x40000040};\n"
        "wgmma.mma_async.sync.aligned.m64n128k16.f32.bf16.bf16 "
        "{%0, %1, %2, %3, %4, %5, %6, %7, %8, %9, %10, %11, %12, %13, %14, %15, %16, %17, %18, %19, %20, %21, %22, %23, %24, %25, %26, %27, %28, %29, %30, %31, %32, %33, %34, %35, %36, %37, %38, %39, %40, %41, %42, %43, %44, %45, %46, %47, %48, %49, %50, %51, %52, %53, %54, %55, %56, %57, %58, %59, %60, %61, %62, %63}, da, db, p, 1, 1, 0, 0;\n}\n"
        : "+f"(d[0]), "+f"(d[1]), "+f"(d[2]), "+f"(d[3]), "+f"(d[4]), "+f"(d[5]), "+f"(d[6]), "+f"(d[7]), "+f"(d[8]), "+f"(d[9]), "+f"(d[10]), "+f"(d[11]), "+f"(d[12]), "+f"(d[13]), "+f"(d[14]), "+f"(d[15]), "+f"(d[16]), "+f"(d[17]), "+f"(d[18]), "+f"(d[19]), "+f"(d[20]), "+f"(d[21]), "+f"(d[22]), "+f"(d[23]), "+f"(d[24]), "+f"(d[25]), "+f"(d[26]), "+f"(d[27]), "+f"(d[28]), "+f"(d[29]), "+f"(d[30]), "+f"(d[31]), "+f"(d[32]), "+f"(d[33]), "+f"(d[34]), "+f"(d[35]), "+f"(d[36]), "+f"(d[37]), "+f"(d[38]), "+f"(d[39]), "+f"(d[40]), "+f"(d[41]), "+f"(d[42]), "+f"(d[43]), "+f"(d[44]), "+f"(d[45]), "+f"(d[46]), "+f"(d[47]), "+f"(d[48]), "+f"(d[49]), "+f"(d[50]), "+f"(d[51]), "+f"(d[52]), "+f"(d[53]), "+f"(d[54]), "+f"(d[55]), "+f"(d[56]), "+f"(d[57]), "+f"(d[58]), "+f"(d[59]), "+f"(d[60]), "+f"(d[61]), "+f"(d[62]), "+f"(d[63])
        : "r"(da), "r"(db), "r"(scale_d), "n"(OA), "n"(OB));
}

template <int OB>
__device__ __forceinline__ void wgmma_rs_n128_tb1(float (&d)[64], uint32_t a0, uint32_t a1, uint32_t a2, uint32_t a3, uint32_t db, int scale_d) {
    asm volatile("{\n.reg .pred p;\n.reg .b32 tb;\n.reg .b64 db;\nsetp.ne.b32 p, %69, 0;\nadd.u32 tb, %68, %70;\n"
        "mov.b64 db, {tb, 0x40000040};\n"
        "wgmma.mma_async.sync.aligned.m64n128k16.f32.bf16.bf16 "
        "{%0, %1, %2, %3, %4, %5, %6, %7, %8, %9, %10, %11, %12, %13, %14, %15, %16, %17, %18, %19, %20, %21, %22, %23, %24, %25, %26, %27, %28, %29, %30, %31, %32, %33, %34, %35, %36, %37, %38, %39, %40, %41, %42, %43, %44, %45, %46, %47, %48, %49, %50, %51, %52, %53, %54, %55, %56, %57, %58, %59, %60, %61, %62, %63}, {%64, %65, %66, %67}, db, p, 1, 1, 1;\n}\n"
        : "+f"(d[0]), "+f"(d[1]), "+f"(d[2]), "+f"(d[3]), "+f"(d[4]), "+f"(d[5]), "+f"(d[6]), "+f"(d[7]), "+f"(d[8]), "+f"(d[9]), "+f"(d[10]), "+f"(d[11]), "+f"(d[12]), "+f"(d[13]), "+f"(d[14]), "+f"(d[15]), "+f"(d[16]), "+f"(d[17]), "+f"(d[18]), "+f"(d[19]), "+f"(d[20]), "+f"(d[21]), "+f"(d[22]), "+f"(d[23]), "+f"(d[24]), "+f"(d[25]), "+f"(d[26]), "+f"(d[27]), "+f"(d[28]), "+f"(d[29]), "+f"(d[30]), "+f"(d[31]), "+f"(d[32]), "+f"(d[33]), "+f"(d[34]), "+f"(d[35]), "+f"(d[36]), "+f"(d[37]), "+f"(d[38]), "+f"(d[39]), "+f"(d[40]), "+f"(d[41]), "+f"(d[42]), "+f"(d[43]), "+f"(d[44]), "+f"(d[45]), "+f"(d[46]), "+f"(d[47]), "+f"(d[48]), "+f"(d[49]), "+f"(d[50]), "+f"(d[51]), "+f"(d[52]), "+f"(d[53]), "+f"(d[54]), "+f"(d[55]), "+f"(d[56]), "+f"(d[57]), "+f"(d[58]), "+f"(d[59]), "+f"(d[60]), "+f"(d[61]), "+f"(d[62]), "+f"(d[63])
        : "r"(a0), "r"(a1), "r"(a2), "r"(a3), "r"(db), "r"(scale_d), "n"(OB));
}

__device__ __forceinline__ uint32_t stage_addr(uint32_t block, int warp, int lane) {
    return block + (warp * 16 + (lane & 7) + ((lane >> 3) & 1) * 8) * 128 + (((lane >> 4) ^ (lane & 7)) << 4);
}
template <int OFF, int N>
__device__ __forceinline__ void stage_packed_64x64(uint32_t a0, int off, const uint32_t (&v)[N]) {
#pragma unroll
    for (int j = 0; j < 8; j += 2) {
        uint32_t a = a0;
        if (j) asm volatile("xor.b32 %0, %1, %2;" : "=r"(a) : "r"(a0), "r"(j << 4));
        stmatrix_x4(a + off, v[OFF + j * 2], v[OFF + j * 2 + 1], v[OFF + j * 2 + 2], v[OFF + j * 2 + 3]);
    }
}

template <int OFF, int N>
__device__ __forceinline__ void stage_packed_64x64(const uint32_t (&a)[4], int off, const uint32_t (&v)[N]) {
#pragma unroll
    for (int j = 0; j < 4; j++) stmatrix_x4(a[j] + off, v[OFF + j * 4], v[OFF + j * 4 + 1], v[OFF + j * 4 + 2], v[OFF + j * 4 + 3]);
}

template <int OFF, int N>
__device__ __forceinline__ void stage_packed_64x64(const uint32_t (&a)[4], int off, const uint32_t (&v)[N], bool trans) {
#pragma unroll
    for (int j = 0; j < 4; j++) stmatrix_x4(a[j] + off, v[OFF + j * 4], v[OFF + j * 4 + 1], v[OFF + j * 4 + 2], v[OFF + j * 4 + 3], trans);
}

constexpr int MAX_JOBS = 24;
constexpr int MAX_ROUNDS = 44;
constexpr int T_P = 0, T_O = 1, T_A = 2;
constexpr int HQ_A = 4, HQ_B = 28;
__host__ __device__ constexpr int unit_head(int g) { return g + (g < 4 ? HQ_A : HQ_B - 4); }
constexpr int G_STAGE = 49152;
constexpr int OFF_Q0 = 0, OFF_K0 = 32768, OFF_Q1 = 65536, OFF_K1 = 98304, OFF_V0 = 131072, OFF_V1 = 163840;
constexpr int OFF_STG = 196608;
constexpr int OFF_BAR = 229376;
constexpr int SMEM_BYTES = OFF_BAR + 640;
constexpr int TURN_THREADS = 288;

struct Params {
    CUtensorMap amap[2];
    CUtensorMap wmap[4];
    CUtensorMap x_par, wo_a, wo_b, qkv_st, qkv_ld, qkv_half, st_par, out_st;
    const __nv_bfloat16* xp;
    const __nv_bfloat16* gate_w;
    __nv_bfloat16* out;
    uint2 first[NUM_SMS];
    int16_t jobs[NUM_SMS][MAX_JOBS];
    uint16_t rounds[NUM_SMS / 2][MAX_ROUNDS];
};

constexpr int O_STAGGER = 4;
constexpr int O_F0 = 35, O_H1 = 5;
constexpr int O_FLEX = 16, O_H0 = O_F0 + 8, O_T0 = 8, O_T1 = 64 - O_F0 - O_FLEX - O_H1;
__device__ __forceinline__ int o_head(int job) { return (job & 32) ? O_H1 : O_H0; }
__device__ __forceinline__ int o_tail(int job) { return (job & 32) ? O_T1 : O_T0; }
__device__ __forceinline__ uint32_t o_state(uint32_t word, int have) {
    uint32_t v;
    asm volatile("{\n.reg .pred p, q;\n.reg .u32 c, t;\nmov.u32 c, 0;\n"
                 "SPIN:\nld.volatile.shared.u32 %0, [%1];\nand.b32 t, %0, 1;\nsetp.ne.u32 q, t, 0;\nsetp.gt.or.u32 p, %0, %2, q;\n@p bra DONE;\n"
                 "add.u32 c, c, 1;\nsetp.lt.u32 q, c, 16777216;\n@q bra SPIN;\ntrap;\nDONE:\n}"
                 : "=r"(v) : "r"(word), "r"(2 * have + 1) : "memory");
    return v;
}

template <class T> __device__ __forceinline__ T* page_ptr(int off) {
    extern __shared__ __align__(1024) uint8_t smem_raw[];
    return *reinterpret_cast<T* volatile*>(smem_raw + OFF_BAR + off);
}
template <int SLEEP_NS = 0>
__device__ __forceinline__ bool wait_flags(bool active, int idx, uint32_t target, bool block = true) {
    for (uint32_t tries = 0;; tries++) {
        const bool ok = !active | ((int32_t)(ld_acquire(g_flags + idx) - target) >= 0);
        if (__all_sync(0xffffffffu, ok)) break;
        if (!block) return false;
        if (SLEEP_NS) __nanosleep(SLEEP_NS);
        trap_if(tries > (1u << 22));
    }
    fence_async_global();
    return true;
}

__global__ void __cluster_dims__(2, 1, 1) __launch_bounds__(384, 1)
fused_kernel(const __grid_constant__ Params p) {
    extern __shared__ __align__(1024) uint8_t smem_raw[];
    const uint32_t base = smem_u32(smem_raw);
    const uint32_t bars = base + OFF_BAR;
    const uint32_t gfull = bars, gempty = bars + 32, sfull = bars + 64, sempty = bars + 96;
    const uint32_t qfull = bars + 128, qempty = bars + 144, kfull = bars + 160, kempty = bars + 176;
    const uint32_t vfull = bars + 192, vempty = bars + 208, lready = bars + 224, hout = bars + 240;
    const uint32_t tfull = bars + 256, aready = bars + 272, gatefull = bars + 280;
    const uint32_t otile = bars + 528;
    const uint32_t olim = bars + 504;
    const uint32_t stg = base + OFF_STG;
    uint32_t* rounds = reinterpret_cast<uint32_t*>(smem_raw + OFF_BAR + 416);
    const uint32_t rank = cluster_rank();
    int* jobs = reinterpret_cast<int*>(smem_raw + OFF_BAR + 312);
    auto w_map = [&](uint32_t rec, uint32_t half) INL { return &p.wmap[(rec & 8) ? 2 + half : ((rec >> 15) && half ? 0 : rec >> 4 & 1)]; };
    auto w_blk = [&](uint32_t rec, uint32_t half) INL -> int {
        const int col = rec >> 6 & 15;
        if (rec & 8) return (col + (rec & 16)) * 2;
        return rec >> 14 == 0 ? col * 4 + half * 2 : (rec >> 14 == 1 ? 16 + half * 16 + col * 2 : (half ? unit_head(col) : col) * 2);
    };
    auto load_round = [&](uint32_t rec, int st0, uint32_t parity) INL {
        const CUtensorMap* wm = w_map(rec, rank);
        const CUtensorMap* am = rec >> 14 ? &p.x_par : &p.amap[rec >> 3 & 1];
        const int wb = w_blk(rec, rank), kc0 = (rec >> 10 & 3) * 4, arow = ((rec & 7) * 256 + rank * 128) >> (rec >> 14 ? 1 : 0);
        const uint32_t bytes = (rec & 4096) ? G_STAGE - 16384 : G_STAGE, amode = (rec & 4096) ? 0 : (rec >> 14 ? 2 : 1);
#pragma unroll 1
        for (int st = st0; st < 4; st++) {
            const uint32_t sa = base + st * G_STAGE;
            mbar_wait(gempty + st * 8, parity);
            load_kstep(sa, sa + 16384 + rank * 16384, gfull + st * 8, bytes, wm, kc0 + st, wb, am, arow, kc0 + st, amode);
        }
    };
    if (threadIdx.x < 32) {
        if (elect_one()) {
            const uint2 r = p.first[blockIdx.x];
            mbar_init(gfull, 1);
            fence_async_smem();
            const char* maps;
            asm("mov.b64 %0, %1;" : "=l"(maps) : "l"(&p.amap[0]));
            asm volatile("{\n.reg .pred q;\nsetp.eq.u32 q, %8, 0;\n"
                         "mbarrier.arrive.expect_tx.shared::cta.b64 _, [%1], 49152;\n"
                         "cp.async.bulk.tensor.3d.shared::cluster.global.mbarrier::complete_tx::bytes.L2::cache_hint [%9], [%3, {0, 0, %6}], [%1], %11;\n"
                         "cp.async.bulk.tensor.3d.shared::cluster.global.mbarrier::complete_tx::bytes.L2::cache_hint [%10], [%4, {0, 0, %7}], [%1], %11;\n"
                         "@q cp.async.bulk.tensor.3d.shared::cluster.global.mbarrier::complete_tx::bytes.L2::cache_hint [%0], [%2, {0, %5, 0}], [%1], %11;\n"
                         "@!q cp.async.bulk.tensor.4d.shared::cluster.global.mbarrier::complete_tx::bytes.L2::cache_hint [%0], [%2, {0, %5, 0, 0}], [%1], %11;\n}"
                         ::"r"(base), "r"(gfull), "l"(maps + (r.x & 0x780)), "l"(maps + (r.x >> 4 & 0x780)), "l"(maps + (r.x >> 8 & 0x780)),
                           "r"(r.x >> 20), "r"(r.y & 0xffff), "r"(r.y >> 16), "r"(r.x & 1), "r"(base + 16384), "r"(base + 32768), "l"(POL_NORMAL) : "memory");
            asm volatile("fence.mbarrier_init.release.cluster;" ::: "memory");
        }
        __syncwarp();
    }
    const int tid = threadIdx.x, warp = uniform(tid >> 5), lane = tid & 31, wg = warp >> 2;
    if (warp == 1) {
        if (elect_one()) {
#pragma unroll
            for (int i = 1; i < 39; i++)
                mbar_init(bars + i * 8, (0x0CC000F0ull >> i & 1) ? 16 : ((0x300000F00ull >> i & 1) ? 4 : ((0xC0000ull >> i & 1) ? 8 : 1)));
            asm volatile("fence.mbarrier_init.release.cluster;" ::: "memory");
            fence_async_smem();
        }
        __syncwarp();
    }
    setup_arrive();
    if (warp > 3) {
        reg_inc<232>();
        named_sync(0, 352);
        const int w = wg - 1, wwarp = warp & 3;
        const uint32_t slot_a = stage_addr(stg + w * 16384, wwarp, lane);
        const uint32_t bars_peer = uniform(mapa(bars, rank ^ 1));
        auto arrive_pair = [&](uint32_t bar, bool pred = true) INL { warp_arrive_pair(bar, bars_peer + (bar - bars), pred); };
        uint32_t gph = 0;
        uint32_t sph = 1;
        int jb = 0;
        int job = uniform(jobs[0]);
        auto next_job = [&]() INL { jb++; job = uniform(jobs[jb]); };
        auto slot_wait = [&](int q) INL { mbar_wait(sempty + (w * 2 + (q & 1)) * 8, (q >> 1) ^ sph ^ 1); };
        auto signal = [&](int q) INL {
            __syncwarp();
            warp_arrive(sfull + (w * 2 + (q & 1)) * 8);
        };
        uint32_t pk[64];
        float O[64];
        float oscale1 = 1.f;
        uint32_t slot4[4];
        bool ptrans = false;
        auto stage_quarter = [&](const int Q) INL {
            slot_wait(Q);
            if (Q == 0) stage_packed_64x64<0>(slot4, 0, pk, ptrans);
            if (Q == 1) stage_packed_64x64<16>(slot4, 8192, pk, ptrans);
            if (Q == 2) stage_packed_64x64<32>(slot4, 0, pk);
            if (Q == 3) stage_packed_64x64<48>(slot4, 8192, pk);
        };
        auto stage_pair = [&]() INL {
            slot_wait(1);
            stage_packed_64x64<0>(slot4, 0, pk, ptrans);
            stage_packed_64x64<16>(slot4, 8192, pk, ptrans);
        };
        auto signal_both = [&]() INL {
            __syncwarp();
            warp_arrive2(sfull + w * 16, sfull + w * 16 + 8);
        };
        uint32_t un = 0;
        auto lane_id = [&]() INL { uint32_t ln; asm volatile("mov.u32 %0, %%laneid;" : "=r"(ln)); return ln; };
        auto v_addr = [&](uint32_t ln) INL { return stg + w * 16384 + (wwarp * 16 + (ln & 7)) * 128 + (((ln >> 3) ^ (ln & 7)) << 4); };
        auto v_off = [&](uint32_t a, const int h) INL { return (a ^ ((h & 1) * 64)) + (h >> 1) * 8192; };
        auto halo_ptr = [&](int mt, int g, int slot, uint32_t ln) INL { return page_ptr<uint4>(512) + (((mt * 8 + g) * 2 + w) * 5 + slot) * 128 + ln; };
        auto pack_k = [&](const float (&acc)[64]) INL {
#pragma unroll
            for (int j = 0; j < 16; j++) { pk[j] = pack_bf16(acc[4 * j], acc[4 * j + 1]); pk[16 + j] = pack_bf16(acc[4 * j + 2], acc[4 * j + 3]); }
        };
        auto unit_export = [&](int cur) INL {
            const uint32_t ln = lane_id();
            uint4* dst = halo_ptr((cur & 7) * 2 + rank, cur >> 3 & 7, wwarp, ln);
            slot_wait(1);
            stage_packed_64x64<32>(slot4, 0, pk);
            stage_packed_64x64<48>(slot4, 8192, pk);
#pragma unroll
            for (int h = 0; h < 4; h++) __stcg(dst + h * 32, make_uint4(pk[16 + h * 4], pk[17 + h * 4], pk[18 + h * 4], pk[19 + h * 4]));
            __syncwarp();
            if (wwarp == 3) {
                const uint32_t va = v_addr(ln) + 1024;
#pragma unroll
                for (int h = 0; h < 4; h++) {
                    uint32_t t[4];
                    ldmatrix_x4_t(v_off(va, h), t);
                    pk[32 + h * 4] = t[0]; pk[33 + h * 4] = t[1]; pk[34 + h * 4] = t[2]; pk[35 + h * 4] = t[3];
                }
#pragma unroll
                for (int h = 0; h < 4; h++) __stcg(dst + 128 + h * 32, make_uint4(pk[32 + h * 4], pk[33 + h * 4], pk[34 + h * 4], pk[35 + h * 4]));
                __syncwarp();
                warp_arrive(hout + w * 8);
            }
        };
        auto unit_import = [&](int cur) INL {
            const uint32_t ln = lane_id();
            const int mt = (cur & 7) * 2 + rank;
            mbar_wait(lready + un * 8, 0);
            un++;
            const uint4* src = halo_ptr(wwarp ? mt : max(mt - 1, 0), cur >> 3 & 7, (wwarp + 3) & 3, ln);
#pragma unroll
            for (int h = 0; h < 4; h++) {
                const uint4 t = __ldcg(src + h * 32);
                pk[32 + h * 4] = t.x; pk[33 + h * 4] = t.y; pk[34 + h * 4] = t.z; pk[35 + h * 4] = t.w;
            }
            if (wwarp) {
                const uint32_t va = v_addr(ln) - 1024;
#pragma unroll
                for (int h = 0; h < 4; h++) {
                    uint32_t t[4];
                    ldmatrix_x4_t(v_off(va, h), t);
                    pk[48 + h * 4] = t[0]; pk[49 + h * 4] = t[1]; pk[50 + h * 4] = t[2]; pk[51 + h * 4] = t[3];
                }
            } else {
#pragma unroll
                for (int h = 0; h < 4; h++) {
                    const uint4 t = __ldcg(src + 128 + h * 32);
                    pk[48 + h * 4] = t.x; pk[49 + h * 4] = t.y; pk[50 + h * 4] = t.z; pk[51 + h * 4] = t.w;
                }
            }
        };
        auto unit_attend = [&](const float (&q)[64], int cur) INL {
            const float cs = 0.17677669529663687f * 1.4426950408889634f;
            const uint32_t ln = lane_id();
            const int g = ln >> 2, c2 = (ln & 3) * 2, mt = (cur & 7) * 2 + rank;
            uint32_t qf[32], vo[8][4];
#pragma unroll
            for (int i = 0; i < 32; i++) qf[i] = pack_bf16(q[2 * i], q[2 * i + 1]);
            fence_regs(qf);
            const float* gp = page_ptr<float>(520) + mt * 128 + wwarp * 32 + g * 2 + w;
            const float lg0 = 1.f - __ldcg(gp), lg1 = 1.f - __ldcg(gp + 16);
            const uint32_t va = stg + w * 16384 + (wwarp * 16 + (ln & 7) + (ln >> 4) * 8) * 128 + ((((ln >> 3) & 1) ^ (ln & 7)) << 4);
#pragma unroll
            for (int i = 0; i < 8; i++) ldmatrix_x4_t((va ^ ((i & 3) * 32)) + (i >> 2) * 8192, vo[i]);
            const bool m0 = c2 > g, m1 = c2 + 1 > g, first = mt + wwarp == 0;
            const uint32_t mk = (m0 ? 0xffffu : 0u) | (m1 ? 0xffff0000u : 0u);
#pragma unroll
            for (int h = 0; h < 4; h++) {
                float s[3][4] = {};
#pragma unroll
                for (int k = 0; k < 2; k++) {
                    const int i = h * 8 + k * 4, j = h * 4 + k * 2;
                    mma_16816(s[0], qf[i], qf[i + 1], qf[i + 2], qf[i + 3], pk[32 + j], pk[33 + j]);
                    mma_16816(s[1], qf[i], qf[i + 1], qf[i + 2], qf[i + 3], pk[j], pk[j + 1]);
                    mma_16816(s[2], qf[i], qf[i + 1], qf[i + 2], qf[i + 3], pk[16 + j], pk[17 + j]);
                }
                if (first) s[0][0] = s[0][1] = -INFINITY;
                float u0 = m0 ? s[0][0] : s[1][0], u1 = m1 ? s[0][1] : s[1][1], v0 = m0 ? s[1][2] : s[2][2], v1 = m1 ? s[1][3] : s[2][3];
                float mu = fmaxf(u0, u1), mv = fmaxf(v0, v1);
                mu = fmaxf(mu, __shfl_xor_sync(0xffffffffu, mu, 1)); mv = fmaxf(mv, __shfl_xor_sync(0xffffffffu, mv, 1));
                mu = fmaxf(mu, __shfl_xor_sync(0xffffffffu, mu, 2)); mv = fmaxf(mv, __shfl_xor_sync(0xffffffffu, mv, 2));
                mu *= -cs; mv *= -cs;
                u0 = ex2(fmaf(u0, cs, mu)); u1 = ex2(fmaf(u1, cs, mu)); v0 = ex2(fmaf(v0, cs, mv)); v1 = ex2(fmaf(v1, cs, mv));
                float lu = u0 + u1, lv = v0 + v1;
                lu += __shfl_xor_sync(0xffffffffu, lu, 1); lv += __shfl_xor_sync(0xffffffffu, lv, 1);
                lu += __shfl_xor_sync(0xffffffffu, lu, 2); lv += __shfl_xor_sync(0xffffffffu, lv, 2);
                const float su = lg0 * rcp(lu), sv = lg1 * rcp(lv);
                const uint32_t pu = pack_bf16(u0 * su, u1 * su), pv = pack_bf16(v0 * sv, v1 * sv);
#pragma unroll
                for (int d = 0; d < 2; d++) {
                    const uint32_t (&vv)[4] = vo[h * 2 + d];
                    float oa[4] = {}, ob[4] = {};
                    mma_16816(oa, pk[48 + h * 4 + d * 2], pk[49 + h * 4 + d * 2], vv[0], vv[1], pu & mk, pu & ~mk);
                    mma_16816(ob, vv[0], vv[1], vv[2], vv[3], pv & mk, pv & ~mk);
                    qf[h * 8 + d * 4] = pack_bf16(oa[0], oa[1]); qf[h * 8 + d * 4 + 1] = pack_bf16(ob[0], ob[1]);
                    qf[h * 8 + d * 4 + 2] = pack_bf16(oa[2], oa[3]); qf[h * 8 + d * 4 + 3] = pack_bf16(ob[2], ob[3]);
                }
            }
#pragma unroll
            for (int i = 0; i < 32; i++) pk[i] = qf[i];
            named_sync(3 + w, 128);
        };
        auto pack_half = [&](const float (&acc)[64], const int OFF, float scale) INL {
#pragma unroll
            for (int i = 0; i < 32; i++) pk[OFF + i] = pack_bf16(acc[2 * i] * scale, acc[2 * i + 1] * scale);
        };
        auto gemm_run = [&]() INL {
                float acc0[64], acc1[64];
#pragma unroll
                for (int i = 0; i < 64; i++) pk[i] = 0;
#pragma unroll
                for (int j = 0; j < 4; j++) asm volatile("xor.b32 %0, %1, %2;" : "=r"(slot4[j]) : "r"(slot_a), "r"(j << 5));
                const uint32_t dA = desc_lo(base + w * 8192, 0), dB = desc_lo(base + 16384, 8192);
                auto wait_full = [&](int st) INL { mbar_wait_hot(gfull + st * 8, gph); };
                auto release = [&](int st) INL { arrive_pair(gempty + st * 8); };
                bool pend = false;
                auto kstep = [&](auto st_, const int Q, bool ending = false) INL {
                    constexpr int st = decltype(st_)::v, OA = st * (G_STAGE >> 4);
                    const bool held = st == 2 && ending && w;
                    if (st == 2 && __builtin_expect(held, 0)) {
                        wg_wait<0>();
                        release(1);
                        named_sync(6, 256);
                    }
                    wait_full(st);
                    wg_fence();
                    wgmma_ss_n256<OA, OA>(acc0, acc1, dA, dB);
                    wg_commit();
                    wg_wait<1>();
                    arrive_pair(gempty + ((st + 3) & 3) * 8, !held);
                    wg_fence();
                    wgmma_ss_n256<OA + 2, OA + 128>(acc0, acc1, dA, dB);
                    wgmma_ss_n256<OA + 4, OA + 256>(acc0, acc1, dA, dB);
                    if (st == 3) named_arrive_if(ending && !w, 6, 256);
                    wgmma_ss_n256<OA + 6, OA + 384>(acc0, acc1, dA, dB);
                    wg_commit();
                    if (Q >= 0) { stage_quarter(Q); signal(Q); }
                    KTRACE(w);
                };
                wait_full(0);
                GTRACE(w);
                while (true) {
                    wg_fence();
                    wgmma_ss_n256_init(acc0, acc1, dA, dB);
                    wgmma_ss_n256<2, 128>(acc0, acc1, dA, dB);
                    wgmma_ss_n256<4, 256>(acc0, acc1, dA, dB);
                    wgmma_ss_n256<6, 384>(acc0, acc1, dA, dB);
                    wg_commit();
                    KTRACE(w);
                    const int cur = job;
                    const bool is_o = cur >= (T_O << 12), unit2 = (cur >> 6) == 3;
                    const int tail = o_tail(cur);
                    int lim = is_o ? o_head(cur) + tail : (cur < 256 ? 16 : 8);
                    int left = unit2 ? 11 : lim - (is_o ? O_STAGGER + 1 : 1);
                    bool imp = unit2;
                    next_job();
                    if (__builtin_expect(unit2, 0)) { if (tid == TRACE_TID) PTRACE(4); unit_export(cur); if (tid == TRACE_TID) PTRACE(5); }
                    if (pend) {
                        kstep(IC<1>{}, 0);
                        kstep(IC<2>{}, -1);
                        kstep(IC<3>{}, 1);
                        GTRACE(w);
                        gph ^= 1;
                        kstep(IC<0>{}, -1);
                        kstep(IC<1>{}, 2);
                        kstep(IC<2>{}, 3, left == 7);
                        kstep(IC<3>{}, -1, left == 7);
                        GTRACE(w);
                        gph ^= 1;
                        left -= 7;
                        if (left > 0) { kstep(IC<0>{}, -1); left--; }
                    }
                    int last_st = 3;
#pragma unroll 1
                    while (left > 0) {
                        auto ends = [&]() INL -> bool {
                            if (__builtin_expect(--left > 0, 1)) return false;
                            if (is_o) {
                                const uint32_t v = uniform(o_state(olim, lim - tail));
                                const int n = (v >> 1) + ((v & 1) ? 0 : tail);
                                left = n - lim; lim = n;
                            }
                            return left == 0;
                        };
                        kstep(IC<1>{}, -1);
                        if (ends()) { last_st = 1; break; }
                        kstep(IC<2>{}, -1, left == 2 && !is_o && !imp);
                        if (ends()) { last_st = 2; break; }
                        kstep(IC<3>{}, -1, left == 1 && !is_o && !imp);
                        GTRACE(w);
                        gph ^= 1;
                        if (ends()) {
                            if (!imp) break;
                            if (tid == TRACE_TID) PTRACE(6);
                            unit_import(cur);
                            if (tid == TRACE_TID) PTRACE(7);
                            imp = false; left = 4;
                        }
                        kstep(IC<0>{}, -1);
                        if (ends()) { last_st = 0; break; }
                    }
                    if (is_o) {
                        if (w) {
                            wg_wait<0>();
                            release(last_st);
                            named_sync(6, 256);
                        }
#pragma unroll 1
                        for (int i = 1; i <= O_STAGGER; i++) {
                            const int st = (last_st + i) & 3;
                            if (i > 1 && st == 0) gph ^= 1;
                            wait_full(st);
                            const uint32_t a = dA + st * (G_STAGE >> 4), b = dB + st * (G_STAGE >> 4);
                            wg_fence();
                            wgmma_ss_n256<0, 0>(acc0, acc1, a, b);
                            wgmma_ss_n256<2, 128>(acc0, acc1, a, b);
                            wgmma_ss_n256<4, 256>(acc0, acc1, a, b);
                            wgmma_ss_n256<6, 384>(acc0, acc1, a, b);
                            wg_commit();
                            named_arrive_if(!w && i == O_STAGGER, 6, 256);
                            wg_wait<1>();
                            arrive_pair(gempty + last_st * 8, i == 1 && !w);
                        }
                        slot_wait(1);
                        wg_wait<0>();
                        fence_regs(acc0);
                        fence_regs(acc1);
                        auto put = [&](const float (&acc)[64], const int Q, int off) INL {
#pragma unroll
                            for (int j = 0; j < 4; j++) {
                                const float* o = acc + Q * 32 + j * 8;
                                stmatrix_x4(slot4[j] + off, pack_bf16(o[0], o[1]), pack_bf16(o[2], o[3]), pack_bf16(o[4], o[5]), pack_bf16(o[6], o[7]));
                            }
                        };
                        put(acc0, 0, 0);
                        signal(0);
                        put(acc0, 1, 8192);
                        signal(1);
                        put(acc1, 0, -OFF_STG - w * 8192);
                        put(acc1, 1, G_STAGE - OFF_STG - w * 8192);
                        __syncwarp();
                        warp_arrive(tfull + w * 8);
#pragma unroll
                        for (int i = 1; i <= O_STAGGER; i++) release((last_st + i) & 3);
                        GTRACE(w);
#pragma unroll
                        for (int i = 0; i < 64; i++) O[i] = 0.f;
                        break;
                    }
                    if (tid == 128 && !is_o) PTRACE(12);
                    oscale1 = cur < 128 || unit2 ? Q_SCALE : 1.f;
                    ptrans = unit2;
                    if (tid == TRACE_TID && unit2) PTRACE(1);
                    named_arrive_if(w && job >= (T_A << 12), 1, TURN_THREADS);
                    wg_wait<0>();
                    fence_regs(acc0);
                    fence_regs(acc1);
                    release(3);
                    if (tid == TRACE_TID && unit2) PTRACE(2);
                    if (__builtin_expect(unit2, 0)) { unit_attend(acc0, cur); if (tid == TRACE_TID) PTRACE(3); }
                    else if (__builtin_expect((cur >> 6) == 2, 0)) pack_k(acc0);
                    else if (cur < 128) pack_half(acc0, 0, Q_SCALE);
                    else pack_half(acc0, 0, 1.f);
                    if (job >= (T_A << 12)) {
                        stage_pair();
                        signal_both();
#pragma unroll
                        for (int i = 0; i < 64; i++) asm volatile("mul.f32 %0, %1, %2;" : "=f"(O[i]) : "f"(acc1[i]), "f"(oscale1));
                        break;
                    }
                    if (cur < 128 || unit2) pack_half(acc1, 32, Q_SCALE);
                    else pack_half(acc1, 32, 1.f);
                    fence_regs(pk);
                    wait_full(0);
                    pend = (cur >> 6) != 2;
                }
        };
        setup_wait();
#pragma unroll 1
        while (true) {
        gemm_run();
        if (job < 0) break;
        if (tid == 128) PTRACE(11);
        GTRACE(w);
        {
            {
                sph ^= 1;
                uint32_t step = ~0u, ajob = ~0u;
                const int r0 = w * 64 + wwarp * 16 + (lane >> 2);
                float S[64];
                uint32_t P[32] = {};
                fence_regs(P);
                float m0 = 0.f, m1 = 0.f, l0 = 0.25f, l1 = 0.25f, g0 = 1.f, g1 = 1.f, e0 = 0.f, e1 = 0.f;
                constexpr float SUM_MAX = 1.1529215e18f;
                float sum_max = SUM_MAX;
                float sum_min = (lane & 3) == 0 ? 8.6736174e-19f : -1.f;
                asm volatile("" : "+f"(sum_min));
                int rem = 0;
                int maskrem = 0;
                uint32_t starts = 1;
                auto issue_S = [&]() INL {
                    const uint32_t da = desc_lo(base + OFF_Q0 + w * 8192, 0) + (ajob & 1) * ((OFF_Q1 - OFF_Q0) >> 4);
                    const uint32_t db = desc_lo(base + OFF_K0, 0) + (step & 1) * ((OFF_K1 - OFF_K0) >> 4);
                    wg_fence();
                    wgmma_ss_n128_init<0, 0, 0>(S, da, db);
                    wgmma_ss_n128_tb0<2, 2>(S, da, db, 1);
                    wgmma_ss_n128_tb0<4, 4>(S, da, db, 1);
                    wgmma_ss_n128_tb0<6, 6>(S, da, db, 1);
                    wgmma_ss_n128_tb0<1024, 1024>(S, da, db, 1);
                    wgmma_ss_n128_tb0<1026, 1026>(S, da, db, 1);
                    wgmma_ss_n128_tb0<1028, 1028>(S, da, db, 1);
                    wgmma_ss_n128_tb0<1030, 1030>(S, da, db, 1);
                    wg_commit();
                };
                auto issue_PV = [&](uint32_t t, int pass) INL {
                    const uint32_t db = desc_lo(base + OFF_V0, 16384) + (t & 1) * ((OFF_V1 - OFF_V0) >> 4);
                    mbar_wait_hot(vfull + (t & 1) * 8, (t >> 1) & 1);
                    wg_fence();
                    wgmma_rs_n128_tb1<0>(O, P[0], P[1], P[2], P[3], db, !(starts & 2));
                    wgmma_rs_n128_tb1<128>(O, P[4], P[5], P[6], P[7], db, 1);
                    wgmma_rs_n128_tb1<256>(O, P[8], P[9], P[10], P[11], db, 1);
                    wgmma_rs_n128_tb1<384>(O, P[12], P[13], P[14], P[15], db, 1);
                    if (pass) named_arrive(pass, TURN_THREADS);
                    wgmma_rs_n128_tb1<512>(O, P[16], P[17], P[18], P[19], db, 1);
                    wgmma_rs_n128_tb1<640>(O, P[20], P[21], P[22], P[23], db, 1);
                    wgmma_rs_n128_tb1<768>(O, P[24], P[25], P[26], P[27], db, 1);
                    wgmma_rs_n128_tb1<896>(O, P[28], P[29], P[30], P[31], db, 1);
                    wg_commit();
                };
                auto pv_done = [&](uint32_t t) INL {
                    wg_wait<0>();
                    fence_regs(O);
                    arrive_pair(vempty + (t & 1) * 8, t != ~0u);
                };
                auto row_max = [&](float& a0, float& a1) INL {
                    a0 = fmaxf(S[0], S[1]); a1 = fmaxf(S[2], S[3]);
#pragma unroll
                    for (int j = 1; j < 16; j++) {
                        a0 = fmaxf(a0, fmaxf(S[j * 4], S[j * 4 + 1]));
                        a1 = fmaxf(a1, fmaxf(S[j * 4 + 2], S[j * 4 + 3]));
                    }
                    a0 = fmaxf(a0, __shfl_xor_sync(0xffffffffu, a0, 1));
                    a1 = fmaxf(a1, __shfl_xor_sync(0xffffffffu, a1, 1));
                    a0 = fmaxf(a0, __shfl_xor_sync(0xffffffffu, a0, 2));
                    a1 = fmaxf(a1, __shfl_xor_sync(0xffffffffu, a1, 2));
                };
                auto mask_diag = [&]() INL {
                    const int d = (r0 & 63) - (lane & 3) * 2;
                    auto mask_block = [&](const int J0) INL {
                        bool up0 = false, up1 = false;
#pragma unroll
                        for (int j = 0; j < 8; j++) {
                            const bool c0 = j * 8 > d, c1 = j * 8 + 1 > d;
                            if (c0) S[(J0 + j) * 4] = -INFINITY;
                            if (c1) S[(J0 + j) * 4 + 1] = -INFINITY;
                            if (up0) S[(J0 + j) * 4 + 2] = -INFINITY;
                            if (up1) S[(J0 + j) * 4 + 3] = -INFINITY;
                            up0 = c0; up1 = c1;
                        }
                    };
                    if (w) {
                        mask_block(8);
                    } else {
                        mask_block(0);
#pragma unroll
                        for (int i = 32; i < 64; i++) S[i] = -INFINITY;
                    }
                };
                auto exp_part = [&](float& t0, float& t1, const int J0, const int J1, const bool SUB) INL {
#pragma unroll
                    for (int j = J0; j < J1; j++) {
                        const float e0 = ex2(SUB ? S[j * 4] - m0 : S[j * 4]), e1 = ex2(SUB ? S[j * 4 + 1] - m0 : S[j * 4 + 1]);
                        const float e2 = ex2(SUB ? S[j * 4 + 2] - m1 : S[j * 4 + 2]), e3 = ex2(SUB ? S[j * 4 + 3] - m1 : S[j * 4 + 3]);
                        t0 = (j ? t0 : l0) + (e0 + e1);
                        t1 = (j ? t1 : l1) + (e2 + e3);
                        P[j * 2] = pack_bf16(e0, e1);
                        P[j * 2 + 1] = pack_bf16(e2, e3);
                    }
                };
                auto exp_head = [&](float& t0, float& t1, auto j1_) INL {
                    constexpr int J1 = decltype(j1_)::v;
                    float E[J1 * 4];
#pragma unroll
                    for (int j = 0; j < J1; j++) {
#pragma unroll
                        for (int e = 0; e < 4; e++) E[j * 4 + e] = ex2(S[j * 4 + e]);
                        t0 = (j ? t0 : l0) + (E[j * 4] + E[j * 4 + 1]);
                        t1 = (j ? t1 : l1) + (E[j * 4 + 2] + E[j * 4 + 3]);
                    }
                    order_after(t0 + t1, bars + 508);
                    pv_done(step - 1);
                    fence_regs(P);
                    fence_regs(S);
                    fence_regs(E);
#pragma unroll
                    for (int i = 0; i < J1 * 2; i++) P[i] = pack_bf16(E[i * 2], E[i * 2 + 1]);
                };
                auto close_job = [&]() INL {
                    l0 += __shfl_xor_sync(0xffffffffu, l0, 1); l1 += __shfl_xor_sync(0xffffffffu, l1, 1);
                    l0 += __shfl_xor_sync(0xffffffffu, l0, 2); l1 += __shfl_xor_sync(0xffffffffu, l1, 2);
                    e0 = g0 * rcp(l0); e1 = g1 * rcp(l1);
                };
                auto put_O = [&]() INL {
                    mbar_wait_hot(sempty + (w * 2 + 1) * 8, sph ^ 1);
                    uint32_t a[4];
#pragma unroll
                    for (int j = 0; j < 4; j++) asm volatile("xor.b32 %0, %1, %2;" : "=r"(a[j]) : "r"(slot_a), "r"(j << 5));
                    const uint32_t h0 = pack_bf16(e0, e0), h1 = pack_bf16(e1, e1);
#pragma unroll
                    for (int q = 0; q < 8; q++) {
                        const float* o = O + q * 8;
                        stmatrix_x4(a[q & 3] + (q >> 2) * 8192, mul_bf16x2(pack_bf16(o[0], o[1]), h0), mul_bf16x2(pack_bf16(o[2], o[3]), h1),
                                    mul_bf16x2(pack_bf16(o[4], o[5]), h0), mul_bf16x2(pack_bf16(o[6], o[7]), h1));
                    }
                    sph ^= 1;
                    signal_both();
                };
                auto exp_plain = [&](float& t0, float& t1) INL {
                    exp_head(t0, t1, IC<6>{});
                    exp_part(t0, t1, 6, 16, false);
                    fence_regs(P);
                };
                auto exp_diag = [&](float& t0, float& t1) INL {
                    const int d = warp - 4, dd = (r0 & 7) - (int)(slot_a >> 6 & 6);
                    auto tri = [&](const int B) INL {
                        if (0 > dd) S[8 * B] = S[8 * B + 6] = -INFINITY;
                        if (1 > dd) S[8 * B + 1] = S[8 * B + 7] = -INFINITY;
                        S[8 * B + 4] = S[8 * B + 5] = -INFINITY;
                        asm volatile("" ::: "memory");
                    };
                    auto blocks = [&](const int B) INL {
                        auto zero = [&](const int B0) INL {
#pragma unroll
                            for (int i = 4 * B0; i < 4 * B + 12; i++) P[i] = 0;
                            asm volatile("" ::: "memory");
                        };
                        auto block = [&](const int B0) INL { exp_part(t0, t1, 2 * B0, 2 * B0 + 2, false); asm volatile("" ::: "memory"); };
                        if (d < B) zero(B);
                        else {
                            block(B);
                            if (d < B + 1) zero(B + 1);
                            else {
                                block(B + 1);
                                if (d < B + 2) zero(B + 2); else block(B + 2);
                            }
                        }
                    };
                    if (d > 3) {
                        if (d < 6) { if (d == 4) tri(4); else tri(5); } else { if (d == 6) tri(6); else tri(7); }
                        exp_head(t0, t1, IC<5>{});
                        exp_part(t0, t1, 5, 10, false);
                        blocks(5);
                    } else {
                        if (d < 2) { if (d == 0) tri(0); else tri(1); } else { if (d == 2) tri(2); else tri(3); }
                        exp_head(t0, t1, IC<2>{});
#pragma unroll
                        for (int i = 16; i < 32; i++) P[i] = 0;
                        blocks(1);
                    }
                    fence_regs(P);
                };
                auto unsafe_tile = [&](float t0, float t1) INL -> bool {
                    const bool unsafe = !(t0 + t1 <= sum_max) | !(fminf(t0, t1) >= sum_min);
                    return __any_sync(0xffffffffu, unsafe);
                };
                auto redo_tile = [&](float& t0, float& t1, bool fresh) INL {
                    wg_wait<0>();
                    fence_regs(O);
                    if (rem == maskrem) mask_diag();
                    float a0, a1;
                    row_max(a0, a1);
                    if (!fresh) { a0 = fmaxf(a0, m0); a1 = fmaxf(a1, m1); }
                    const float c0 = fresh ? 1.f : ex2(m0 - a0), c1 = fresh ? 1.f : ex2(m1 - a1);
                    m0 = a0; m1 = a1; sum_max = -1.f;
                    l0 *= c0; l1 *= c1;
#pragma unroll
                    for (int j = 0; j < 16; j++) { O[j * 4] *= c0; O[j * 4 + 1] *= c0; O[j * 4 + 2] *= c1; O[j * 4 + 3] *= c1; }
                    exp_part(t0, t1, 0, 16, true);
                };
                auto finish = [&]() INL {
                    if (starts & 2) put_O();
                    named_sync(1 + w, TURN_THREADS);
                    TRACE_MARK(0, w, step + 1);
                    issue_PV(step, w == 0 ? 2 : 0);
                    close_job();
                    pv_done(step);
                    put_O();
                };
                int njob;
                auto open_job = [&]() INL {
                    ajob++; rem = (job & 15) + 1; maskrem = (job & 512) ? 0 : job & 15;
                    njob = jobs[jb + 1];
                };
                auto do_step = [&]() INL -> bool {
                    float t0, t1;
                    const bool fresh = starts & 1, pending = starts & 2;
                    rem--; step++;
                    named_sync(1 + w, TURN_THREADS);
                    TRACE_MARK(0, w, step);
                    issue_S();
                    uint32_t ob[18];
#pragma unroll
                    for (int i = 0; i < 18; i++) asm volatile("" : "=r"(ob[i]));
                    if (__builtin_expect(pending || fresh, 0)) {
                        if (pending) {
                            const uint32_t h0 = pack_bf16(e0, e0), h1 = pack_bf16(e1, e1);
                            mbar_wait_hot(sempty + (w * 2 + 1) * 8, sph ^ 1);
#pragma unroll
                            for (int q = 0; q < 4; q++) {
                                const float* o = O + q * 8;
                                uint32_t a;
                                asm volatile("xor.b32 %0, %1, %2;" : "=r"(a) : "r"(slot_a), "r"(q << 5));
                                stmatrix_x4(a, mul_bf16x2(pack_bf16(o[0], o[1]), h0), mul_bf16x2(pack_bf16(o[2], o[3]), h1),
                                            mul_bf16x2(pack_bf16(o[4], o[5]), h0), mul_bf16x2(pack_bf16(o[6], o[7]), h1));
                            }
#pragma unroll
                            for (int i = 0; i < 16; i++) ob[i] = pack_bf16(O[32 + 2 * i], O[33 + 2 * i]);
                            ob[16] = h0; ob[17] = h1;
                            fence_regs(ob);
                        }
                        if (fresh) {
                            close_job();
                            g0 = __ldcg(g_gate + (job & 15) * 128 + r0); g1 = __ldcg(g_gate + (job & 15) * 128 + r0 + 8);
                            l0 = 0.f; l1 = 0.f; m0 = 0.f; m1 = 0.f; sum_max = SUM_MAX;
                            if (step == 0) {
                                wg_fence();
                                wg_commit();
                                named_arrive(2 - w, TURN_THREADS);
                                goto issued;
                            }
                        }
                    }
                    issue_PV(step - 1, 2 - w);
                    if (__builtin_expect(pending, 0)) {
#pragma unroll
                        for (int q = 0; q < 4; q++) {
                            uint32_t a;
                            asm volatile("xor.b32 %0, %1, %2;" : "=r"(a) : "r"(slot_a), "r"(q << 5));
                            stmatrix_x4(a + 8192, mul_bf16x2(ob[q * 4], ob[16]), mul_bf16x2(ob[q * 4 + 1], ob[17]),
                                        mul_bf16x2(ob[q * 4 + 2], ob[16]), mul_bf16x2(ob[q * 4 + 3], ob[17]));
                        }
                        sph ^= 1;
                        signal_both();
                    }
                issued:
                    starts = (starts << 1 & 2) | (rem == 0);
                    TRACE_MARK(1, w, step);
                    wg_wait<1>();
                    fence_regs(S);
                    arrive_pair(kempty + (step & 1) * 8);
                    TRACE_MARK(2, w, step);
                    warp_arrive(qempty + (ajob & 1) * 8, rem == 0);
                    bool bad;
                    if (__builtin_expect(rem != maskrem, 1)) {
                        exp_plain(t0, t1);
                        bad = unsafe_tile(t0, t1);
                        if (__builtin_expect(!bad && rem != 0, 1)) {
                            l0 = t0; l1 = t1;
                            TRACE_MARK(3, w, step);
                            return true;
                        }
                    } else {
                        exp_diag(t0, t1);
                        bad = unsafe_tile(t0, t1);
                    }
                    if (bad) redo_tile(t0, t1, fresh);
                    l0 = t0; l1 = t1;
                    TRACE_MARK(3, w, step);
                    if (rem == 0) {
                        jb++;
                        job = uniform(njob);
                        if ((job >> 12) != T_A) return false;
                        open_job();
                    }
                    return true;
                };
                open_job();
#pragma unroll 1
                while (do_step()) {}
                finish();
            }
        }
        GTRACE(w);
        jb = uniform(jb); job = uniform(job); sph = uniform(sph); gph = uniform(gph);
        if (job < 0) break;
        }
    } else {
        reg_dec<40>();
        if (base & 1023) __trap();
        if (warp == 0) {
            const uint2 r = p.first[blockIdx.x];
            const char* maps = reinterpret_cast<const char*>(&p.amap[0]);
            const CUtensorMap* wm = reinterpret_cast<const CUtensorMap*>(maps + (r.x >> (rank ? 8 : 4) & 0x780));
            const CUtensorMap* am = reinterpret_cast<const CUtensorMap*>(maps + (r.x & 0x780));
            const int wb = rank ? r.y >> 16 : r.y & 0xffff;
            setup_wait();
#pragma unroll 1
            for (int st = 1; st < 4; st++) {
                const uint32_t sa = base + st * G_STAGE;
                load_kstep(sa, sa + 16384 + rank * 16384, gfull + st * 8, G_STAGE, wm, st, wb, am, r.x >> 20, st, 1 + (r.x & 1));
            }
            named_sync(7, 96);
        } else {
            if (warp == 2) {
                const int jl = lane < MAX_JOBS ? p.jobs[blockIdx.x][lane] : -1;
                if (lane <= MAX_JOBS) jobs[lane] = jl;
                if ((jl >> 12) == T_O) *reinterpret_cast<volatile uint32_t*>(smem_raw + OFF_BAR + 504) = 2 * o_head(jl);
                if (lane == 31) *reinterpret_cast<volatile uint32_t*>(smem_raw + OFF_BAR + 528) = 0;
            } else if (warp == 3) {
                if (lane == 31) *reinterpret_cast<ulonglong2*>(smem_raw + OFF_BAR + 512) = make_ulonglong2((uint64_t)g_halo, (uint64_t)g_gate);
                if (lane < MAX_ROUNDS / 2) rounds[lane] = reinterpret_cast<const uint32_t*>(p.rounds[blockIdx.x >> 1])[lane];
            }
            named_arrive_if(warp > 1, 7, 96);
            named_sync(0, 352);
            setup_wait();
        }
        volatile uint32_t* epoch_word = reinterpret_cast<volatile uint32_t*>(smem_raw + OFF_BAR + 532);
        uint32_t epoch1 = 0;
        if (warp > 0) {
        if (warp == 3) { epoch1 = uniform(ld_acquire(g_flags + F_DONE)) / NUM_SMS + 1; if (lane == 0) *epoch_word = epoch1; }
        {
            if (warp == 1 && elect_one()) {
#pragma unroll
                for (int i = 0; i < 7; i++) prefetch_map(&p.amap[0] + i);
            }
            __syncwarp();
            if (warp < 3) __nanosleep(jobs[0] < 256 ? GATE_DELAY_LONG_NS : GATE_DELAY_SHORT_NS);
            if (tid == TRACE_GATE) PTRACE(10);
            float* gate_vals = reinterpret_cast<float*>(smem_raw + OFF_BAR + 576);
            if (warp == 3) {
                if (blockIdx.x == 0) g_flags[F_SPLIT + lane] = g_flags[F_TICKET + lane] = 0;
                named_sync(5, 96);
                if (lane < 16 && blockIdx.x + lane * NUM_SMS < SEQ) g_gate[blockIdx.x + lane * NUM_SMS] = 1.f / (1.f + __expf(-gate_vals[lane]));
                if (tid == TRACE_GATE) PTRACE(9);
                __threadfence();
                __syncwarp();
                if (lane == 0) red_release(g_flags + F_GATE);
            } else {
                const uint32_t bar = gatefull + (warp - 1) * 16;
                auto fetch = [&](int r) INL {
                    if (lane == 0) mbar_expect_tx(bar + (r & 2) * 4, 4096);
                    __syncwarp();
                    if (lane < 2) asm volatile("cp.async.bulk.shared::cluster.global.mbarrier::complete_tx::bytes [%0], [%1], 2048, [%2];"
                                               ::"r"(stg + ((warp - 1) * 8 + r + lane) * 2048), "l"(p.xp + (size_t)min((int)blockIdx.x + ((warp - 1) * 8 + r + lane) * NUM_SMS, SEQ - 1) * DM), "r"(bar + (r & 2) * 4) : "memory");
                };
                fetch(0); fetch(2);
                uint32_t gw[16];
#pragma unroll
                for (int i = 0; i < 4; i++) {
                    const uint4 t = __ldg(reinterpret_cast<const uint4*>(p.gate_w) + i * 32 + lane);
                    gw[i * 4] = t.x; gw[i * 4 + 1] = t.y; gw[i * 4 + 2] = t.z; gw[i * 4 + 3] = t.w;
                }
#pragma unroll 1
                for (int r = 0; r < 8; r += 2) {
                    mbar_wait(bar + (r & 2) * 4, r >> 2);
                    if (r < 4) fetch(r + 4);
                    fence_regs(gw);
                    float acc0 = 0.f, acc1 = 0.f;
                    uint32_t ln;
                    asm volatile("mov.u32 %0, %%laneid;" : "=r"(ln));
#pragma unroll
                    for (int i = 0; i < 4; i++) {
                        const uint4* xr = reinterpret_cast<const uint4*>(smem_raw + OFF_STG + ((warp - 1) * 8 + r) * 2048) + i * 32 + ln;
                        const uint4 a = xr[0], c = xr[128];
                        const uint32_t av[4] = {a.x, a.y, a.z, a.w}, cv[4] = {c.x, c.y, c.z, c.w};
#pragma unroll
                        for (int e = 0; e < 4; e++) {
                            const float lo = __uint_as_float(gw[i * 4 + e] << 16), hi = __uint_as_float(gw[i * 4 + e] & 0xffff0000u);
                            acc0 = fmaf(__uint_as_float(av[e] << 16), lo, acc0);
                            acc1 = fmaf(__uint_as_float(cv[e] << 16), lo, acc1);
                            acc0 = fmaf(__uint_as_float(av[e] & 0xffff0000u), hi, acc0);
                            acc1 = fmaf(__uint_as_float(cv[e] & 0xffff0000u), hi, acc1);
                        }
                    }
                    float t = (lane < 16 ? acc0 : acc1) + __shfl_xor_sync(0xffffffffu, lane < 16 ? acc1 : acc0, 16);
#pragma unroll
                    for (int o = 8; o > 0; o >>= 1) t += __shfl_xor_sync(0xffffffffu, t, o);
                    if ((lane & 15) == 0) gate_vals[(warp - 1) * 8 + r + (lane >> 4)] = t;
                }
                uint32_t t2;
                asm volatile("mov.u32 %0, %%tid.x;" : "=r"(t2));
                warp_arrive2(sempty - 16 + (t2 >> 5) * 16, sempty - 8 + (t2 >> 5) * 16);
                named_arrive(5, 96);
                if (tid == TRACE_GATE) PTRACE(9);
            }
            if (tid == TRACE_GATE) PTRACE(8);
        }
        if (warp < 3) {
            if (elect_one()) {
                const int w = warp - 1;
                uint32_t qn = 0, un = 0;
                prefetch_map(&p.qkv_st); prefetch_map(&p.st_par);
                for (int jb = 0; jb < MAX_JOBS; jb++) {
                    const int job = jobs[jb];
                    if (job < 0) break;
                    const int type = job >> 12, pl = type == T_O ? o_state(otile, 0) >> 1 : job & 0xFFF;
                    const CUtensorMap* map = &p.qkv_st;
                    int nq = 4, mt, ob0, ob1, flag, flag2 = -1;
                    bool par = false;
                    if (type <= T_O) {
                        const int n = pl >> 3;
                        mt = (pl & 7) * 2 + rank;
                        if (type == T_O)  {
                            map = &p.out_st; ob0 = (n & 3) * 4; ob1 = ob0 + 2; flag = -1;
                            for (uint32_t tries = 0; (int32_t)(ld_acquire(g_flags + F_OUT + pl * 2 + rank) - *epoch_word) < 0; tries++) {
                                __nanosleep(300);
                                if (tries > (1u << 22)) __trap();
                            }
                            fence_async_global();
                        }
                        else if (n < 16)  { ob0 = n * 4; ob1 = ob0 + 2; flag = F_Q + n * 32 + mt; flag2 = flag + 16; }
                        else if (n < 24)  {
                            mbar_wait(hout + w * 8, un++ & 1);
                            nq = ob0 = ob1 = 0; flag = F_H + mt * 8 + (n & 7);
                        } else if (n < 32) {
                            par = true; ob0 = 192 + (n & 7) * 2; ob1 = unit_head(n & 7) * 2;
                            flag = F_CTX + mt * 40 + 32 + (n & 7); flag2 = F_Q + ob1 * 8 + mt;
                        } else            { ob0 = n * 2; ob1 = ob0 + 64; flag = F_KV + (n - 32) * 16 + mt; }
                    } else {
                        nq = 2; mt = pl & 15; ob0 = ob1 = ((pl >> 4) & 31) * 2; flag = F_CTX + mt * 40 + ((pl >> 4) & 31);
                    }
                    for (int q = 0; q < nq; q++, qn++) {
                        const uint32_t slot = w * 2 + (qn & 1);
                        const int blk = (q < 2 ? ob0 : ob1) + (q & 1);
                        if (type == T_O && q == 2) {
                            mbar_wait(tfull + w * 8, 0);
                            fence_async_smem();
                            tma_reduce_add_3d(map, base + w * 8192, 0, mt * 128 + w * 64, ob1);
                            tma_reduce_add_3d(map, base + G_STAGE + w * 8192, 0, mt * 128 + w * 64, ob1 + 1);
                            bulk_commit();
                            break;
                        }
                        mbar_wait(sfull + slot * 8, (qn >> 1) & 1);
                        fence_async_smem();
                        if (type == T_O) {
                            tma_reduce_add_3d(map, stg + slot * 8192, 0, mt * 128 + w * 64, blk);
                        } else if (par) {
                            tma_store_par(&p.st_par, stg + slot * 8192, mt * 64, w, blk);
                        } else {
                            tma_store_3d(map, stg + slot * 8192, 0, mt * 128 + w * 64, blk, POL_STREAM);
                        }
                        bulk_commit();
                        if (type == T_O) continue;
                        if (!(q & 1)) continue;
                        bulk_wait_read<1>();
                        mbar_arrive(sempty + (slot ^ 1) * 8);
                        bulk_wait_read<0>();
                        mbar_arrive(sempty + slot * 8);
                    }
                    bulk_wait<0>();
                    END_MARK(jb);
                    if (flag >= 0) {
                        asm volatile("fence.release.gpu;" ::: "memory");
                        red_relaxed(g_flags + flag);
                        if (flag2 >= 0) red_relaxed(g_flags + flag2);
                    }
                }
            }
        } else {
            int jb = 0;
            for (int un = 0; (jobs[jb] >> 12) == T_P; jb++) {
                const int n = jobs[jb] >> 3, mt = (jobs[jb] & 7) * 2 + rank;
                if ((n >> 3) != 3) continue;
                wait_flags<200>(lane == 31 || (lane == 0 && mt > 0), lane == 31 ? F_GATE : F_H + max(mt - 1, 0) * 8 + (n & 7),
                                epoch1 * (lane == 31 ? GATE_COUNT : 2));
                if (lane == 0) mbar_arrive(lready + un * 8);
                un++;
            }
            if ((jobs[jb] >> 12) != T_A) {
                wait_flags<200>(lane == 0, F_GATE, epoch1 * GATE_COUNT);
                if (lane == 0) { mbar_arrive(aready); red_relaxed(g_flags + F_DONE); }
            } else {
                const int jh = jobs[jb] >> 4 & 31, jq = jobs[jb] & 15;
                wait_flags<100>(lane <= jq || lane >= 30, lane == 31 ? F_GATE : (lane == 30 ? F_Q + jh * 16 + jq : F_KV + jh * 16 + (lane & 15)),
                                epoch1 * (lane == 31 ? GATE_COUNT : 2));
                if (lane == 0) { mbar_arrive(aready); red_relaxed(g_flags + F_DONE); }
            int left = 0, nxt = jobs[jb];
            uint32_t ajob = 0;
#pragma unroll 1
            for (uint32_t astep = 0;; astep++) {
                if (left == 0) {
                    if ((nxt >> 12) != T_A) break;
                    left = (nxt & 15) + 1;
                    nxt = jobs[++jb];
                    mbar_wait(qfull + (ajob & 1) * 8, (ajob >> 1) & 1);
                    ajob++;
                }
                left--;
                mbar_wait(kfull + (astep & 1) * 8, (astep >> 1) & 1);
                named_sync(1, TURN_THREADS);
                named_sync(2, TURN_THREADS);
            }
            named_sync(1, TURN_THREADS);
            named_sync(2, TURN_THREADS);
            }
            if (jobs[jb] == (T_O << 12)) {
                mbar_wait(gatefull, 0);
                const int tile = o_state(otile, 0) >> 1;
                uint4* dst = reinterpret_cast<uint4*>(p.out) + ((tile & 7) * 256 + rank * 128) * (DM / 8) + (tile >> 3) * 32 + lane;
#pragma unroll 4
                for (int r = 0; r < 128; r++) {
                    dst[r * (DM / 8)] = make_uint4(0, 0, 0, 0);
                    if ((r & 3) == 3) __nanosleep(CLEAR_GAP_NS);
                }
                __threadfence();
                fence_async_global();
                __syncwarp();
                if (lane == 0) red_release(g_flags + F_OUT + tile * 2 + rank);
            }
        }
        } else {
            uint32_t gph = 1;
            int vrow = 0, vblk = 0;
            bool vsolo = false;
            auto load_kv = [&](uint32_t dst, uint32_t bar, int row, int blk, bool solo) INL {
                load_operand(dst, bar, &p.qkv_ld, &p.qkv_half, row, blk, rank, solo, POL_NORMAL);
            };
            auto load_v = [&](uint32_t t) INL {
                if (t == 0) mbar_wait(gempty + 24, gph);
                mbar_wait(vempty + (t & 1) * 8, ((t >> 1) & 1) ^ 1);
                load_kv(base + ((t & 1) ? OFF_V1 : OFF_V0), vfull + (t & 1) * 8, vrow, vblk, vsolo);
            };
            int jb = __ffs(__ballot_sync(0xffffffffu, lane <= MAX_JOBS && (jobs[min(lane, MAX_JOBS)] >> 12) != T_P)) - 1;
            int cur = uniform(jobs[jb]);
            auto announce = [&](uint32_t word, uint32_t v) INL {
                asm volatile("{\n.reg .pred p;\nsetp.lt.u32 p, %2, 2;\n@p red.relaxed.cluster.shared::cluster.max.u32 [%0], %1;\n}"
                             ::"r"(mapa(word, lane & 1)), "r"(v), "r"(lane) : "memory");
                __syncwarp();
            };
            uint32_t ticket = 0;
            auto draw_ticket = [&](int ojob) INL {
                asm volatile("{\n.reg .pred p;\nsetp.ne.u32 p, %2, 0;\n@p atom.relaxed.gpu.global.inc.u32 %0, [%1], 0x7fffffff;\n}"
                             : "+r"(ticket) : "l"(g_flags + F_TICKET + (ojob >> 5 & 1)), "r"((uint32_t)(rank == 0 && lane == 0)) : "memory");
                __syncwarp();
            };
            int pl = 0;
            uint32_t seen_a = 0, seen_b = 0;
            auto ask_ctx = [&]() INL {
                const uint32_t* f = g_flags + F_CTX + ((pl & 7) * 2 + rank) * 40;
                seen_a = ld_relaxed(f + lane); seen_b = ld_relaxed(f + 32 + (lane & 7));
            };
            auto open_tile = [&](int ojob) INL {
                if (rank == 0) {
                    const uint32_t t = uniform(ticket);
                    announce(otile, 2 * ((ojob & 32) ? 31 - t : t) + 1);
                }
                pl = (ojob & 32) | uniform(o_state(otile, 0) >> 1);
                ask_ctx();
            };
            const uint16_t* recs = reinterpret_cast<const uint16_t*>(rounds);
            uint32_t rec = uniform(recs[0]), nrec = uniform(recs[1]);
            int st0 = 4;
#pragma unroll 1
            for (int r = 2; rec != 0xFFFF; r++) {
                const uint32_t nnrec = recs[r];
                load_round(rec, st0, gph);
                gph ^= 1;
                st0 = 0;
                rec = nrec; nrec = uniform(nnrec);
                if (nrec == 0xFFFF || (rec & 8192)) {
                    if (nrec != 0xFFFF) {
                        prefetch_map(&p.qkv_ld); prefetch_map(&p.qkv_half);
                        if ((cur >> 12) == T_O) { prefetch_map(&p.wo_a); prefetch_map(&p.wo_b); prefetch_map(&p.out_st); }
                    } else if ((cur >> 12) == T_O) {
                        if (rec != 0xFFFF) {
                            mbar_wait(aready, 0);
                            draw_ticket(cur);
                        } else {
                            open_tile(cur);
                        }
                    }
                }
            }
            int nxt = cur;
            uint32_t astep = 0;
            if ((cur >> 12) == T_A) {
            {
                const int jh = cur >> 4 & 31, jq = cur & 15, j0 = (cur & 512) ? 0 : jq;
                mbar_wait(aready, 0);
                fence_async_global();
                mbar_wait(gempty, gph);
                load_operand(base + OFF_Q0, qfull, &p.qkv_ld, &p.qkv_ld, jq * 128, jh * 2, 0, true, POL_STREAM);
                PTRACE(17);
                mbar_wait(gempty + 8, gph);
                load_kv(base + OFF_K0, kfull, j0 * 128, 64 + jh * 2, j0 == jq && (jq & 1));
                PTRACE(16);
            }
            epoch1 = *epoch_word;
            jb++;
            nxt = uniform(jobs[jb]);
            int i = 0;
            uint32_t ajob = 1;
            bool q_issued = false;
#pragma unroll 1
            while (true) {
                const int qt = cur & 15;
                const bool last = i == qt;
                const int j = (cur & 512) ? i : qt - i, blk = (cur >> 4 & 31) * 2;
                const bool solo = j == qt && (qt & 1);
                {
                    const uint32_t sl = astep & 1;
                    if (astep == 0) {
                        mbar_wait(gempty + 16, gph);
                    } else {
                        mbar_wait(kempty + sl * 8, ((astep >> 1) & 1) ^ 1);
                        load_kv(base + (sl ? OFF_K1 : OFF_K0), kfull + sl * 8, j * 128, 64 + blk, solo);
                        if (astep == 1) PTRACE(14);
                        load_v(astep - 1);
                        if (astep == 1) PTRACE(15);
                    }
                }
                vrow = j * 128; vblk = 128 + blk; vsolo = solo;
                astep++;
                if ((nxt >> 12) != T_A) {
                    if (last) break;
                } else if (!q_issued && (last || i == 2 || (i > 2 && i >= qt - 2))) {
                    const int jh = nxt >> 4 & 31, jq = nxt & 15;
                    q_issued = wait_flags(lane <= jq || lane >= 30, lane == 31 ? F_GATE : (lane == 30 ? F_Q + jh * 16 + jq : F_KV + jh * 16 + (lane & 15)),
                                          epoch1 * (lane == 31 ? GATE_COUNT : 2), last);
                    if (q_issued) {
                        mbar_wait(qempty + (ajob & 1) * 8, ((ajob >> 1) & 1) ^ 1);
                        load_operand(base + ((ajob & 1) ? OFF_Q1 : OFF_Q0), qfull + (ajob & 1) * 8, &p.qkv_ld, &p.qkv_ld, jq * 128, jh * 2, 0, true, POL_STREAM);
                    }
                }
                i++;
                if (last) {
                    cur = nxt; jb++; nxt = uniform(jobs[jb]); i = 0; ajob++; q_issued = false;
                    if ((nxt >> 12) == T_O) { prefetch_map(&p.wo_a); prefetch_map(&p.wo_b); prefetch_map(&p.out_st); }
                }
            }
            if (nxt >= 0) draw_ticket(nxt);
            load_v(astep - 1);
            if (nxt >= 0) open_tile(nxt);
            }
            int nks = 0;
            if (nxt >= 0) {
                epoch1 = *epoch_word;
                const int m0 = (pl & 7) * 256 + rank * 128, nb = (pl >> 3 & 3) * 4 + rank * 2, part = pl >> 5 & 1;
                uint32_t ready_a = 0, ready_b = 0;
                uint32_t claim_even = 0, claim_odd = 0;
                const int head = o_head(pl), tail = o_tail(pl);
                int lim = head;
                bool known = false;
#pragma unroll 1
                for (int ks = 0;; ks++) {
                    const int st = ks & 3;
                    if (rank == 0) {
                        auto exchange = [&](uint32_t& claim) INL {
                            if (ks + 1 >= head) {
                                known = (uint32_t)uniform(claim) >= O_FLEX;
                                if (!known) lim = ks + 2;
                                announce(olim, known ? 2 * (lim + tail) + 1 : 2 * lim);
                            }
                            asm volatile("{\n.reg .pred p;\nsetp.ne.u32 p, %2, 0;\n@p atom.relaxed.gpu.global.inc.u32 %0, [%1], 0x7fffffff;\n}"
                                         : "+r"(claim) : "l"(g_flags + F_SPLIT + (pl & 31)), "r"((uint32_t)(!known && lane == 0)) : "memory");
                            __syncwarp();
                        };
                        if (!known && ks + 3 >= head) { if (ks & 1) exchange(claim_odd); else exchange(claim_even); }
                    } else if (!known && ks >= lim) {
                        const uint32_t v = uniform(o_state(olim, ks));
                        known = v & 1;
                        lim = (v >> 1) - (known ? tail : 0);
                    }
                    if (ks >= lim + tail) { nks = ks; break; }
                    if (ks == CLEAR_KS && !part) warp_arrive(gatefull);
                    int acol;
                    if (ks >= lim) acol = (part ? 64 - O_T1 : 200) + ks - lim;
                    else if (part) acol = ks < O_H1 ? O_F0 + ks : O_F0 + 2 * O_H1 + O_FLEX - 1 - ks;
                    else acol = ks < 8 ? 192 + ks : (ks < O_H0 ? ks - 8 : ks - 8 + O_H1);
                    for (uint32_t tries = 0; !(((acol < 192 ? ready_a : ready_b) >> (acol >> 1 & 31)) & 1); tries++) {
                        if (ks | tries) ask_ctx();
                        ready_a = __ballot_sync(0xffffffffu, (int32_t)(seen_a - epoch1 * 2) >= 0);
                        ready_b = __ballot_sync(0xffffffffu, (int32_t)(seen_b - epoch1 * 2) >= 0);
                        fence_acquire();
                        trap_if(tries > (1u << 22));
                    }
                    {
                        const uint32_t sa = base + st * G_STAGE;
                        if (ks < 4 && astep) mbar_wait((ks < 2 ? kempty : vempty) + ((astep - 1) & 1) * 8, ((astep - 1) >> 1) & 1);
                        else mbar_wait(gempty + st * 8, gph);
                        load_kstep(sa, sa + 16384 + rank * 16384, gfull + st * 8, G_STAGE, acol >= 192 ? &p.wo_b : &p.wo_a, acol & 63, nb,
                                   &p.qkv_half, m0, acol, 1);
                    }
                    if (st == 3) gph ^= 1;
                }
            }
            if (lane == 0) {
                if (nxt >= 0) for (int s = 0; s < 4; s++) mbar_wait(gempty + s * 8, gph ^ (s < (nks & 3)));
                else for (uint32_t t = astep; t < astep + 2; t++) {
                    mbar_wait(kempty + (t & 1) * 8, ((t >> 1) & 1) ^ 1);
                    mbar_wait(vempty + (t & 1) * 8, ((t >> 1) & 1) ^ 1);
                }
            }
        }
    }
}

typedef CUresult (*EncodeFn)(CUtensorMap*, CUtensorMapDataType, cuuint32_t, void*, const cuuint64_t*, const cuuint64_t*,
                             const cuuint32_t*, const cuuint32_t*, CUtensorMapInterleave, CUtensorMapSwizzle,
                             CUtensorMapL2promotion, CUtensorMapFloatOOBfill);

void make_map3(EncodeFn enc, CUtensorMap* m, const void* ptr, int rows, int cols, int box_rows, int box_blks, bool blocked = false) {
    cuuint64_t dims[3] = {64, (cuuint64_t)rows, (cuuint64_t)(cols / 64)};
    cuuint64_t strides[2] = {blocked ? 128 : (cuuint64_t)cols * 2, blocked ? (cuuint64_t)rows * 128 : 128};
    cuuint32_t box[3] = {64, (cuuint32_t)box_rows, (cuuint32_t)box_blks};
    cuuint32_t es[3] = {1, 1, 1};
    enc(m, CU_TENSOR_MAP_DATA_TYPE_BFLOAT16, 3, const_cast<void*>(ptr), dims, strides, box, es, CU_TENSOR_MAP_INTERLEAVE_NONE,
        CU_TENSOR_MAP_SWIZZLE_128B, CU_TENSOR_MAP_L2_PROMOTION_L2_256B, CU_TENSOR_MAP_FLOAT_OOB_FILL_NONE);
}

Params h_params;

const int16_t k_jobs[NUM_SMS][MAX_JOBS] = {
    {339,153,217,8890,8339,8802,8311,9042,8405,9008,8551,9134,8677,4128,-1,-1,-1,-1,-1,-1,-1,-1,-1,-1},
    {339,153,217,8891,8338,8803,8310,9043,8404,9009,8550,9135,8676,4128,-1,-1,-1,-1,-1,-1,-1,-1,-1,-1},
    {40,0,307,8888,8289,8720,8259,8854,8539,8898,8627,8998,8655,4128,-1,-1,-1,-1,-1,-1,-1,-1,-1,-1},
    {40,0,307,8889,8288,8721,8258,8855,8538,8899,8626,8999,8654,4128,-1,-1,-1,-1,-1,-1,-1,-1,-1,-1},
    {10,157,221,8706,8269,8820,8457,9006,8687,4128,-1,-1,-1,-1,-1,-1,-1,-1,-1,-1,-1,-1,-1,-1},
    {10,157,221,8707,8268,8821,8456,9007,8686,4128,-1,-1,-1,-1,-1,-1,-1,-1,-1,-1,-1,-1,-1,-1},
    {132,196,296,8730,8333,8940,8503,9082,8697,4128,-1,-1,-1,-1,-1,-1,-1,-1,-1,-1,-1,-1,-1,-1},
    {132,196,296,8731,8332,8941,8502,9083,8696,4128,-1,-1,-1,-1,-1,-1,-1,-1,-1,-1,-1,-1,-1,-1},
    {128,192,8758,8199,8774,8313,9026,8415,9130,8663,4128,-1,-1,-1,-1,-1,-1,-1,-1,-1,-1,-1,-1,-1},
    {128,192,8759,8198,8775,8312,9027,8414,9131,8662,4128,-1,-1,-1,-1,-1,-1,-1,-1,-1,-1,-1,-1,-1},
    {133,197,8742,8369,8704,8285,8768,8543,9022,8601,4128,-1,-1,-1,-1,-1,-1,-1,-1,-1,-1,-1,-1,-1},
    {133,197,8743,8368,8705,8284,8769,8542,9023,8600,4128,-1,-1,-1,-1,-1,-1,-1,-1,-1,-1,-1,-1,-1},
    {131,195,38,8708,8265,8932,8461,8896,8631,9076,8585,4128,-1,-1,-1,-1,-1,-1,-1,-1,-1,-1,-1,-1},
    {131,195,38,8709,8264,8933,8460,8897,8630,9077,8584,4128,-1,-1,-1,-1,-1,-1,-1,-1,-1,-1,-1,-1},
    {137,201,8750,8331,8816,8533,8912,8411,9078,8671,4128,-1,-1,-1,-1,-1,-1,-1,-1,-1,-1,-1,-1,-1},
    {137,201,8751,8330,8817,8532,8913,8410,9079,8670,4128,-1,-1,-1,-1,-1,-1,-1,-1,-1,-1,-1,-1,-1},
    {43,264,440,8744,8201,8858,8417,8954,8483,9016,8649,9152,8691,4128,-1,-1,-1,-1,-1,-1,-1,-1,-1,-1},
    {43,264,440,8745,8200,8859,8416,8955,8482,9017,8648,9153,8690,4128,-1,-1,-1,-1,-1,-1,-1,-1,-1,-1},
    {151,215,8876,8299,8964,8445,9146,8703,4128,-1,-1,-1,-1,-1,-1,-1,-1,-1,-1,-1,-1,-1,-1,-1},
    {151,215,8877,8298,8965,8444,9147,8702,4128,-1,-1,-1,-1,-1,-1,-1,-1,-1,-1,-1,-1,-1,-1,-1},
    {470,5,159,223,8772,8281,8936,8407,9066,8651,4128,-1,-1,-1,-1,-1,-1,-1,-1,-1,-1,-1,-1,-1},
    {470,5,159,223,8773,8280,8937,8406,9067,8650,4128,-1,-1,-1,-1,-1,-1,-1,-1,-1,-1,-1,-1,-1},
    {136,200,444,8760,8275,8848,8477,9040,8525,9148,8681,4128,-1,-1,-1,-1,-1,-1,-1,-1,-1,-1,-1,-1},
    {136,200,444,8761,8274,8849,8476,9041,8524,9149,8680,4128,-1,-1,-1,-1,-1,-1,-1,-1,-1,-1,-1,-1},
    {46,510,462,310,8764,8293,8862,8439,9064,8653,4128,-1,-1,-1,-1,-1,-1,-1,-1,-1,-1,-1,-1,-1},
    {46,510,462,310,8765,8292,8863,8438,9065,8652,4128,-1,-1,-1,-1,-1,-1,-1,-1,-1,-1,-1,-1,-1},
    {145,209,8894,8335,8942,8485,9098,8695,4128,-1,-1,-1,-1,-1,-1,-1,-1,-1,-1,-1,-1,-1,-1,-1},
    {145,209,8895,8334,8943,8484,9099,8694,4128,-1,-1,-1,-1,-1,-1,-1,-1,-1,-1,-1,-1,-1,-1,-1},
    {140,204,8878,8329,8934,8441,9070,8685,4128,-1,-1,-1,-1,-1,-1,-1,-1,-1,-1,-1,-1,-1,-1,-1},
    {140,204,8879,8328,8935,8440,9071,8684,4128,-1,-1,-1,-1,-1,-1,-1,-1,-1,-1,-1,-1,-1,-1,-1},
    {146,210,504,8884,8301,8966,8527,9128,8603,4128,-1,-1,-1,-1,-1,-1,-1,-1,-1,-1,-1,-1,-1,-1},
    {146,210,504,8885,8300,8967,8526,9129,8602,4128,-1,-1,-1,-1,-1,-1,-1,-1,-1,-1,-1,-1,-1,-1},
    {14,6,8868,8245,8806,8267,8938,8547,9000,8611,9108,8643,4128,-1,-1,-1,-1,-1,-1,-1,-1,-1,-1,-1},
    {14,6,8869,8244,8807,8266,8939,8546,9001,8610,9109,8642,4128,-1,-1,-1,-1,-1,-1,-1,-1,-1,-1,-1},
    {144,208,8748,8211,8836,8463,9004,8591,4128,-1,-1,-1,-1,-1,-1,-1,-1,-1,-1,-1,-1,-1,-1,-1},
    {144,208,8749,8210,8837,8462,9005,8590,4128,-1,-1,-1,-1,-1,-1,-1,-1,-1,-1,-1,-1,-1,-1,-1},
    {12,4,8740,8243,8724,8287,8930,8435,8900,8517,9086,8659,4128,-1,-1,-1,-1,-1,-1,-1,-1,-1,-1,-1},
    {12,4,8741,8242,8725,8286,8931,8434,8901,8516,9087,8658,4128,-1,-1,-1,-1,-1,-1,-1,-1,-1,-1,-1},
    {143,207,8866,8353,8752,8205,8830,8409,9056,8561,9140,8581,9104,8679,4128,-1,-1,-1,-1,-1,-1,-1,-1,-1},
    {143,207,8867,8352,8753,8204,8831,8408,9057,8560,9141,8580,9105,8678,4128,-1,-1,-1,-1,-1,-1,-1,-1,-1},
    {147,211,8872,8297,8834,8459,9030,8437,9100,8665,4128,-1,-1,-1,-1,-1,-1,-1,-1,-1,-1,-1,-1,-1},
    {147,211,8873,8296,8835,8458,9031,8436,9101,8664,4128,-1,-1,-1,-1,-1,-1,-1,-1,-1,-1,-1,-1,-1},
    {41,1,8766,8327,8828,8399,9126,8667,4128,-1,-1,-1,-1,-1,-1,-1,-1,-1,-1,-1,-1,-1,-1,-1},
    {41,1,8767,8326,8829,8398,9127,8666,4128,-1,-1,-1,-1,-1,-1,-1,-1,-1,-1,-1,-1,-1,-1,-1},
    {150,214,8882,8223,8832,8473,8980,8413,9094,8669,4128,-1,-1,-1,-1,-1,-1,-1,-1,-1,-1,-1,-1,-1},
    {150,214,8883,8222,8833,8472,8981,8412,9095,8668,4128,-1,-1,-1,-1,-1,-1,-1,-1,-1,-1,-1,-1,-1},
    {141,205,33,8726,8341,8976,8479,9024,8449,9136,8501,9144,8683,4128,-1,-1,-1,-1,-1,-1,-1,-1,-1,-1},
    {141,205,33,8727,8340,8977,8478,9025,8448,9137,8500,9145,8682,4128,-1,-1,-1,-1,-1,-1,-1,-1,-1,-1},
    {277,405,152,216,8718,8475,8902,8403,9150,8661,4128,-1,-1,-1,-1,-1,-1,-1,-1,-1,-1,-1,-1,-1},
    {277,405,152,216,8719,8474,8903,8402,9151,8660,4128,-1,-1,-1,-1,-1,-1,-1,-1,-1,-1,-1,-1,-1},
    {139,203,8886,8203,8856,8433,9032,8393,9080,8599,4128,-1,-1,-1,-1,-1,-1,-1,-1,-1,-1,-1,-1,-1},
    {139,203,8887,8202,8857,8432,9033,8392,9081,8598,4128,-1,-1,-1,-1,-1,-1,-1,-1,-1,-1,-1,-1,-1},
    {149,213,8746,8303,8982,8397,9084,8645,4128,-1,-1,-1,-1,-1,-1,-1,-1,-1,-1,-1,-1,-1,-1,-1},
    {149,213,8747,8302,8983,8396,9085,8644,4128,-1,-1,-1,-1,-1,-1,-1,-1,-1,-1,-1,-1,-1,-1,-1},
    {138,202,8870,8221,8860,8395,9060,8607,4128,-1,-1,-1,-1,-1,-1,-1,-1,-1,-1,-1,-1,-1,-1,-1},
    {138,202,8871,8220,8861,8394,9061,8606,4128,-1,-1,-1,-1,-1,-1,-1,-1,-1,-1,-1,-1,-1,-1,-1},
    {134,198,8738,8225,8728,8283,8962,8541,8992,8499,9074,8609,9124,8595,9184,8693,4128,-1,-1,-1,-1,-1,-1,-1},
    {134,198,8739,8224,8729,8282,8963,8540,8993,8498,9075,8608,9125,8594,9185,8692,4128,-1,-1,-1,-1,-1,-1,-1},
    {142,206,8874,8271,8818,8447,9068,8647,4128,-1,-1,-1,-1,-1,-1,-1,-1,-1,-1,-1,-1,-1,-1,-1},
    {142,206,8875,8270,8819,8446,9069,8646,4128,-1,-1,-1,-1,-1,-1,-1,-1,-1,-1,-1,-1,-1,-1,-1},
    {47,498,506,306,8892,8277,8784,8467,9048,8535,9020,8579,9088,8657,9186,8689,4128,-1,-1,-1,-1,-1,-1,-1},
    {47,498,506,306,8893,8276,8785,8466,9049,8534,9021,8578,9089,8656,9187,8688,4128,-1,-1,-1,-1,-1,-1,-1},
    {148,212,8762,8279,8826,8523,9002,8605,4128,-1,-1,-1,-1,-1,-1,-1,-1,-1,-1,-1,-1,-1,-1,-1},
    {148,212,8763,8278,8827,8522,9003,8604,4128,-1,-1,-1,-1,-1,-1,-1,-1,-1,-1,-1,-1,-1,-1,-1},
    {276,404,268,500,450,490,374,390,430,380,356,412,168,232,9018,8701,-1,-1,-1,-1,-1,-1,-1,-1},
    {276,404,268,500,450,490,374,390,430,380,356,412,168,232,9019,8700,-1,-1,-1,-1,-1,-1,-1,-1},
    {11,403,459,507,329,393,369,377,417,361,433,167,231,9132,8699,-1,-1,-1,-1,-1,-1,-1,-1,-1},
    {11,403,459,507,329,393,369,377,417,361,433,167,231,9133,8698,-1,-1,-1,-1,-1,-1,-1,-1,-1},
    {350,486,502,262,302,334,318,87,52,100,179,243,4096,-1,-1,-1,-1,-1,-1,-1,-1,-1,-1,-1},
    {350,486,502,262,302,334,318,87,52,100,179,243,4096,-1,-1,-1,-1,-1,-1,-1,-1,-1,-1,-1},
    {340,158,222,492,60,108,76,172,236,4096,-1,-1,-1,-1,-1,-1,-1,-1,-1,-1,-1,-1,-1,-1},
    {340,158,222,492,60,108,76,172,236,4096,-1,-1,-1,-1,-1,-1,-1,-1,-1,-1,-1,-1,-1,-1},
    {42,3,35,59,107,360,408,181,245,4096,-1,-1,-1,-1,-1,-1,-1,-1,-1,-1,-1,-1,-1,-1},
    {42,3,35,59,107,360,408,181,245,4096,-1,-1,-1,-1,-1,-1,-1,-1,-1,-1,-1,-1,-1,-1},
    {45,156,220,396,85,109,93,180,244,4096,-1,-1,-1,-1,-1,-1,-1,-1,-1,-1,-1,-1,-1,-1},
    {45,156,220,396,85,109,93,180,244,4096,-1,-1,-1,-1,-1,-1,-1,-1,-1,-1,-1,-1,-1,-1},
    {466,482,266,258,37,69,53,77,183,247,4096,-1,-1,-1,-1,-1,-1,-1,-1,-1,-1,-1,-1,-1},
    {466,482,266,258,37,69,53,77,183,247,4096,-1,-1,-1,-1,-1,-1,-1,-1,-1,-1,-1,-1,-1},
    {471,407,463,442,290,322,314,386,478,382,366,414,182,246,4096,-1,-1,-1,-1,-1,-1,-1,-1,-1},
    {471,407,463,442,290,322,314,386,478,382,366,414,182,246,4096,-1,-1,-1,-1,-1,-1,-1,-1,-1},
    {469,349,485,501,445,333,317,373,477,423,439,415,173,237,4096,-1,-1,-1,-1,-1,-1,-1,-1,-1},
    {469,349,485,501,445,333,317,373,477,423,439,415,173,237,4096,-1,-1,-1,-1,-1,-1,-1,-1,-1},
    {8,269,309,453,449,489,385,425,422,358,92,188,252,4096,-1,-1,-1,-1,-1,-1,-1,-1,-1,-1},
    {8,269,309,453,449,489,385,425,422,358,92,188,252,4096,-1,-1,-1,-1,-1,-1,-1,-1,-1,-1},
    {343,287,487,263,303,455,495,391,51,91,160,224,4096,-1,-1,-1,-1,-1,-1,-1,-1,-1,-1,-1},
    {343,287,487,263,303,455,495,391,51,91,160,224,4096,-1,-1,-1,-1,-1,-1,-1,-1,-1,-1,-1},
    {464,272,480,456,288,488,392,61,379,363,435,176,240,4096,-1,-1,-1,-1,-1,-1,-1,-1,-1,-1},
    {464,272,480,456,288,488,392,61,379,363,435,176,240,4096,-1,-1,-1,-1,-1,-1,-1,-1,-1,-1},
    {336,280,400,256,448,320,312,384,424,416,352,432,472,171,235,4096,-1,-1,-1,-1,-1,-1,-1,-1},
    {336,280,400,256,448,320,312,384,424,416,352,432,472,171,235,4096,-1,-1,-1,-1,-1,-1,-1,-1},
    {337,273,265,155,219,368,376,479,359,102,184,248,4096,-1,-1,-1,-1,-1,-1,-1,-1,-1,-1,-1},
    {337,273,265,155,219,368,376,479,359,102,184,248,4096,-1,-1,-1,-1,-1,-1,-1,-1,-1,-1,-1},
    {468,284,508,260,300,324,332,388,104,72,174,238,4096,-1,-1,-1,-1,-1,-1,-1,-1,-1,-1,-1},
    {468,284,508,260,300,324,332,388,104,72,174,238,4096,-1,-1,-1,-1,-1,-1,-1,-1,-1,-1,-1},
    {338,281,2,34,66,110,78,175,239,4096,-1,-1,-1,-1,-1,-1,-1,-1,-1,-1,-1,-1,-1,-1},
    {338,281,2,34,66,110,78,175,239,4096,-1,-1,-1,-1,-1,-1,-1,-1,-1,-1,-1,-1,-1,-1},
    {130,194,39,63,55,95,103,97,4096,-1,-1,-1,-1,-1,-1,-1,-1,-1,-1,-1,-1,-1,-1,-1},
    {130,194,39,63,55,95,103,97,4096,-1,-1,-1,-1,-1,-1,-1,-1,-1,-1,-1,-1,-1,-1,-1},
    {135,199,454,494,67,83,365,413,191,255,4096,-1,-1,-1,-1,-1,-1,-1,-1,-1,-1,-1,-1,-1},
    {135,199,454,494,67,83,365,413,191,255,4096,-1,-1,-1,-1,-1,-1,-1,-1,-1,-1,-1,-1,-1},
    {348,484,460,308,292,452,316,372,428,420,476,101,187,251,4096,-1,-1,-1,-1,-1,-1,-1,-1,-1},
    {348,484,460,308,292,452,316,372,428,420,476,101,187,251,4096,-1,-1,-1,-1,-1,-1,-1,-1,-1},
    {13,154,218,58,106,74,178,242,4096,-1,-1,-1,-1,-1,-1,-1,-1,-1,-1,-1,-1,-1,-1,-1},
    {13,154,218,58,106,74,178,242,4096,-1,-1,-1,-1,-1,-1,-1,-1,-1,-1,-1,-1,-1,-1,-1},
    {465,481,457,505,289,328,71,111,79,166,230,4096,-1,-1,-1,-1,-1,-1,-1,-1,-1,-1,-1,-1},
    {465,481,457,505,289,328,71,111,79,166,230,4096,-1,-1,-1,-1,-1,-1,-1,-1,-1,-1,-1,-1},
    {44,270,446,294,326,65,81,89,161,225,4096,-1,-1,-1,-1,-1,-1,-1,-1,-1,-1,-1,-1,-1},
    {44,270,446,294,326,65,81,89,161,225,4096,-1,-1,-1,-1,-1,-1,-1,-1,-1,-1,-1,-1,-1},
    {9,511,503,295,327,375,399,381,437,353,409,473,169,233,4096,-1,-1,-1,-1,-1,-1,-1,-1,-1},
    {9,511,503,295,327,375,399,381,437,353,409,473,169,233,4096,-1,-1,-1,-1,-1,-1,-1,-1,-1},
    {347,283,483,259,291,491,331,371,431,383,367,99,186,250,4096,-1,-1,-1,-1,-1,-1,-1,-1,-1},
    {347,283,483,259,291,491,331,371,431,383,367,99,186,250,4096,-1,-1,-1,-1,-1,-1,-1,-1,-1},
    {274,282,458,261,293,493,397,389,429,421,357,75,189,253,4096,-1,-1,-1,-1,-1,-1,-1,-1,-1},
    {274,282,458,261,293,493,397,389,429,421,357,75,189,253,4096,-1,-1,-1,-1,-1,-1,-1,-1,-1},
    {278,286,406,32,64,56,48,88,170,234,4096,-1,-1,-1,-1,-1,-1,-1,-1,-1,-1,-1,-1,-1},
    {278,286,406,32,64,56,48,88,170,234,4096,-1,-1,-1,-1,-1,-1,-1,-1,-1,-1,-1,-1,-1},
    {279,351,271,447,298,330,394,370,426,378,354,434,164,228,4096,-1,-1,-1,-1,-1,-1,-1,-1,-1},
    {279,351,271,447,298,330,394,370,426,378,354,434,164,228,4096,-1,-1,-1,-1,-1,-1,-1,-1,-1},
    {344,345,497,257,297,321,313,82,50,90,98,96,4096,-1,-1,-1,-1,-1,-1,-1,-1,-1,-1,-1},
    {344,345,497,257,297,321,313,82,50,90,98,96,4096,-1,-1,-1,-1,-1,-1,-1,-1,-1,-1,-1},
    {129,193,311,335,319,86,438,364,436,163,227,4096,-1,-1,-1,-1,-1,-1,-1,-1,-1,-1,-1,-1},
    {129,193,311,335,319,86,438,364,436,163,227,4096,-1,-1,-1,-1,-1,-1,-1,-1,-1,-1,-1,-1},
    {341,285,509,461,301,325,398,80,418,362,410,474,177,241,4096,-1,-1,-1,-1,-1,-1,-1,-1,-1},
    {341,285,509,461,301,325,398,80,418,362,410,474,177,241,4096,-1,-1,-1,-1,-1,-1,-1,-1,-1},
    {342,275,267,499,299,451,395,57,49,73,185,249,4096,-1,-1,-1,-1,-1,-1,-1,-1,-1,-1,-1},
    {342,275,267,499,299,451,395,57,49,73,185,249,4096,-1,-1,-1,-1,-1,-1,-1,-1,-1,-1,-1},
    {346,402,496,304,443,323,315,387,427,419,355,411,165,229,4096,-1,-1,-1,-1,-1,-1,-1,-1,-1},
    {346,402,496,304,443,323,315,387,427,419,355,411,165,229,4096,-1,-1,-1,-1,-1,-1,-1,-1,-1},
    {15,401,305,441,70,62,54,94,190,254,4096,-1,-1,-1,-1,-1,-1,-1,-1,-1,-1,-1,-1,-1},
    {15,401,305,441,70,62,54,94,190,254,4096,-1,-1,-1,-1,-1,-1,-1,-1,-1,-1,-1,-1,-1},
    {467,7,36,68,84,105,475,162,226,4096,-1,-1,-1,-1,-1,-1,-1,-1,-1,-1,-1,-1,-1,-1},
    {467,7,36,68,84,105,475,162,226,4096,-1,-1,-1,-1,-1,-1,-1,-1,-1,-1,-1,-1,-1,-1},
};

void build_rounds() {
    for (int c = 0; c < NUM_SMS / 2; c++) {
        const int16_t* jobs = h_params.jobs[2 * c];
        int nr = 0, prev_key = -1, last = 0;
        for (int j = 0; (jobs[j] >> 12) == T_P; j++) {
            const int n = jobs[j] >> 3, a = n >= 32, unit = n >= 16 && n < 32 ? (n >> 3) - 1 : 0, cnt = a ? 2 : 4;
            const int key = (jobs[j] & 7) | a << 3 | (unit > 0) << 4;
            const int wm = n < 16 ? 0 : (n < 32 ? 1 : n >> 4 & 1), col = n < 16 ? n : (n < 32 ? n & 7 : n & 15);
            const bool keep = key == prev_key, final_tile = (jobs[j + 1] >> 12) != T_P;
            const int k0 = keep ? last : 0;
            for (int r = 0; r < cnt; r++) {
                last = (k0 + r) % cnt;
                h_params.rounds[c][nr++] = (uint16_t)((key & 15) | wm << 4 | col << 6 | last << 10 | (keep && r == 0) << 12 | (final_tile && r == 0) << 13 | unit << 14);
            }
            prev_key = key;
        }
        while (nr < MAX_ROUNDS) h_params.rounds[c][nr++] = 0xFFFF;
        {
            const uint32_t rec = h_params.rounds[c][0], col = rec >> 6 & 15, unit = rec >> 14;
            for (uint32_t r = 0; r < 2; r++) {
                uint32_t wm[2], wb[2];
                for (uint32_t h = 0; h < 2; h++) {
                    wm[h] = 2 + ((rec & 8) ? 2 + h : ((rec >> 15) && h ? 0 : rec >> 4 & 1));
                    wb[h] = (rec & 8) ? (col + (rec & 16)) * 2
                                      : (unit == 0 ? col * 4 + h * 2 : (unit == 1 ? 16 + h * 16 + col * 2 : (h ? unit_head(col) : col) * 2));
                }
                const uint32_t am = unit ? 6 : (rec >> 3 & 1), arow = unit ? (rec & 7) * 128 + r * 64 : (rec & 7) * 256 + r * 128;
                h_params.first[2 * c + r] = make_uint2((unit ? 1 : 0) | am << 7 | wm[0] << 11 | wm[1] << 15 | arow << 20, wb[0] | wb[1] << 16);
            }
        }
    }
}

void build_schedule() {
    for (int c = 0; c < NUM_SMS; c++) {
        for (int j = 0; j < MAX_JOBS; j++) h_params.jobs[c][j] = k_jobs[c][j];
    }
    build_rounds();
}

}

extern "C" void kernel_launch(void* const* d_in, const int* in_sizes, int n_in, void* d_out, int out_size) {
    (void)in_sizes; (void)n_in; (void)out_size;
    static EncodeFn enc = nullptr;
    if (!enc) {
        cudaDriverEntryPointQueryResult qr;
        void* fn = nullptr;
        cudaGetDriverEntryPoint("cuTensorMapEncodeTiled", &fn, cudaEnableDefault, &qr);
        enc = (EncodeFn)fn;
        cudaFuncSetAttribute(fused_kernel, cudaFuncAttributeMaxDynamicSharedMemorySize, SMEM_BYTES);
        build_schedule();
    }
    void* qkv;
    cudaGetSymbolAddress(&qkv, g_qkv);
    Params& p = h_params;
    make_map3(enc, &p.amap[0], d_in[0], SEQ, DM, 128, 1);
    make_map3(enc, &p.amap[1], d_in[1], SEQ, DC, 128, 1);
    make_map3(enc, &p.wmap[0], d_in[2], DM, 4096, 64, 2);
    make_map3(enc, &p.wmap[2], d_in[3], DC, 4096, 64, 2);
    make_map3(enc, &p.wmap[3], d_in[4], DC, 4096, 64, 2);
    make_map3(enc, &p.wmap[1], d_in[7], DM, 3072, 64, 2);
    make_map3(enc, &p.wo_a, d_in[5], 4096, DM, 64, 2);
    make_map3(enc, &p.wo_b, d_in[8], DM, DM, 64, 2);
    make_map3(enc, &p.qkv_st, qkv, SEQ, QKV_W, 64, 1, true);
    make_map3(enc, &p.qkv_ld, qkv, SEQ, QKV_W, 128, 2, true);
    make_map3(enc, &p.qkv_half, qkv, SEQ, QKV_W, 128, 1, true);
    {
        cuuint64_t dims[4] = {64, SEQ / 2, 2, QKV_W / 64}, strides[3] = {256, 128, (cuuint64_t)SEQ * 128};
        cuuint32_t box[4] = {64, 64, 1, 1}, es[4] = {1, 1, 1, 1};
        enc(&p.st_par, CU_TENSOR_MAP_DATA_TYPE_BFLOAT16, 4, qkv, dims, strides, box, es, CU_TENSOR_MAP_INTERLEAVE_NONE,
            CU_TENSOR_MAP_SWIZZLE_128B, CU_TENSOR_MAP_L2_PROMOTION_L2_256B, CU_TENSOR_MAP_FLOAT_OOB_FILL_NONE);
        dims[3] = DM / 64; strides[0] = DM * 4; strides[1] = DM * 2; strides[2] = 128; box[2] = 2;
        enc(&p.x_par, CU_TENSOR_MAP_DATA_TYPE_BFLOAT16, 4, d_in[0], dims, strides, box, es, CU_TENSOR_MAP_INTERLEAVE_NONE,
            CU_TENSOR_MAP_SWIZZLE_128B, CU_TENSOR_MAP_L2_PROMOTION_L2_256B, CU_TENSOR_MAP_FLOAT_OOB_FILL_NONE);
    }
    make_map3(enc, &p.out_st, d_out, SEQ, DM, 64, 1);
    p.xp = (const __nv_bfloat16*)d_in[0];
    p.gate_w = (const __nv_bfloat16*)d_in[9];
    p.out = (__nv_bfloat16*)d_out;
    fused_kernel<<<NUM_SMS, 384, SMEM_BYTES, cudaStreamPerThread>>>(p);
}
```

```cpp
#include <cuda_runtime.h>
#include <cuda_bf16.h>
#include <cuda.h>
#include <stdint.h>

#define INL __attribute__((always_inline))

namespace {

constexpr int SEQ = 2048;
constexpr int DM = 1024;
constexpr int DC = 512;
constexpr int QKV_W = 13312;
constexpr int NUM_SMS = 132;
constexpr int GATE_DELAY_SHORT_NS = 1000, GATE_DELAY_LONG_NS = 3000;
constexpr int CLEAR_KS = 44, CLEAR_GAP_NS = 100;
constexpr float K_SCALE = 0.08838834764831845f * 1.4426950408889634f;

__device__ __align__(1024) __nv_bfloat16 g_qkv[(size_t)SEQ * QKV_W];
__device__ float g_gate[SEQ];
__device__ uint4 g_halo[16 * 8 * 2 * 5 * 4 * 32];

constexpr int F_Q = 0;
constexpr int F_KV = 1792;
constexpr int F_H = 768;
constexpr int F_CTX = 960;
constexpr int F_GATE = 1600;
constexpr int F_DONE = 1632;
constexpr int F_SPLIT = 1664;
constexpr int F_TICKET = 1696;
constexpr int F_OUT = 1728;
constexpr int GATE_COUNT = NUM_SMS;
__device__ uint32_t g_flags[2304];

#define END_MARK(slot)
#define TRACE_MARK(k, w, i)
#define GTRACE(w)
#define KTRACE(w)
#define PTRACE(i)
#define TRACE_GATE 32
#define TRACE_TID 128

__device__ __forceinline__ uint32_t smem_u32(const void* p) { return (uint32_t)__cvta_generic_to_shared(p); }
__device__ __forceinline__ void mbar_init(uint32_t bar, uint32_t cnt) {
    asm volatile("mbarrier.init.shared::cta.b64 [%0], %1;" ::"r"(bar), "r"(cnt));
}
__device__ __forceinline__ void mbar_arrive(uint32_t bar) {
    asm volatile("mbarrier.arrive.shared::cta.b64 _, [%0];" ::"r"(bar) : "memory");
}
__device__ __forceinline__ bool elect_one() {
    uint32_t r;
    asm volatile("{\n.reg .pred p;\nelect.sync _|p, 0xffffffff;\nselp.b32 %0, 1, 0, p;\n}" : "=r"(r));
    return r != 0;
}
__device__ __forceinline__ uint32_t mapa(uint32_t addr, uint32_t cta) {
    uint32_t r;
    asm("mapa.shared::cluster.u32 %0, %1, %2;" : "=r"(r) : "r"(addr), "r"(cta));
    return r;
}
__device__ __forceinline__ void warp_arrive(uint32_t bar, bool pred = true) {
    asm volatile("{\n.reg .pred p, q;\nsetp.ne.u32 q, %1, 0;\nelect.sync _|p, 0xffffffff;\nand.pred p, p, q;\n"
                 "@p mbarrier.arrive.shared::cta.b64 _, [%0];\n}" ::"r"(bar), "r"((uint32_t)pred) : "memory");
}
__device__ __forceinline__ void warp_arrive2(uint32_t bar0, uint32_t bar1) {
    asm volatile("{\n.reg .pred p;\nelect.sync _|p, 0xffffffff;\n@p mbarrier.arrive.shared::cta.b64 _, [%0];\n"
                 "@p mbarrier.arrive.shared::cta.b64 _, [%1];\n}" ::"r"(bar0), "r"(bar1) : "memory");
}
__device__ __forceinline__ void warp_arrive_pair(uint32_t bar, uint32_t peer_bar, bool pred = true) {
    asm volatile("{\n.reg .pred p, q;\nsetp.ne.u32 q, %2, 0;\nelect.sync _|p, 0xffffffff;\nand.pred p, p, q;\n"
                 "@p mbarrier.arrive.shared::cluster.b64 _, [%1];\n@p mbarrier.arrive.shared::cta.b64 _, [%0];\n}"
                 ::"r"(bar), "r"(peer_bar), "r"((uint32_t)pred) : "memory");
}
__device__ __forceinline__ void mbar_expect_tx(uint32_t bar, uint32_t bytes) {
    asm volatile("mbarrier.arrive.expect_tx.shared::cta.b64 _, [%0], %1;" ::"r"(bar), "r"(bytes) : "memory");
}
constexpr int WAIT_HINT_NS = 20000, WAIT_TRIES = 200000;
__device__ __forceinline__ void mbar_wait(uint32_t bar, uint32_t parity) {
    asm volatile("{\n.reg .pred p;\n.reg .u32 c;\n"
                 "mbarrier.try_wait.parity.shared::cta.b64 p, [%0], %1;\n@p bra DONE;\nmov.u32 c, 0;\n"
                 "SPIN:\nmbarrier.try_wait.parity.shared::cta.b64 p, [%0], %1, %2;\n@p bra DONE;\n"
                 "add.u32 c, c, 1;\nsetp.lt.u32 p, c, %3;\n@p bra SPIN;\ntrap;\nDONE:\n}"
                 ::"r"(bar), "r"(parity), "n"(WAIT_HINT_NS), "n"(WAIT_TRIES) : "memory");
}
__device__ __forceinline__ void mbar_wait_hot(uint32_t bar, uint32_t parity) {
    asm volatile("{\n.reg .pred p, q;\n.reg .u32 c;\n.reg .u64 z;\nmov.u32 c, 0;\nmov.u64 z, 0;\n"
                 "SPIN:\nmbarrier.try_wait.parity.shared::cta.b64 p, [%0], %1;\n"
                 "add.u32 c, c, 1;\nsetp.lt.and.u32 q, c, 4194304, !p;\n@q bra SPIN;\n@!p st.global.u32 [z], c;\n}"
                 ::"r"(bar), "r"(parity) : "memory");
}
constexpr uint64_t POL_STREAM = 0x12F0000000000000ull;
constexpr uint64_t POL_NORMAL = 0x1000000000000000ull;
__device__ __forceinline__ void tma_load_3d(uint32_t dst, const CUtensorMap* map, uint32_t bar, int c0, int c1, int c2, uint64_t pol = POL_NORMAL) {
    asm volatile("cp.async.bulk.tensor.3d.shared::cluster.global.mbarrier::complete_tx::bytes.L2::cache_hint [%0], [%1, {%3, %4, %5}], [%2], %6;"
                 ::"r"(dst), "l"(map), "r"(bar), "r"(c0), "r"(c1), "r"(c2), "l"(pol) : "memory");
}
__device__ __forceinline__ void load_kstep(uint32_t sa, uint32_t sw, uint32_t bar, uint32_t bytes, const CUtensorMap* wmap, int wk, int wblk,
                                           const CUtensorMap* amap, int arow, int kc, uint32_t amode) {
    asm volatile("{\n.reg .pred p, q, r;\n.reg .b32 k;\nelect.sync _|p, 0xffffffff;\nsetp.eq.and.u32 q, %9, 1, p;\nsetp.eq.and.u32 r, %9, 2, p;\nshl.b32 k, %12, 6;\n"
                 "@p mbarrier.arrive.expect_tx.shared::cta.b64 _, [%2], %3;\n"
                 "@p cp.async.bulk.tensor.3d.shared::cluster.global.mbarrier::complete_tx::bytes.multicast::cluster.L2::cache_hint [%1], [%4, {0, k, %5}], [%2], %10, %11;\n"
                 "@q cp.async.bulk.tensor.3d.shared::cluster.global.mbarrier::complete_tx::bytes.L2::cache_hint [%0], [%6, {0, %7, %8}], [%2], %11;\n"
                 "@r cp.async.bulk.tensor.4d.shared::cluster.global.mbarrier::complete_tx::bytes.L2::cache_hint [%0], [%6, {0, %7, 0, %8}], [%2], %11;\n}"
                 ::"r"(sa), "r"(sw), "r"(bar), "r"(bytes), "l"(wmap), "r"(wblk), "l"(amap), "r"(arow), "r"(kc), "r"(amode), "h"((uint16_t)3), "l"(POL_NORMAL), "r"(wk) : "memory");
}
__device__ __forceinline__ void load_operand(uint32_t dst, uint32_t bar, const CUtensorMap* full, const CUtensorMap* half, int row, int blk,
                                             uint32_t rank, bool solo, uint64_t pol) {
    asm volatile("{\n.reg .pred p, q, r;\n.reg .b32 d, b;\nelect.sync _|p, 0xffffffff;\nsetp.ne.and.u32 q, %7, 0, p;\nsetp.eq.and.u32 r, %7, 0, p;\n"
                 "mad.lo.u32 d, %6, 16384, %0;\nadd.u32 b, %5, %6;\n"
                 "@p mbarrier.arrive.expect_tx.shared::cta.b64 _, [%1], 32768;\n"
                 "@q cp.async.bulk.tensor.3d.shared::cluster.global.mbarrier::complete_tx::bytes.L2::cache_hint [%0], [%2, {0, %4, %5}], [%1], %9;\n"
                 "@r cp.async.bulk.tensor.3d.shared::cluster.global.mbarrier::complete_tx::bytes.multicast::cluster.L2::cache_hint [d], [%3, {0, %4, b}], [%1], %8, %9;\n}"
                 ::"r"(dst), "r"(bar), "l"(full), "l"(half), "r"(row), "r"(blk), "r"(rank), "r"((uint32_t)solo), "h"((uint16_t)3), "l"(pol) : "memory");
}
__device__ __forceinline__ void tma_store_par(const CUtensorMap* map, uint32_t src, int pair, int parity, int blk) {
    asm volatile("cp.async.bulk.tensor.4d.global.shared::cta.bulk_group.L2::cache_hint [%0, {0, %2, %3, %4}], [%1], %5;"
                 ::"l"(map), "r"(src), "r"(pair), "r"(parity), "r"(blk), "l"(POL_STREAM) : "memory");
}
__device__ __forceinline__ void tma_store_3d(const CUtensorMap* map, uint32_t src, int c0, int c1, int c2, uint64_t pol) {
    asm volatile("cp.async.bulk.tensor.3d.global.shared::cta.bulk_group.L2::cache_hint [%0, {%2, %3, %4}], [%1], %5;"
                 ::"l"(map), "r"(src), "r"(c0), "r"(c1), "r"(c2), "l"(pol) : "memory");
}
__device__ __forceinline__ void tma_reduce_add_3d(const CUtensorMap* map, uint32_t src, int c0, int c1, int c2) {
    asm volatile("cp.reduce.async.bulk.tensor.3d.global.shared::cta.add.tile.bulk_group [%0, {%2, %3, %4}], [%1];"
                 ::"l"(map), "r"(src), "r"(c0), "r"(c1), "r"(c2) : "memory");
}
__device__ __forceinline__ void bulk_commit() { asm volatile("cp.async.bulk.commit_group;" ::: "memory"); }
template <int N> __device__ __forceinline__ void bulk_wait_read() { asm volatile("cp.async.bulk.wait_group.read %0;" ::"n"(N) : "memory"); }
template <int N> __device__ __forceinline__ void bulk_wait() { asm volatile("cp.async.bulk.wait_group %0;" ::"n"(N) : "memory"); }
__device__ __forceinline__ void fence_async_smem() { asm volatile("fence.proxy.async.shared::cta;" ::: "memory"); }
__device__ __forceinline__ void fence_async_global() { asm volatile("fence.proxy.async.global;" ::: "memory"); }
__device__ __forceinline__ uint32_t ld_acquire(const uint32_t* p) {
    uint32_t v;
    asm volatile("ld.acquire.gpu.global.u32 %0, [%1];" : "=r"(v) : "l"(p) : "memory");
    return v;
}
__device__ __forceinline__ uint32_t ld_relaxed(const uint32_t* p) {
    uint32_t v;
    asm volatile("ld.relaxed.gpu.global.u32 %0, [%1];" : "=r"(v) : "l"(p) : "memory");
    return v;
}
__device__ __forceinline__ void fence_acquire() { asm volatile("fence.acquire.gpu;\nfence.proxy.async.global;" ::: "memory"); }
__device__ __forceinline__ void red_release(uint32_t* p) {
    asm volatile("red.release.gpu.global.add.u32 [%0], 1;" ::"l"(p) : "memory");
}
__device__ __forceinline__ void red_relaxed(uint32_t* p) {
    asm volatile("red.relaxed.gpu.global.add.u32 [%0], 1;" ::"l"(p) : "memory");
}
__device__ __forceinline__ void prefetch_map(const CUtensorMap* map) { asm volatile("prefetch.tensormap [%0];" ::"l"(map) : "memory"); }
__device__ __forceinline__ void trap_if(bool c) { asm volatile("{\n.reg .pred p;\nsetp.ne.u32 p, %0, 0;\n@p trap;\n}" ::"r"((uint32_t)c)); }
__device__ __forceinline__ void setup_arrive() { asm volatile("barrier.cluster.arrive.relaxed.aligned;" ::: "memory"); }
__device__ __forceinline__ void setup_wait() { asm volatile("barrier.cluster.wait.aligned;" ::: "memory"); }
__device__ __forceinline__ uint32_t cluster_rank() { uint32_t r; asm("mov.u32 %0, %%cluster_ctarank;" : "=r"(r)); return r; }
__device__ __forceinline__ void named_sync(int id, int n) { asm volatile("bar.sync %0, %1;" ::"r"(id), "r"(n) : "memory"); }
__device__ __forceinline__ void named_arrive(int id, int n) { asm volatile("bar.arrive %0, %1;" ::"r"(id), "r"(n) : "memory"); }
__device__ __forceinline__ void named_sync_if(bool c, int id, int n) {
    asm volatile("{\n.reg .pred p;\nsetp.ne.u32 p, %0, 0;\n@p bar.sync %1, %2;\n}" ::"r"((uint32_t)c), "r"(id), "r"(n) : "memory");
}
__device__ __forceinline__ void named_arrive_if(bool c, int id, int n) {
    asm volatile("{\n.reg .pred p;\nsetp.ne.u32 p, %0, 0;\n@p bar.arrive %1, %2;\n}" ::"r"((uint32_t)c), "r"(id), "r"(n) : "memory");
}
template <int V> struct IC { static constexpr int v = V; };
template <int N> __device__ __forceinline__ void reg_dec() { asm volatile("setmaxnreg.dec.sync.aligned.u32 %0;" ::"n"(N)); }
template <int N> __device__ __forceinline__ void reg_inc() { asm volatile("setmaxnreg.inc.sync.aligned.u32 %0;" ::"n"(N)); }

__device__ __forceinline__ void wg_fence() { asm volatile("wgmma.fence.sync.aligned;" ::: "memory"); }
__device__ __forceinline__ void wg_commit() { asm volatile("wgmma.commit_group.sync.aligned;" ::: "memory"); }
template <int N> __device__ __forceinline__ void wg_wait() { asm volatile("wgmma.wait_group.sync.aligned %0;" ::"n"(N) : "memory"); }
template <int N> __device__ __forceinline__ void fence_regs(float (&r)[N]) {
#pragma unroll
    for (int i = 0; i < N; i++) asm volatile("" : "+f"(r[i])::"memory");
}
template <int N> __device__ __forceinline__ void fence_regs(uint32_t (&r)[N]) {
#pragma unroll
    for (int i = 0; i < N; i++) asm volatile("" : "+r"(r[i])::"memory");
}
__device__ __forceinline__ uint32_t desc_lo(uint32_t addr, uint32_t lbo) { return ((addr & 0x3FFFF) >> 4) | ((lbo >> 4) << 16); }
__device__ __forceinline__ int uniform(int v) { return __shfl_sync(0xffffffffu, v, 0); }
__device__ __forceinline__ uint32_t pack_bf16(float lo, float hi) {
    uint32_t r;
    asm("cvt.rn.bf16x2.f32 %0, %1, %2;" : "=r"(r) : "f"(hi), "f"(lo));
    return r;
}
__device__ __forceinline__ uint32_t mul_bf16x2(uint32_t x, uint32_t y) {
    uint32_t r;
    asm("mul.rn.bf16x2 %0, %1, %2;" : "=r"(r) : "r"(x), "r"(y));
    return r;
}
__device__ __forceinline__ void stmatrix_x4(uint32_t addr, uint32_t r0, uint32_t r1, uint32_t r2, uint32_t r3) {
    asm volatile("stmatrix.sync.aligned.m8n8.x4.shared.b16 [%0], {%1, %2, %3, %4};"
                 ::"r"(addr), "r"(r0), "r"(r1), "r"(r2), "r"(r3) : "memory");
}
__device__ __forceinline__ void stmatrix_x4(uint32_t addr, uint32_t r0, uint32_t r1, uint32_t r2, uint32_t r3, bool trans) {
    asm volatile("{\n.reg .pred p;\nsetp.ne.u32 p, %5, 0;\n@p stmatrix.sync.aligned.m8n8.x4.trans.shared.b16 [%0], {%1, %2, %3, %4};\n"
                 "@!p stmatrix.sync.aligned.m8n8.x4.shared.b16 [%0], {%1, %2, %3, %4};\n}"
                 ::"r"(addr), "r"(r0), "r"(r1), "r"(r2), "r"(r3), "r"((uint32_t)trans) : "memory");
}
__device__ __forceinline__ void ldmatrix_x4_t(uint32_t addr, uint32_t (&r)[4]) {
    asm volatile("ldmatrix.sync.aligned.m8n8.x4.trans.shared.b16 {%0, %1, %2, %3}, [%4];"
                 : "=r"(r[0]), "=r"(r[1]), "=r"(r[2]), "=r"(r[3]) : "r"(addr) : "memory");
}
__device__ __forceinline__ void mma_16816(float (&d)[4], uint32_t a0, uint32_t a1, uint32_t a2, uint32_t a3, uint32_t b0, uint32_t b1) {
    asm("mma.sync.aligned.m16n8k16.row.col.f32.bf16.bf16.f32 {%0, %1, %2, %3}, {%4, %5, %6, %7}, {%8, %9}, {%0, %1, %2, %3};"
        : "+f"(d[0]), "+f"(d[1]), "+f"(d[2]), "+f"(d[3]) : "r"(a0), "r"(a1), "r"(a2), "r"(a3), "r"(b0), "r"(b1));
}
__device__ __forceinline__ void order_after(float v, uint32_t scratch) {
    asm volatile("{\n.reg .pred p;\nsetp.gt.f32 p, %0, 0f70000000;\n@p st.shared.u32 [%1], 0;\n}" ::"f"(v), "r"(scratch) : "memory");
}
__device__ __forceinline__ float rcp(float x) { float y; asm("rcp.approx.ftz.f32 %0, %1;" : "=f"(y) : "f"(x)); return y; }
__device__ __forceinline__ float ex2(float x) { float y; asm("ex2.approx.ftz.f32 %0, %1;" : "=f"(y) : "f"(x)); return y; }

template <int OA, int OB>
__device__ __forceinline__ void wgmma_ss_n256(float (&d0)[64], float (&d1)[64], uint32_t da, uint32_t db) {
    asm volatile("{\n.reg .b32 ta, tb;\n.reg .b64 da, db;\nadd.u32 ta, %128, %130;\nadd.u32 tb, %129, %131;\n"
        "mov.b64 da, {ta, 0x40000040};\nmov.b64 db, {tb, 0x40000040};\n"
        "wgmma.mma_async.sync.aligned.m64n256k16.f32.bf16.bf16 {%0, %1, %2, %3, %4, %5, %6, %7, %8, %9, %10, %11, %12, %13, %14, %15, %16, %17, %18, %19, %20, %21, %22, %23, %24, %25, %26, %27, %28, %29, %30, %31, %32, %33, %34, %35, %36, %37, %38, %39, %40, %41, %42, %43, %44, %45, %46, %47, %48, %49, %50, %51, %52, %53, %54, %55, %56, %57, %58, %59, %60, %61, %62, %63, %64, %65, %66, %67, %68, %69, %70, %71, %72, %73, %74, %75, %76, %77, %78, %79, %80, %81, %82, %83, %84, %85, %86, %87, %88, %89, %90, %91, %92, %93, %94, %95, %96, %97, %98, %99, %100, %101, %102, %103, %104, %105, %106, %107, %108, %109, %110, %111, %112, %113, %114, %115, %116, %117, %118, %119, %120, %121, %122, %123, %124, %125, %126, %127}, da, db, 1, 1, 1, 0, 1;\n}\n"
        : "+f"(d0[0]), "+f"(d0[1]), "+f"(d0[2]), "+f"(d0[3]), "+f"(d0[4]), "+f"(d0[5]), "+f"(d0[6]), "+f"(d0[7]), "+f"(d0[8]), "+f"(d0[9]), "+f"(d0[10]), "+f"(d0[11]), "+f"(d0[12]), "+f"(d0[13]), "+f"(d0[14]), "+f"(d0[15]), "+f"(d0[16]), "+f"(d0[17]), "+f"(d0[18]), "+f"(d0[19]), "+f"(d0[20]), "+f"(d0[21]), "+f"(d0[22]), "+f"(d0[23]), "+f"(d0[24]), "+f"(d0[25]), "+f"(d0[26]), "+f"(d0[27]), "+f"(d0[28]), "+f"(d0[29]), "+f"(d0[30]), "+f"(d0[31]), "+f"(d0[32]), "+f"(d0[33]), "+f"(d0[34]), "+f"(d0[35]), "+f"(d0[36]), "+f"(d0[37]), "+f"(d0[38]), "+f"(d0[39]), "+f"(d0[40]), "+f"(d0[41]), "+f"(d0[42]), "+f"(d0[43]), "+f"(d0[44]), "+f"(d0[45]), "+f"(d0[46]), "+f"(d0[47]), "+f"(d0[48]), "+f"(d0[49]), "+f"(d0[50]), "+f"(d0[51]), "+f"(d0[52]), "+f"(d0[53]), "+f"(d0[54]), "+f"(d0[55]), "+f"(d0[56]), "+f"(d0[57]), "+f"(d0[58]), "+f"(d0[59]), "+f"(d0[60]), "+f"(d0[61]), "+f"(d0[62]), "+f"(d0[63]), "+f"(d1[0]), "+f"(d1[1]), "+f"(d1[2]), "+f"(d1[3]), "+f"(d1[4]), "+f"(d1[5]), "+f"(d1[6]), "+f"(d1[7]), "+f"(d1[8]), "+f"(d1[9]), "+f"(d1[10]), "+f"(d1[11]), "+f"(d1[12]), "+f"(d1[13]), "+f"(d1[14]), "+f"(d1[15]), "+f"(d1[16]), "+f"(d1[17]), "+f"(d1[18]), "+f"(d1[19]), "+f"(d1[20]), "+f"(d1[21]), "+f"(d1[22]), "+f"(d1[23]), "+f"(d1[24]), "+f"(d1[25]), "+f"(d1[26]), "+f"(d1[27]), "+f"(d1[28]), "+f"(d1[29]), "+f"(d1[30]), "+f"(d1[31]), "+f"(d1[32]), "+f"(d1[33]), "+f"(d1[34]), "+f"(d1[35]), "+f"(d1[36]), "+f"(d1[37]), "+f"(d1[38]), "+f"(d1[39]), "+f"(d1[40]), "+f"(d1[41]), "+f"(d1[42]), "+f"(d1[43]), "+f"(d1[44]), "+f"(d1[45]), "+f"(d1[46]), "+f"(d1[47]), "+f"(d1[48]), "+f"(d1[49]), "+f"(d1[50]), "+f"(d1[51]), "+f"(d1[52]), "+f"(d1[53]), "+f"(d1[54]), "+f"(d1[55]), "+f"(d1[56]), "+f"(d1[57]), "+f"(d1[58]), "+f"(d1[59]), "+f"(d1[60]), "+f"(d1[61]), "+f"(d1[62]), "+f"(d1[63])
        : "r"(da), "r"(db), "n"(OA), "n"(OB));
}

__device__ __forceinline__ void wgmma_ss_n256_init(float (&d0)[64], float (&d1)[64], uint32_t da, uint32_t db) {
    asm volatile("{\n.reg .b64 da, db;\n"
        "mov.b64 da, {%128, 0x40000040};\nmov.b64 db, {%129, 0x40000040};\n"
        "wgmma.mma_async.sync.aligned.m64n256k16.f32.bf16.bf16 {%0, %1, %2, %3, %4, %5, %6, %7, %8, %9, %10, %11, %12, %13, %14, %15, %16, %17, %18, %19, %20, %21, %22, %23, %24, %25, %26, %27, %28, %29, %30, %31, %32, %33, %34, %35, %36, %37, %38, %39, %40, %41, %42, %43, %44, %45, %46, %47, %48, %49, %50, %51, %52, %53, %54, %55, %56, %57, %58, %59, %60, %61, %62, %63, %64, %65, %66, %67, %68, %69, %70, %71, %72, %73, %74, %75, %76, %77, %78, %79, %80, %81, %82, %83, %84, %85, %86, %87, %88, %89, %90, %91, %92, %93, %94, %95, %96, %97, %98, %99, %100, %101, %102, %103, %104, %105, %106, %107, %108, %109, %110, %111, %112, %113, %114, %115, %116, %117, %118, %119, %120, %121, %122, %123, %124, %125, %126, %127}, da, db, 0, 1, 1, 0, 1;\n}\n"
        : "=f"(d0[0]), "=f"(d0[1]), "=f"(d0[2]), "=f"(d0[3]), "=f"(d0[4]), "=f"(d0[5]), "=f"(d0[6]), "=f"(d0[7]), "=f"(d0[8]), "=f"(d0[9]), "=f"(d0[10]), "=f"(d0[11]), "=f"(d0[12]), "=f"(d0[13]), "=f"(d0[14]), "=f"(d0[15]), "=f"(d0[16]), "=f"(d0[17]), "=f"(d0[18]), "=f"(d0[19]), "=f"(d0[20]), "=f"(d0[21]), "=f"(d0[22]), "=f"(d0[23]), "=f"(d0[24]), "=f"(d0[25]), "=f"(d0[26]), "=f"(d0[27]), "=f"(d0[28]), "=f"(d0[29]), "=f"(d0[30]), "=f"(d0[31]), "=f"(d0[32]), "=f"(d0[33]), "=f"(d0[34]), "=f"(d0[35]), "=f"(d0[36]), "=f"(d0[37]), "=f"(d0[38]), "=f"(d0[39]), "=f"(d0[40]), "=f"(d0[41]), "=f"(d0[42]), "=f"(d0[43]), "=f"(d0[44]), "=f"(d0[45]), "=f"(d0[46]), "=f"(d0[47]), "=f"(d0[48]), "=f"(d0[49]), "=f"(d0[50]), "=f"(d0[51]), "=f"(d0[52]), "=f"(d0[53]), "=f"(d0[54]), "=f"(d0[55]), "=f"(d0[56]), "=f"(d0[57]), "=f"(d0[58]), "=f"(d0[59]), "=f"(d0[60]), "=f"(d0[61]), "=f"(d0[62]), "=f"(d0[63]), "=f"(d1[0]), "=f"(d1[1]), "=f"(d1[2]), "=f"(d1[3]), "=f"(d1[4]), "=f"(d1[5]), "=f"(d1[6]), "=f"(d1[7]), "=f"(d1[8]), "=f"(d1[9]), "=f"(d1[10]), "=f"(d1[11]), "=f"(d1[12]), "=f"(d1[13]), "=f"(d1[14]), "=f"(d1[15]), "=f"(d1[16]), "=f"(d1[17]), "=f"(d1[18]), "=f"(d1[19]), "=f"(d1[20]), "=f"(d1[21]), "=f"(d1[22]), "=f"(d1[23]), "=f"(d1[24]), "=f"(d1[25]), "=f"(d1[26]), "=f"(d1[27]), "=f"(d1[28]), "=f"(d1[29]), "=f"(d1[30]), "=f"(d1[31]), "=f"(d1[32]), "=f"(d1[33]), "=f"(d1[34]), "=f"(d1[35]), "=f"(d1[36]), "=f"(d1[37]), "=f"(d1[38]), "=f"(d1[39]), "=f"(d1[40]), "=f"(d1[41]), "=f"(d1[42]), "=f"(d1[43]), "=f"(d1[44]), "=f"(d1[45]), "=f"(d1[46]), "=f"(d1[47]), "=f"(d1[48]), "=f"(d1[49]), "=f"(d1[50]), "=f"(d1[51]), "=f"(d1[52]), "=f"(d1[53]), "=f"(d1[54]), "=f"(d1[55]), "=f"(d1[56]), "=f"(d1[57]), "=f"(d1[58]), "=f"(d1[59]), "=f"(d1[60]), "=f"(d1[61]), "=f"(d1[62]), "=f"(d1[63])
        : "r"(da), "r"(db));
}

template <int TB, int OA, int OB>
__device__ __forceinline__ void wgmma_ss_n128_init(float (&d)[64], uint32_t da, uint32_t db) {
    asm volatile("{\n.reg .b32 ta, tb;\n.reg .b64 da, db;\nadd.u32 ta, %64, %66;\nadd.u32 tb, %65, %67;\n"
        "mov.b64 da, {ta, 0x40000040};\nmov.b64 db, {tb, 0x40000040};\n"
        "wgmma.mma_async.sync.aligned.m64n128k16.f32.bf16.bf16 {%0, %1, %2, %3, %4, %5, %6, %7, %8, %9, %10, %11, %12, %13, %14, %15, %16, %17, %18, %19, %20, %21, %22, %23, %24, %25, %26, %27, %28, %29, %30, %31, %32, %33, %34, %35, %36, %37, %38, %39, %40, %41, %42, %43, %44, %45, %46, %47, %48, %49, %50, %51, %52, %53, %54, %55, %56, %57, %58, %59, %60, %61, %62, %63}, da, db, 0, 1, 1, 0, %68;\n}\n"
        : "=f"(d[0]), "=f"(d[1]), "=f"(d[2]), "=f"(d[3]), "=f"(d[4]), "=f"(d[5]), "=f"(d[6]), "=f"(d[7]), "=f"(d[8]), "=f"(d[9]), "=f"(d[10]), "=f"(d[11]), "=f"(d[12]), "=f"(d[13]), "=f"(d[14]), "=f"(d[15]), "=f"(d[16]), "=f"(d[17]), "=f"(d[18]), "=f"(d[19]), "=f"(d[20]), "=f"(d[21]), "=f"(d[22]), "=f"(d[23]), "=f"(d[24]), "=f"(d[25]), "=f"(d[26]), "=f"(d[27]), "=f"(d[28]), "=f"(d[29]), "=f"(d[30]), "=f"(d[31]), "=f"(d[32]), "=f"(d[33]), "=f"(d[34]), "=f"(d[35]), "=f"(d[36]), "=f"(d[37]), "=f"(d[38]), "=f"(d[39]), "=f"(d[40]), "=f"(d[41]), "=f"(d[42]), "=f"(d[43]), "=f"(d[44]), "=f"(d[45]), "=f"(d[46]), "=f"(d[47]), "=f"(d[48]), "=f"(d[49]), "=f"(d[50]), "=f"(d[51]), "=f"(d[52]), "=f"(d[53]), "=f"(d[54]), "=f"(d[55]), "=f"(d[56]), "=f"(d[57]), "=f"(d[58]), "=f"(d[59]), "=f"(d[60]), "=f"(d[61]), "=f"(d[62]), "=f"(d[63])
        : "r"(da), "r"(db), "n"(OA), "n"(OB), "n"(TB));
}

template <int OA, int OB>
__device__ __forceinline__ void wgmma_ss_n128_tb0(float (&d)[64], uint32_t da, uint32_t db, int scale_d) {
    asm volatile("{\n.reg .pred p;\n.reg .b32 ta, tb;\n.reg .b64 da, db;\nsetp.ne.b32 p, %66, 0;\nadd.u32 ta, %64, %67;\nadd.u32 tb, %65, %68;\n"
        "mov.b64 da, {ta, 0x40000040};\nmov.b64 db, {tb, 0x40000040};\n"
        "wgmma.mma_async.sync.aligned.m64n128k16.f32.bf16.bf16 "
        "{%0, %1, %2, %3, %4, %5, %6, %7, %8, %9, %10, %11, %12, %13, %14, %15, %16, %17, %18, %19, %20, %21, %22, %23, %24, %25, %26, %27, %28, %29, %30, %31, %32, %33, %34, %35, %36, %37, %38, %39, %40, %41, %42, %43, %44, %45, %46, %47, %48, %49, %50, %51, %52, %53, %54, %55, %56, %57, %58, %59, %60, %61, %62, %63}, da, db, p, 1, 1, 0, 0;\n}\n"
        : "+f"(d[0]), "+f"(d[1]), "+f"(d[2]), "+f"(d[3]), "+f"(d[4]), "+f"(d[5]), "+f"(d[6]), "+f"(d[7]), "+f"(d[8]), "+f"(d[9]), "+f"(d[10]), "+f"(d[11]), "+f"(d[12]), "+f"(d[13]), "+f"(d[14]), "+f"(d[15]), "+f"(d[16]), "+f"(d[17]), "+f"(d[18]), "+f"(d[19]), "+f"(d[20]), "+f"(d[21]), "+f"(d[22]), "+f"(d[23]), "+f"(d[24]), "+f"(d[25]), "+f"(d[26]), "+f"(d[27]), "+f"(d[28]), "+f"(d[29]), "+f"(d[30]), "+f"(d[31]), "+f"(d[32]), "+f"(d[33]), "+f"(d[34]), "+f"(d[35]), "+f"(d[36]), "+f"(d[37]), "+f"(d[38]), "+f"(d[39]), "+f"(d[40]), "+f"(d[41]), "+f"(d[42]), "+f"(d[43]), "+f"(d[44]), "+f"(d[45]), "+f"(d[46]), "+f"(d[47]), "+f"(d[48]), "+f"(d[49]), "+f"(d[50]), "+f"(d[51]), "+f"(d[52]), "+f"(d[53]), "+f"(d[54]), "+f"(d[55]), "+f"(d[56]), "+f"(d[57]), "+f"(d[58]), "+f"(d[59]), "+f"(d[60]), "+f"(d[61]), "+f"(d[62]), "+f"(d[63])
        : "r"(da), "r"(db), "r"(scale_d), "n"(OA), "n"(OB));
}

template <int OB>
__device__ __forceinline__ void wgmma_rs_n128_tb1(float (&d)[64], uint32_t a0, uint32_t a1, uint32_t a2, uint32_t a3, uint32_t db, int scale_d) {
    asm volatile("{\n.reg .pred p;\n.reg .b32 tb;\n.reg .b64 db;\nsetp.ne.b32 p, %69, 0;\nadd.u32 tb, %68, %70;\n"
        "mov.b64 db, {tb, 0x40000040};\n"
        "wgmma.mma_async.sync.aligned.m64n128k16.f32.bf16.bf16 "
        "{%0, %1, %2, %3, %4, %5, %6, %7, %8, %9, %10, %11, %12, %13, %14, %15, %16, %17, %18, %19, %20, %21, %22, %23, %24, %25, %26, %27, %28, %29, %30, %31, %32, %33, %34, %35, %36, %37, %38, %39, %40, %41, %42, %43, %44, %45, %46, %47, %48, %49, %50, %51, %52, %53, %54, %55, %56, %57, %58, %59, %60, %61, %62, %63}, {%64, %65, %66, %67}, db, p, 1, 1, 1;\n}\n"
        : "+f"(d[0]), "+f"(d[1]), "+f"(d[2]), "+f"(d[3]), "+f"(d[4]), "+f"(d[5]), "+f"(d[6]), "+f"(d[7]), "+f"(d[8]), "+f"(d[9]), "+f"(d[10]), "+f"(d[11]), "+f"(d[12]), "+f"(d[13]), "+f"(d[14]), "+f"(d[15]), "+f"(d[16]), "+f"(d[17]), "+f"(d[18]), "+f"(d[19]), "+f"(d[20]), "+f"(d[21]), "+f"(d[22]), "+f"(d[23]), "+f"(d[24]), "+f"(d[25]), "+f"(d[26]), "+f"(d[27]), "+f"(d[28]), "+f"(d[29]), "+f"(d[30]), "+f"(d[31]), "+f"(d[32]), "+f"(d[33]), "+f"(d[34]), "+f"(d[35]), "+f"(d[36]), "+f"(d[37]), "+f"(d[38]), "+f"(d[39]), "+f"(d[40]), "+f"(d[41]), "+f"(d[42]), "+f"(d[43]), "+f"(d[44]), "+f"(d[45]), "+f"(d[46]), "+f"(d[47]), "+f"(d[48]), "+f"(d[49]), "+f"(d[50]), "+f"(d[51]), "+f"(d[52]), "+f"(d[53]), "+f"(d[54]), "+f"(d[55]), "+f"(d[56]), "+f"(d[57]), "+f"(d[58]), "+f"(d[59]), "+f"(d[60]), "+f"(d[61]), "+f"(d[62]), "+f"(d[63])
        : "r"(a0), "r"(a1), "r"(a2), "r"(a3), "r"(db), "r"(scale_d), "n"(OB));
}

__device__ __forceinline__ uint32_t stage_addr(uint32_t block, int warp, int lane) {
    return block + (warp * 16 + (lane & 7) + ((lane >> 3) & 1) * 8) * 128 + (((lane >> 4) ^ (lane & 7)) << 4);
}
template <int OFF, int N>
__device__ __forceinline__ void stage_packed_64x64(uint32_t a0, int off, const uint32_t (&v)[N]) {
#pragma unroll
    for (int j = 0; j < 8; j += 2) {
        uint32_t a = a0;
        if (j) asm volatile("xor.b32 %0, %1, %2;" : "=r"(a) : "r"(a0), "r"(j << 4));
        stmatrix_x4(a + off, v[OFF + j * 2], v[OFF + j * 2 + 1], v[OFF + j * 2 + 2], v[OFF + j * 2 + 3]);
    }
}

template <int OFF, int N>
__device__ __forceinline__ void stage_packed_64x64(const uint32_t (&a)[4], int off, const uint32_t (&v)[N]) {
#pragma unroll
    for (int j = 0; j < 4; j++) stmatrix_x4(a[j] + off, v[OFF + j * 4], v[OFF + j * 4 + 1], v[OFF + j * 4 + 2], v[OFF + j * 4 + 3]);
}

template <int OFF, int N>
__device__ __forceinline__ void stage_packed_64x64(const uint32_t (&a)[4], int off, const uint32_t (&v)[N], bool trans) {
#pragma unroll
    for (int j = 0; j < 4; j++) stmatrix_x4(a[j] + off, v[OFF + j * 4], v[OFF + j * 4 + 1], v[OFF + j * 4 + 2], v[OFF + j * 4 + 3], trans);
}

constexpr int MAX_JOBS = 24;
constexpr int MAX_ROUNDS = 44;
constexpr int T_P = 0, T_O = 1, T_A = 2;
constexpr int HQ_A = 4, HQ_B = 28;
__host__ __device__ constexpr int unit_head(int g) { return g + (g < 4 ? HQ_A : HQ_B - 4); }
constexpr int G_STAGE = 49152;
constexpr int OFF_Q0 = 0, OFF_K0 = 32768, OFF_Q1 = 65536, OFF_K1 = 98304, OFF_V0 = 131072, OFF_V1 = 163840;
constexpr int OFF_STG = 196608;
constexpr int OFF_BAR = 229376;
constexpr int SMEM_BYTES = OFF_BAR + 640;
constexpr int TURN_THREADS = 288;

struct Params {
    CUtensorMap amap[2];
    CUtensorMap wmap[4];
    CUtensorMap x_par, wo_a, wo_b, qkv_st, qkv_ld, qkv_half, st_par, out_st;
    const __nv_bfloat16* xp;
    const __nv_bfloat16* gate_w;
    __nv_bfloat16* out;
    uint2 first[NUM_SMS];
    int16_t jobs[NUM_SMS][MAX_JOBS];
    uint16_t rounds[NUM_SMS / 2][MAX_ROUNDS];
};

constexpr int O_STAGGER = 4;
constexpr int O_F0 = 35, O_H1 = 5;
constexpr int O_FLEX = 16, O_H0 = O_F0 + 8, O_T0 = 8, O_T1 = 64 - O_F0 - O_FLEX - O_H1;
__device__ __forceinline__ int o_head(int job) { return (job & 32) ? O_H1 : O_H0; }
__device__ __forceinline__ int o_tail(int job) { return (job & 32) ? O_T1 : O_T0; }
__device__ __forceinline__ uint32_t o_state(uint32_t word, int have) {
    uint32_t v;
    asm volatile("{\n.reg .pred p, q;\n.reg .u32 c, t;\nmov.u32 c, 0;\n"
                 "SPIN:\nld.volatile.shared.u32 %0, [%1];\nand.b32 t, %0, 1;\nsetp.ne.u32 q, t, 0;\nsetp.gt.or.u32 p, %0, %2, q;\n@p bra DONE;\n"
                 "add.u32 c, c, 1;\nsetp.lt.u32 q, c, 16777216;\n@q bra SPIN;\ntrap;\nDONE:\n}"
                 : "=r"(v) : "r"(word), "r"(2 * have + 1) : "memory");
    return v;
}

template <class T> __device__ __forceinline__ T* page_ptr(int off) {
    extern __shared__ __align__(1024) uint8_t smem_raw[];
    return *reinterpret_cast<T* volatile*>(smem_raw + OFF_BAR + off);
}
template <int SLEEP_NS = 0>
__device__ __forceinline__ bool wait_flags(bool active, int idx, uint32_t target, bool block = true) {
    for (uint32_t tries = 0;; tries++) {
        const bool ok = !active | ((int32_t)(ld_acquire(g_flags + idx) - target) >= 0);
        if (__all_sync(0xffffffffu, ok)) break;
        if (!block) return false;
        if (SLEEP_NS) __nanosleep(SLEEP_NS);
        trap_if(tries > (1u << 22));
    }
    fence_async_global();
    return true;
}

__global__ void __cluster_dims__(2, 1, 1) __launch_bounds__(384, 1)
fused_kernel(const __grid_constant__ Params p) {
    extern __shared__ __align__(1024) uint8_t smem_raw[];
    const uint32_t base = smem_u32(smem_raw);
    const uint32_t bars = base + OFF_BAR;
    const uint32_t gfull = bars, gempty = bars + 32, sfull = bars + 64, sempty = bars + 96;
    const uint32_t qfull = bars + 128, qempty = bars + 144, kfull = bars + 160, kempty = bars + 176;
    const uint32_t vfull = bars + 192, vempty = bars + 208, lready = bars + 224, hout = bars + 240;
    const uint32_t tfull = bars + 256, aready = bars + 272, gatefull = bars + 280;
    const uint32_t otile = bars + 528;
    const uint32_t olim = bars + 504;
    const uint32_t stg = base + OFF_STG;
    uint32_t* rounds = reinterpret_cast<uint32_t*>(smem_raw + OFF_BAR + 416);
    const uint32_t rank = cluster_rank();
    int* jobs = reinterpret_cast<int*>(smem_raw + OFF_BAR + 312);
    auto w_map = [&](uint32_t rec, uint32_t half) INL { return &p.wmap[(rec & 8) ? 2 + half : ((rec >> 15) && half ? 0 : rec >> 4 & 1)]; };
    auto w_blk = [&](uint32_t rec, uint32_t half) INL -> int {
        const int col = rec >> 6 & 15;
        if (rec & 8) return (col + (rec & 16)) * 2;
        return rec >> 14 == 0 ? col * 4 + half * 2 : (rec >> 14 == 1 ? 16 + half * 16 + col * 2 : (half ? unit_head(col) : col) * 2);
    };
    auto load_round = [&](uint32_t rec, int st0, uint32_t parity) INL {
        const CUtensorMap* wm = w_map(rec, rank);
        const CUtensorMap* am = rec >> 14 ? &p.x_par : &p.amap[rec >> 3 & 1];
        const int wb = w_blk(rec, rank), kc0 = (rec >> 10 & 3) * 4, arow = ((rec & 7) * 256 + rank * 128) >> (rec >> 14 ? 1 : 0);
        const uint32_t bytes = (rec & 4096) ? G_STAGE - 16384 : G_STAGE, amode = (rec & 4096) ? 0 : (rec >> 14 ? 2 : 1);
#pragma unroll 1
        for (int st = st0; st < 4; st++) {
            const uint32_t sa = base + st * G_STAGE;
            mbar_wait(gempty + st * 8, parity);
            load_kstep(sa, sa + 16384 + rank * 16384, gfull + st * 8, bytes, wm, kc0 + st, wb, am, arow, kc0 + st, amode);
        }
    };
    if (threadIdx.x < 32) {
        if (elect_one()) {
            const uint2 r = p.first[blockIdx.x];
            mbar_init(gfull, 1);
            fence_async_smem();
            const char* maps;
            asm("mov.b64 %0, %1;" : "=l"(maps) : "l"(&p.amap[0]));
            asm volatile("{\n.reg .pred q;\nsetp.eq.u32 q, %8, 0;\n"
                         "mbarrier.arrive.expect_tx.shared::cta.b64 _, [%1], 49152;\n"
                         "cp.async.bulk.tensor.3d.shared::cluster.global.mbarrier::complete_tx::bytes.L2::cache_hint [%9], [%3, {0, 0, %6}], [%1], %11;\n"
                         "cp.async.bulk.tensor.3d.shared::cluster.global.mbarrier::complete_tx::bytes.L2::cache_hint [%10], [%4, {0, 0, %7}], [%1], %11;\n"
                         "@q cp.async.bulk.tensor.3d.shared::cluster.global.mbarrier::complete_tx::bytes.L2::cache_hint [%0], [%2, {0, %5, 0}], [%1], %11;\n"
                         "@!q cp.async.bulk.tensor.4d.shared::cluster.global.mbarrier::complete_tx::bytes.L2::cache_hint [%0], [%2, {0, %5, 0, 0}], [%1], %11;\n}"
                         ::"r"(base), "r"(gfull), "l"(maps + (r.x & 0x780)), "l"(maps + (r.x >> 4 & 0x780)), "l"(maps + (r.x >> 8 & 0x780)),
                           "r"(r.x >> 20), "r"(r.y & 0xffff), "r"(r.y >> 16), "r"(r.x & 1), "r"(base + 16384), "r"(base + 32768), "l"(POL_NORMAL) : "memory");
            asm volatile("fence.mbarrier_init.release.cluster;" ::: "memory");
        }
        __syncwarp();
    }
    const int tid = threadIdx.x, warp = uniform(tid >> 5), lane = tid & 31, wg = warp >> 2;
    if (warp == 1) {
        if (elect_one()) {
#pragma unroll
            for (int i = 1; i < 39; i++)
                mbar_init(bars + i * 8, (0x0CC000F0ull >> i & 1) ? 16 : ((0x300000F00ull >> i & 1) ? 4 : ((0xC0000ull >> i & 1) ? 8 : 1)));
            asm volatile("fence.mbarrier_init.release.cluster;" ::: "memory");
            fence_async_smem();
        }
        __syncwarp();
    }
    setup_arrive();
    if (warp > 3) {
        reg_inc<232>();
        named_sync(0, 352);
        const int w = wg - 1, wwarp = warp & 3;
        const uint32_t slot_a = stage_addr(stg + w * 16384, wwarp, lane);
        const uint32_t bars_peer = uniform(mapa(bars, rank ^ 1));
        auto arrive_pair = [&](uint32_t bar, bool pred = true) INL { warp_arrive_pair(bar, bars_peer + (bar - bars), pred); };
        uint32_t gph = 0;
        uint32_t sph = 1;
        int jb = 0;
        int job = uniform(jobs[0]);
        auto next_job = [&]() INL { jb++; job = uniform(jobs[jb]); };
        auto slot_wait = [&](int q) INL { mbar_wait(sempty + (w * 2 + (q & 1)) * 8, (q >> 1) ^ sph ^ 1); };
        auto signal = [&](int q) INL {
            __syncwarp();
            warp_arrive(sfull + (w * 2 + (q & 1)) * 8);
        };
        uint32_t pk[64];
        float O[64];
        uint32_t slot4[4];
        bool ptrans = false;
        auto stage_quarter = [&](const int Q) INL {
            slot_wait(Q);
            if (Q == 0) stage_packed_64x64<0>(slot4, 0, pk, ptrans);
            if (Q == 1) stage_packed_64x64<16>(slot4, 8192, pk, ptrans);
            if (Q == 2) stage_packed_64x64<32>(slot4, 0, pk);
            if (Q == 3) stage_packed_64x64<48>(slot4, 8192, pk);
        };
        auto stage_pair = [&]() INL {
            slot_wait(1);
            stage_packed_64x64<0>(slot4, 0, pk, ptrans);
            stage_packed_64x64<16>(slot4, 8192, pk, ptrans);
        };
        auto signal_both = [&]() INL {
            __syncwarp();
            warp_arrive2(sfull + w * 16, sfull + w * 16 + 8);
        };
        uint32_t un = 0;
        auto lane_id = [&]() INL { uint32_t ln; asm volatile("mov.u32 %0, %%laneid;" : "=r"(ln)); return ln; };
        auto v_addr = [&](uint32_t ln) INL { return stg + w * 16384 + (wwarp * 16 + (ln & 7)) * 128 + (((ln >> 3) ^ (ln & 7)) << 4); };
        auto v_off = [&](uint32_t a, const int h) INL { return (a ^ ((h & 1) * 64)) + (h >> 1) * 8192; };
        auto halo_ptr = [&](int mt, int g, int slot, uint32_t ln) INL { return page_ptr<uint4>(512) + (((mt * 8 + g) * 2 + w) * 5 + slot) * 128 + ln; };
        auto pack_k = [&](const float (&acc)[64]) INL {
#pragma unroll
            for (int j = 0; j < 16; j++) { pk[j] = pack_bf16(acc[4 * j], acc[4 * j + 1]); pk[16 + j] = pack_bf16(acc[4 * j + 2], acc[4 * j + 3]); }
        };
        auto unit_export = [&](int cur) INL {
            const uint32_t ln = lane_id();
            uint4* dst = halo_ptr((cur & 7) * 2 + rank, cur >> 3 & 7, wwarp, ln);
            slot_wait(1);
            stage_packed_64x64<32>(slot4, 0, pk);
            stage_packed_64x64<48>(slot4, 8192, pk);
#pragma unroll
            for (int h = 0; h < 4; h++) __stcg(dst + h * 32, make_uint4(pk[16 + h * 4], pk[17 + h * 4], pk[18 + h * 4], pk[19 + h * 4]));
            __syncwarp();
            if (wwarp == 3) {
                const uint32_t va = v_addr(ln) + 1024;
#pragma unroll
                for (int h = 0; h < 4; h++) {
                    uint32_t t[4];
                    ldmatrix_x4_t(v_off(va, h), t);
                    pk[32 + h * 4] = t[0]; pk[33 + h * 4] = t[1]; pk[34 + h * 4] = t[2]; pk[35 + h * 4] = t[3];
                }
#pragma unroll
                for (int h = 0; h < 4; h++) __stcg(dst + 128 + h * 32, make_uint4(pk[32 + h * 4], pk[33 + h * 4], pk[34 + h * 4], pk[35 + h * 4]));
                __syncwarp();
                warp_arrive(hout + w * 8);
            }
        };
        auto unit_import = [&](int cur) INL {
            const uint32_t ln = lane_id();
            const int mt = (cur & 7) * 2 + rank;
            mbar_wait(lready + un * 8, 0);
            un++;
            const uint4* src = halo_ptr(wwarp ? mt : max(mt - 1, 0), cur >> 3 & 7, (wwarp + 3) & 3, ln);
#pragma unroll
            for (int h = 0; h < 4; h++) {
                const uint4 t = __ldcg(src + h * 32);
                pk[32 + h * 4] = t.x; pk[33 + h * 4] = t.y; pk[34 + h * 4] = t.z; pk[35 + h * 4] = t.w;
            }
            if (wwarp) {
                const uint32_t va = v_addr(ln) - 1024;
#pragma unroll
                for (int h = 0; h < 4; h++) {
                    uint32_t t[4];
                    ldmatrix_x4_t(v_off(va, h), t);
                    pk[48 + h * 4] = t[0]; pk[49 + h * 4] = t[1]; pk[50 + h * 4] = t[2]; pk[51 + h * 4] = t[3];
                }
            } else {
#pragma unroll
                for (int h = 0; h < 4; h++) {
                    const uint4 t = __ldcg(src + 128 + h * 32);
                    pk[48 + h * 4] = t.x; pk[49 + h * 4] = t.y; pk[50 + h * 4] = t.z; pk[51 + h * 4] = t.w;
                }
            }
        };
        auto unit_attend = [&](const float (&q)[64], int cur) INL {
            const float cs = 0.17677669529663687f * 1.4426950408889634f;
            const uint32_t ln = lane_id();
            const int g = ln >> 2, c2 = (ln & 3) * 2, mt = (cur & 7) * 2 + rank;
            uint32_t qf[32], vo[8][4];
#pragma unroll
            for (int i = 0; i < 32; i++) qf[i] = pack_bf16(q[2 * i], q[2 * i + 1]);
            fence_regs(qf);
            const float* gp = page_ptr<float>(520) + mt * 128 + wwarp * 32 + g * 2 + w;
            const float lg0 = 1.f - __ldcg(gp), lg1 = 1.f - __ldcg(gp + 16);
            const uint32_t va = stg + w * 16384 + (wwarp * 16 + (ln & 7) + (ln >> 4) * 8) * 128 + ((((ln >> 3) & 1) ^ (ln & 7)) << 4);
#pragma unroll
            for (int i = 0; i < 8; i++) ldmatrix_x4_t((va ^ ((i & 3) * 32)) + (i >> 2) * 8192, vo[i]);
            const bool m0 = c2 > g, m1 = c2 + 1 > g, first = mt + wwarp == 0;
            const uint32_t mk = (m0 ? 0xffffu : 0u) | (m1 ? 0xffff0000u : 0u);
#pragma unroll
            for (int h = 0; h < 4; h++) {
                float s[3][4] = {};
#pragma unroll
                for (int k = 0; k < 2; k++) {
                    const int i = h * 8 + k * 4, j = h * 4 + k * 2;
                    mma_16816(s[0], qf[i], qf[i + 1], qf[i + 2], qf[i + 3], pk[32 + j], pk[33 + j]);
                    mma_16816(s[1], qf[i], qf[i + 1], qf[i + 2], qf[i + 3], pk[j], pk[j + 1]);
                    mma_16816(s[2], qf[i], qf[i + 1], qf[i + 2], qf[i + 3], pk[16 + j], pk[17 + j]);
                }
                if (first) s[0][0] = s[0][1] = -INFINITY;
                float u0 = m0 ? s[0][0] : s[1][0], u1 = m1 ? s[0][1] : s[1][1], v0 = m0 ? s[1][2] : s[2][2], v1 = m1 ? s[1][3] : s[2][3];
                float mu = fmaxf(u0, u1), mv = fmaxf(v0, v1);
                mu = fmaxf(mu, __shfl_xor_sync(0xffffffffu, mu, 1)); mv = fmaxf(mv, __shfl_xor_sync(0xffffffffu, mv, 1));
                mu = fmaxf(mu, __shfl_xor_sync(0xffffffffu, mu, 2)); mv = fmaxf(mv, __shfl_xor_sync(0xffffffffu, mv, 2));
                mu *= -cs; mv *= -cs;
                u0 = ex2(fmaf(u0, cs, mu)); u1 = ex2(fmaf(u1, cs, mu)); v0 = ex2(fmaf(v0, cs, mv)); v1 = ex2(fmaf(v1, cs, mv));
                float lu = u0 + u1, lv = v0 + v1;
                lu += __shfl_xor_sync(0xffffffffu, lu, 1); lv += __shfl_xor_sync(0xffffffffu, lv, 1);
                lu += __shfl_xor_sync(0xffffffffu, lu, 2); lv += __shfl_xor_sync(0xffffffffu, lv, 2);
                const float su = lg0 * rcp(lu), sv = lg1 * rcp(lv);
                const uint32_t pu = pack_bf16(u0 * su, u1 * su), pv = pack_bf16(v0 * sv, v1 * sv);
#pragma unroll
                for (int d = 0; d < 2; d++) {
                    const uint32_t (&vv)[4] = vo[h * 2 + d];
                    float oa[4] = {}, ob[4] = {};
                    mma_16816(oa, pk[48 + h * 4 + d * 2], pk[49 + h * 4 + d * 2], vv[0], vv[1], pu & mk, pu & ~mk);
                    mma_16816(ob, vv[0], vv[1], vv[2], vv[3], pv & mk, pv & ~mk);
                    qf[h * 8 + d * 4] = pack_bf16(oa[0], oa[1]); qf[h * 8 + d * 4 + 1] = pack_bf16(ob[0], ob[1]);
                    qf[h * 8 + d * 4 + 2] = pack_bf16(oa[2], oa[3]); qf[h * 8 + d * 4 + 3] = pack_bf16(ob[2], ob[3]);
                }
            }
#pragma unroll
            for (int i = 0; i < 32; i++) pk[i] = qf[i];
            named_sync(3 + w, 128);
        };
        auto pack_half = [&](const float (&acc)[64], const int OFF, float scale) INL {
#pragma unroll
            for (int i = 0; i < 32; i++) pk[OFF + i] = pack_bf16(acc[2 * i] * scale, acc[2 * i + 1] * scale);
        };
        auto gemm_run = [&]() INL {
                float acc0[64], acc1[64];
#pragma unroll
                for (int i = 0; i < 64; i++) pk[i] = 0;
#pragma unroll
                for (int j = 0; j < 4; j++) asm volatile("xor.b32 %0, %1, %2;" : "=r"(slot4[j]) : "r"(slot_a), "r"(j << 5));
                const uint32_t dA = desc_lo(base + w * 8192, 0), dB = desc_lo(base + 16384, 8192);
                auto wait_full = [&](int st) INL { mbar_wait_hot(gfull + st * 8, gph); };
                auto release = [&](int st) INL { arrive_pair(gempty + st * 8); };
                bool pend = false;
                auto kstep = [&](auto st_, const int Q, bool ending = false) INL {
                    constexpr int st = decltype(st_)::v, OA = st * (G_STAGE >> 4);
                    const bool held = st == 2 && ending && w;
                    if (st == 2 && __builtin_expect(held, 0)) {
                        wg_wait<0>();
                        release(1);
                        named_sync(6, 256);
                    }
                    wait_full(st);
                    wg_fence();
                    wgmma_ss_n256<OA, OA>(acc0, acc1, dA, dB);
                    wg_commit();
                    wg_wait<1>();
                    arrive_pair(gempty + ((st + 3) & 3) * 8, !held);
                    wg_fence();
                    wgmma_ss_n256<OA + 2, OA + 128>(acc0, acc1, dA, dB);
                    wgmma_ss_n256<OA + 4, OA + 256>(acc0, acc1, dA, dB);
                    if (st == 3) named_arrive_if(ending && !w, 6, 256);
                    wgmma_ss_n256<OA + 6, OA + 384>(acc0, acc1, dA, dB);
                    wg_commit();
                    if (Q >= 0) { stage_quarter(Q); signal(Q); }
                    KTRACE(w);
                };
                wait_full(0);
                GTRACE(w);
                while (true) {
                    wg_fence();
                    wgmma_ss_n256_init(acc0, acc1, dA, dB);
                    wgmma_ss_n256<2, 128>(acc0, acc1, dA, dB);
                    wgmma_ss_n256<4, 256>(acc0, acc1, dA, dB);
                    wgmma_ss_n256<6, 384>(acc0, acc1, dA, dB);
                    wg_commit();
                    KTRACE(w);
                    const int cur = job;
                    const bool is_o = cur >= (T_O << 12), unit2 = (cur >> 6) == 3;
                    const int tail = o_tail(cur);
                    int lim = is_o ? o_head(cur) + tail : (cur < 256 ? 16 : 8);
                    int left = unit2 ? 11 : lim - (is_o ? O_STAGGER + 1 : 1);
                    bool imp = unit2;
                    next_job();
                    if (__builtin_expect(unit2, 0)) { if (tid == TRACE_TID) PTRACE(4); unit_export(cur); if (tid == TRACE_TID) PTRACE(5); }
                    if (pend) {
                        kstep(IC<1>{}, 0);
                        kstep(IC<2>{}, -1);
                        kstep(IC<3>{}, 1);
                        GTRACE(w);
                        gph ^= 1;
                        kstep(IC<0>{}, -1);
                        kstep(IC<1>{}, 2);
                        kstep(IC<2>{}, 3, left == 7);
                        kstep(IC<3>{}, -1, left == 7);
                        GTRACE(w);
                        gph ^= 1;
                        left -= 7;
                        if (left > 0) { kstep(IC<0>{}, -1); left--; }
                    }
                    int last_st = 3;
#pragma unroll 1
                    while (left > 0) {
                        auto ends = [&]() INL -> bool {
                            if (__builtin_expect(--left > 0, 1)) return false;
                            if (is_o) {
                                const uint32_t v = uniform(o_state(olim, lim - tail));
                                const int n = (v >> 1) + ((v & 1) ? 0 : tail);
                                left = n - lim; lim = n;
                            }
                            return left == 0;
                        };
                        kstep(IC<1>{}, -1);
                        if (ends()) { last_st = 1; break; }
                        kstep(IC<2>{}, -1, left == 2 && !is_o && !imp);
                        if (ends()) { last_st = 2; break; }
                        kstep(IC<3>{}, -1, left == 1 && !is_o && !imp);
                        GTRACE(w);
                        gph ^= 1;
                        if (ends()) {
                            if (!imp) break;
                            if (tid == TRACE_TID) PTRACE(6);
                            unit_import(cur);
                            if (tid == TRACE_TID) PTRACE(7);
                            imp = false; left = 4;
                        }
                        kstep(IC<0>{}, -1);
                        if (ends()) { last_st = 0; break; }
                    }
                    if (is_o) {
                        if (w) {
                            wg_wait<0>();
                            release(last_st);
                            named_sync(6, 256);
                        }
#pragma unroll 1
                        for (int i = 1; i <= O_STAGGER; i++) {
                            const int st = (last_st + i) & 3;
                            if (i > 1 && st == 0) gph ^= 1;
                            wait_full(st);
                            const uint32_t a = dA + st * (G_STAGE >> 4), b = dB + st * (G_STAGE >> 4);
                            wg_fence();
                            wgmma_ss_n256<0, 0>(acc0, acc1, a, b);
                            wgmma_ss_n256<2, 128>(acc0, acc1, a, b);
                            wgmma_ss_n256<4, 256>(acc0, acc1, a, b);
                            wgmma_ss_n256<6, 384>(acc0, acc1, a, b);
                            wg_commit();
                            named_arrive_if(!w && i == O_STAGGER, 6, 256);
                            wg_wait<1>();
                            arrive_pair(gempty + last_st * 8, i == 1 && !w);
                        }
                        slot_wait(1);
                        wg_wait<0>();
                        fence_regs(acc0);
                        fence_regs(acc1);
                        auto put = [&](const float (&acc)[64], const int Q, int off) INL {
#pragma unroll
                            for (int j = 0; j < 4; j++) {
                                const float* o = acc + Q * 32 + j * 8;
                                stmatrix_x4(slot4[j] + off, pack_bf16(o[0], o[1]), pack_bf16(o[2], o[3]), pack_bf16(o[4], o[5]), pack_bf16(o[6], o[7]));
                            }
                        };
                        put(acc0, 0, 0);
                        signal(0);
                        put(acc0, 1, 8192);
                        signal(1);
                        put(acc1, 0, -OFF_STG - w * 8192);
                        put(acc1, 1, G_STAGE - OFF_STG - w * 8192);
                        __syncwarp();
                        warp_arrive(tfull + w * 8);
#pragma unroll
                        for (int i = 1; i <= O_STAGGER; i++) release((last_st + i) & 3);
                        GTRACE(w);
#pragma unroll
                        for (int i = 0; i < 64; i++) O[i] = 0.f;
                        break;
                    }
                    if (tid == 128 && !is_o) PTRACE(12);
                    ptrans = unit2;
                    if (tid == TRACE_TID && unit2) PTRACE(1);
                    named_arrive_if(w && job >= (T_A << 12), 1, TURN_THREADS);
                    wg_wait<0>();
                    fence_regs(acc0);
                    fence_regs(acc1);
                    release(3);
                    if (tid == TRACE_TID && unit2) PTRACE(2);
                    if (__builtin_expect(unit2, 0)) { unit_attend(acc0, cur); if (tid == TRACE_TID) PTRACE(3); }
                    else if (__builtin_expect((cur >> 6) == 2, 0)) pack_k(acc0);
                    else if (cur < 128) pack_half(acc0, 0, 1.f);
                    else pack_half(acc0, 0, K_SCALE);
                    if (job >= (T_A << 12)) {
                        stage_pair();
                        signal_both();
#pragma unroll
                        for (int i = 0; i < 64; i++) asm volatile("mov.b32 %0, %1;" : "=f"(O[i]) : "f"(acc1[i]));
                        break;
                    }
                    pack_half(acc1, 32, 1.f);
                    fence_regs(pk);
                    wait_full(0);
                    pend = (cur >> 6) != 2;
                }
        };
        setup_wait();
#pragma unroll 1
        while (true) {
        gemm_run();
        if (job < 0) break;
        if (tid == 128) PTRACE(11);
        GTRACE(w);
        {
            {
                sph ^= 1;
                uint32_t step = ~0u, ajob = ~0u;
                const int r0 = w * 64 + wwarp * 16 + (lane >> 2);
                float S[64];
                uint32_t P[32] = {};
                fence_regs(P);
                float m0 = 0.f, m1 = 0.f, l0 = 0.25f, l1 = 0.25f, g0 = 1.f, g1 = 1.f, e0 = 0.f, e1 = 0.f;
                constexpr float SUM_MAX = 1.1529215e18f;
                float sum_max = SUM_MAX;
                float sum_min = (lane & 3) == 0 ? 8.6736174e-19f : -1.f;
                asm volatile("" : "+f"(sum_min));
                int rem = 0;
                int maskrem = 0;
                uint32_t starts = 1;
                auto issue_S = [&]() INL {
                    const uint32_t da = desc_lo(base + OFF_Q0 + w * 8192, 0) + (ajob & 1) * ((OFF_Q1 - OFF_Q0) >> 4);
                    const uint32_t db = desc_lo(base + OFF_K0, 0) + (step & 1) * ((OFF_K1 - OFF_K0) >> 4);
                    wg_fence();
                    wgmma_ss_n128_init<0, 0, 0>(S, da, db);
                    wgmma_ss_n128_tb0<2, 2>(S, da, db, 1);
                    wgmma_ss_n128_tb0<4, 4>(S, da, db, 1);
                    wgmma_ss_n128_tb0<6, 6>(S, da, db, 1);
                    wgmma_ss_n128_tb0<1024, 1024>(S, da, db, 1);
                    wgmma_ss_n128_tb0<1026, 1026>(S, da, db, 1);
                    wgmma_ss_n128_tb0<1028, 1028>(S, da, db, 1);
                    wgmma_ss_n128_tb0<1030, 1030>(S, da, db, 1);
                    wg_commit();
                };
                auto issue_PV = [&](uint32_t t, int pass) INL {
                    const uint32_t db = desc_lo(base + OFF_V0, 16384) + (t & 1) * ((OFF_V1 - OFF_V0) >> 4);
                    mbar_wait_hot(vfull + (t & 1) * 8, (t >> 1) & 1);
                    wg_fence();
                    wgmma_rs_n128_tb1<0>(O, P[0], P[1], P[2], P[3], db, !(starts & 2));
                    wgmma_rs_n128_tb1<128>(O, P[4], P[5], P[6], P[7], db, 1);
                    wgmma_rs_n128_tb1<256>(O, P[8], P[9], P[10], P[11], db, 1);
                    wgmma_rs_n128_tb1<384>(O, P[12], P[13], P[14], P[15], db, 1);
                    if (pass) named_arrive(pass, TURN_THREADS);
                    wgmma_rs_n128_tb1<512>(O, P[16], P[17], P[18], P[19], db, 1);
                    wgmma_rs_n128_tb1<640>(O, P[20], P[21], P[22], P[23], db, 1);
                    wgmma_rs_n128_tb1<768>(O, P[24], P[25], P[26], P[27], db, 1);
                    wgmma_rs_n128_tb1<896>(O, P[28], P[29], P[30], P[31], db, 1);
                    wg_commit();
                };
                auto pv_done = [&](uint32_t t) INL {
                    wg_wait<0>();
                    fence_regs(O);
                    arrive_pair(vempty + (t & 1) * 8, t != ~0u);
                };
                auto row_max = [&](float& a0, float& a1) INL {
                    a0 = fmaxf(S[0], S[1]); a1 = fmaxf(S[2], S[3]);
#pragma unroll
                    for (int j = 1; j < 16; j++) {
                        a0 = fmaxf(a0, fmaxf(S[j * 4], S[j * 4 + 1]));
                        a1 = fmaxf(a1, fmaxf(S[j * 4 + 2], S[j * 4 + 3]));
                    }
                    a0 = fmaxf(a0, __shfl_xor_sync(0xffffffffu, a0, 1));
                    a1 = fmaxf(a1, __shfl_xor_sync(0xffffffffu, a1, 1));
                    a0 = fmaxf(a0, __shfl_xor_sync(0xffffffffu, a0, 2));
                    a1 = fmaxf(a1, __shfl_xor_sync(0xffffffffu, a1, 2));
                };
                auto mask_diag = [&]() INL {
                    const int d = (r0 & 63) - (lane & 3) * 2;
                    auto mask_block = [&](const int J0) INL {
                        bool up0 = false, up1 = false;
#pragma unroll
                        for (int j = 0; j < 8; j++) {
                            const bool c0 = j * 8 > d, c1 = j * 8 + 1 > d;
                            if (c0) S[(J0 + j) * 4] = -INFINITY;
                            if (c1) S[(J0 + j) * 4 + 1] = -INFINITY;
                            if (up0) S[(J0 + j) * 4 + 2] = -INFINITY;
                            if (up1) S[(J0 + j) * 4 + 3] = -INFINITY;
                            up0 = c0; up1 = c1;
                        }
                    };
                    if (w) {
                        mask_block(8);
                    } else {
                        mask_block(0);
#pragma unroll
                        for (int i = 32; i < 64; i++) S[i] = -INFINITY;
                    }
                };
                auto exp_part = [&](float& t0, float& t1, const int J0, const int J1, const bool SUB) INL {
#pragma unroll
                    for (int j = J0; j < J1; j++) {
                        const float e0 = ex2(SUB ? S[j * 4] - m0 : S[j * 4]), e1 = ex2(SUB ? S[j * 4 + 1] - m0 : S[j * 4 + 1]);
                        const float e2 = ex2(SUB ? S[j * 4 + 2] - m1 : S[j * 4 + 2]), e3 = ex2(SUB ? S[j * 4 + 3] - m1 : S[j * 4 + 3]);
                        t0 = (j ? t0 : l0) + (e0 + e1);
                        t1 = (j ? t1 : l1) + (e2 + e3);
                        P[j * 2] = pack_bf16(e0, e1);
                        P[j * 2 + 1] = pack_bf16(e2, e3);
                    }
                };
                auto exp_head = [&](float& t0, float& t1, auto j1_) INL {
                    constexpr int J1 = decltype(j1_)::v;
                    float E[J1 * 4];
#pragma unroll
                    for (int j = 0; j < J1; j++) {
#pragma unroll
                        for (int e = 0; e < 4; e++) E[j * 4 + e] = ex2(S[j * 4 + e]);
                        t0 = (j ? t0 : l0) + (E[j * 4] + E[j * 4 + 1]);
                        t1 = (j ? t1 : l1) + (E[j * 4 + 2] + E[j * 4 + 3]);
                    }
                    order_after(t0 + t1, bars + 508);
                    pv_done(step - 1);
                    fence_regs(P);
                    fence_regs(S);
                    fence_regs(E);
#pragma unroll
                    for (int i = 0; i < J1 * 2; i++) P[i] = pack_bf16(E[i * 2], E[i * 2 + 1]);
                };
                auto close_job = [&]() INL {
                    l0 += __shfl_xor_sync(0xffffffffu, l0, 1); l1 += __shfl_xor_sync(0xffffffffu, l1, 1);
                    l0 += __shfl_xor_sync(0xffffffffu, l0, 2); l1 += __shfl_xor_sync(0xffffffffu, l1, 2);
                    e0 = g0 * rcp(l0); e1 = g1 * rcp(l1);
                };
                auto put_O = [&]() INL {
                    mbar_wait_hot(sempty + (w * 2 + 1) * 8, sph ^ 1);
                    uint32_t a[4];
#pragma unroll
                    for (int j = 0; j < 4; j++) asm volatile("xor.b32 %0, %1, %2;" : "=r"(a[j]) : "r"(slot_a), "r"(j << 5));
                    const uint32_t h0 = pack_bf16(e0, e0), h1 = pack_bf16(e1, e1);
#pragma unroll
                    for (int q = 0; q < 8; q++) {
                        const float* o = O + q * 8;
                        stmatrix_x4(a[q & 3] + (q >> 2) * 8192, mul_bf16x2(pack_bf16(o[0], o[1]), h0), mul_bf16x2(pack_bf16(o[2], o[3]), h1),
                                    mul_bf16x2(pack_bf16(o[4], o[5]), h0), mul_bf16x2(pack_bf16(o[6], o[7]), h1));
                    }
                    sph ^= 1;
                    signal_both();
                };
                auto exp_plain = [&](float& t0, float& t1) INL {
                    exp_head(t0, t1, IC<6>{});
                    exp_part(t0, t1, 6, 16, false);
                    fence_regs(P);
                };
                auto exp_diag = [&](float& t0, float& t1) INL {
                    const int d = warp - 4, dd = (r0 & 7) - (int)(slot_a >> 6 & 6);
                    auto tri = [&](const int B) INL {
                        if (0 > dd) S[8 * B] = S[8 * B + 6] = -INFINITY;
                        if (1 > dd) S[8 * B + 1] = S[8 * B + 7] = -INFINITY;
                        S[8 * B + 4] = S[8 * B + 5] = -INFINITY;
                        asm volatile("" ::: "memory");
                    };
                    auto blocks = [&](const int B) INL {
                        auto zero = [&](const int B0) INL {
#pragma unroll
                            for (int i = 4 * B0; i < 4 * B + 12; i++) P[i] = 0;
                            asm volatile("" ::: "memory");
                        };
                        auto block = [&](const int B0) INL { exp_part(t0, t1, 2 * B0, 2 * B0 + 2, false); asm volatile("" ::: "memory"); };
                        if (d < B) zero(B);
                        else {
                            block(B);
                            if (d < B + 1) zero(B + 1);
                            else {
                                block(B + 1);
                                if (d < B + 2) zero(B + 2); else block(B + 2);
                            }
                        }
                    };
                    if (d > 3) {
                        if (d < 6) { if (d == 4) tri(4); else tri(5); } else { if (d == 6) tri(6); else tri(7); }
                        exp_head(t0, t1, IC<5>{});
                        exp_part(t0, t1, 5, 10, false);
                        blocks(5);
                    } else {
                        if (d < 2) { if (d == 0) tri(0); else tri(1); } else { if (d == 2) tri(2); else tri(3); }
                        exp_head(t0, t1, IC<2>{});
#pragma unroll
                        for (int i = 16; i < 32; i++) P[i] = 0;
                        blocks(1);
                    }
                    fence_regs(P);
                };
                auto unsafe_tile = [&](float t0, float t1) INL -> bool {
                    const bool unsafe = !(t0 + t1 <= sum_max) | !(fminf(t0, t1) >= sum_min);
                    return __any_sync(0xffffffffu, unsafe);
                };
                auto redo_tile = [&](float& t0, float& t1, bool fresh) INL {
                    wg_wait<0>();
                    fence_regs(O);
                    if (rem == maskrem) mask_diag();
                    float a0, a1;
                    row_max(a0, a1);
                    if (!fresh) { a0 = fmaxf(a0, m0); a1 = fmaxf(a1, m1); }
                    const float c0 = fresh ? 1.f : ex2(m0 - a0), c1 = fresh ? 1.f : ex2(m1 - a1);
                    m0 = a0; m1 = a1; sum_max = -1.f;
                    l0 *= c0; l1 *= c1;
#pragma unroll
                    for (int j = 0; j < 16; j++) { O[j * 4] *= c0; O[j * 4 + 1] *= c0; O[j * 4 + 2] *= c1; O[j * 4 + 3] *= c1; }
                    exp_part(t0, t1, 0, 16, true);
                };
                auto finish = [&]() INL {
                    if (starts & 2) put_O();
                    named_sync(1 + w, TURN_THREADS);
                    TRACE_MARK(0, w, step + 1);
                    issue_PV(step, w == 0 ? 2 : 0);
                    close_job();
                    pv_done(step);
                    put_O();
                };
                int njob;
                auto open_job = [&]() INL {
                    ajob++; rem = (job & 15) + 1; maskrem = (job & 512) ? 0 : job & 15;
                    njob = jobs[jb + 1];
                };
                auto do_step = [&]() INL -> bool {
                    float t0, t1;
                    const bool fresh = starts & 1, pending = starts & 2;
                    rem--; step++;
                    named_sync(1 + w, TURN_THREADS);
                    TRACE_MARK(0, w, step);
                    issue_S();
                    uint32_t ob[18];
#pragma unroll
                    for (int i = 0; i < 18; i++) asm volatile("" : "=r"(ob[i]));
                    if (__builtin_expect(pending || fresh, 0)) {
                        if (pending) {
                            const uint32_t h0 = pack_bf16(e0, e0), h1 = pack_bf16(e1, e1);
                            mbar_wait_hot(sempty + (w * 2 + 1) * 8, sph ^ 1);
#pragma unroll
                            for (int q = 0; q < 4; q++) {
                                const float* o = O + q * 8;
                                uint32_t a;
                                asm volatile("xor.b32 %0, %1, %2;" : "=r"(a) : "r"(slot_a), "r"(q << 5));
                                stmatrix_x4(a, mul_bf16x2(pack_bf16(o[0], o[1]), h0), mul_bf16x2(pack_bf16(o[2], o[3]), h1),
                                            mul_bf16x2(pack_bf16(o[4], o[5]), h0), mul_bf16x2(pack_bf16(o[6], o[7]), h1));
                            }
#pragma unroll
                            for (int i = 0; i < 16; i++) ob[i] = pack_bf16(O[32 + 2 * i], O[33 + 2 * i]);
                            ob[16] = h0; ob[17] = h1;
                            fence_regs(ob);
                        }
                        if (fresh) {
                            close_job();
                            g0 = __ldcg(g_gate + (job & 15) * 128 + r0); g1 = __ldcg(g_gate + (job & 15) * 128 + r0 + 8);
                            l0 = 0.f; l1 = 0.f; m0 = 0.f; m1 = 0.f; sum_max = SUM_MAX;
                            if (step == 0) {
                                wg_fence();
                                wg_commit();
                                named_arrive(2 - w, TURN_THREADS);
                                goto issued;
                            }
                        }
                    }
                    issue_PV(step - 1, 2 - w);
                    if (__builtin_expect(pending, 0)) {
#pragma unroll
                        for (int q = 0; q < 4; q++) {
                            uint32_t a;
                            asm volatile("xor.b32 %0, %1, %2;" : "=r"(a) : "r"(slot_a), "r"(q << 5));
                            stmatrix_x4(a + 8192, mul_bf16x2(ob[q * 4], ob[16]), mul_bf16x2(ob[q * 4 + 1], ob[17]),
                                        mul_bf16x2(ob[q * 4 + 2], ob[16]), mul_bf16x2(ob[q * 4 + 3], ob[17]));
                        }
                        sph ^= 1;
                        signal_both();
                    }
                issued:
                    starts = (starts << 1 & 2) | (rem == 0);
                    TRACE_MARK(1, w, step);
                    wg_wait<1>();
                    fence_regs(S);
                    arrive_pair(kempty + (step & 1) * 8);
                    TRACE_MARK(2, w, step);
                    warp_arrive(qempty + (ajob & 1) * 8, rem == 0);
                    bool bad;
                    if (__builtin_expect(rem != maskrem, 1)) {
                        exp_plain(t0, t1);
                        bad = unsafe_tile(t0, t1);
                        if (__builtin_expect(!bad && rem != 0, 1)) {
                            l0 = t0; l1 = t1;
                            TRACE_MARK(3, w, step);
                            return true;
                        }
                    } else {
                        exp_diag(t0, t1);
                        bad = unsafe_tile(t0, t1);
                    }
                    if (bad) redo_tile(t0, t1, fresh);
                    l0 = t0; l1 = t1;
                    TRACE_MARK(3, w, step);
                    if (rem == 0) {
                        jb++;
                        job = uniform(njob);
                        if ((job >> 12) != T_A) return false;
                        open_job();
                    }
                    return true;
                };
                open_job();
#pragma unroll 1
                while (do_step()) {}
                finish();
            }
        }
        GTRACE(w);
        jb = uniform(jb); job = uniform(job); sph = uniform(sph); gph = uniform(gph);
        if (job < 0) break;
        }
    } else {
        reg_dec<40>();
        if (base & 1023) __trap();
        if (warp == 0) {
            const uint2 r = p.first[blockIdx.x];
            const char* maps = reinterpret_cast<const char*>(&p.amap[0]);
            const CUtensorMap* wm = reinterpret_cast<const CUtensorMap*>(maps + (r.x >> (rank ? 8 : 4) & 0x780));
            const CUtensorMap* am = reinterpret_cast<const CUtensorMap*>(maps + (r.x & 0x780));
            const int wb = rank ? r.y >> 16 : r.y & 0xffff;
            setup_wait();
#pragma unroll 1
            for (int st = 1; st < 4; st++) {
                const uint32_t sa = base + st * G_STAGE;
                load_kstep(sa, sa + 16384 + rank * 16384, gfull + st * 8, G_STAGE, wm, st, wb, am, r.x >> 20, st, 1 + (r.x & 1));
            }
            named_sync(7, 96);
        } else {
            if (warp == 2) {
                const int jl = lane < MAX_JOBS ? p.jobs[blockIdx.x][lane] : -1;
                if (lane <= MAX_JOBS) jobs[lane] = jl;
                if ((jl >> 12) == T_O) *reinterpret_cast<volatile uint32_t*>(smem_raw + OFF_BAR + 504) = 2 * o_head(jl);
                if (lane == 31) *reinterpret_cast<volatile uint32_t*>(smem_raw + OFF_BAR + 528) = 0;
            } else if (warp == 3) {
                if (lane == 31) *reinterpret_cast<ulonglong2*>(smem_raw + OFF_BAR + 512) = make_ulonglong2((uint64_t)g_halo, (uint64_t)g_gate);
                if (lane < MAX_ROUNDS / 2) rounds[lane] = reinterpret_cast<const uint32_t*>(p.rounds[blockIdx.x >> 1])[lane];
            }
            named_arrive_if(warp > 1, 7, 96);
            named_sync(0, 352);
            setup_wait();
        }
        volatile uint32_t* epoch_word = reinterpret_cast<volatile uint32_t*>(smem_raw + OFF_BAR + 532);
        uint32_t epoch1 = 0;
        if (warp > 0) {
        if (warp == 3) { epoch1 = uniform(ld_acquire(g_flags + F_DONE)) / NUM_SMS + 1; if (lane == 0) *epoch_word = epoch1; }
        {
            if (warp == 1 && elect_one()) {
#pragma unroll
                for (int i = 0; i < 7; i++) prefetch_map(&p.amap[0] + i);
            }
            __syncwarp();
            if (warp < 3) __nanosleep(jobs[0] < 256 ? GATE_DELAY_LONG_NS : GATE_DELAY_SHORT_NS);
            if (tid == TRACE_GATE) PTRACE(10);
            float* gate_vals = reinterpret_cast<float*>(smem_raw + OFF_BAR + 576);
            if (warp == 3) {
                if (blockIdx.x == 0) g_flags[F_SPLIT + lane] = g_flags[F_TICKET + lane] = 0;
                named_sync(5, 96);
                if (lane < 16 && blockIdx.x + lane * NUM_SMS < SEQ) g_gate[blockIdx.x + lane * NUM_SMS] = 1.f / (1.f + __expf(-gate_vals[lane]));
                if (tid == TRACE_GATE) PTRACE(9);
                __threadfence();
                __syncwarp();
                if (lane == 0) red_release(g_flags + F_GATE);
            } else {
                const uint32_t bar = gatefull + (warp - 1) * 16;
                auto fetch = [&](int r) INL {
                    if (lane == 0) mbar_expect_tx(bar + (r & 2) * 4, 4096);
                    __syncwarp();
                    if (lane < 2) asm volatile("cp.async.bulk.shared::cluster.global.mbarrier::complete_tx::bytes [%0], [%1], 2048, [%2];"
                                               ::"r"(stg + ((warp - 1) * 8 + r + lane) * 2048), "l"(p.xp + (size_t)min((int)blockIdx.x + ((warp - 1) * 8 + r + lane) * NUM_SMS, SEQ - 1) * DM), "r"(bar + (r & 2) * 4) : "memory");
                };
                fetch(0); fetch(2);
                uint32_t gw[16];
#pragma unroll
                for (int i = 0; i < 4; i++) {
                    const uint4 t = __ldg(reinterpret_cast<const uint4*>(p.gate_w) + i * 32 + lane);
                    gw[i * 4] = t.x; gw[i * 4 + 1] = t.y; gw[i * 4 + 2] = t.z; gw[i * 4 + 3] = t.w;
                }
#pragma unroll 1
                for (int r = 0; r < 8; r += 2) {
                    mbar_wait(bar + (r & 2) * 4, r >> 2);
                    if (r < 4) fetch(r + 4);
                    fence_regs(gw);
                    float acc0 = 0.f, acc1 = 0.f;
                    uint32_t ln;
                    asm volatile("mov.u32 %0, %%laneid;" : "=r"(ln));
#pragma unroll
                    for (int i = 0; i < 4; i++) {
                        const uint4* xr = reinterpret_cast<const uint4*>(smem_raw + OFF_STG + ((warp - 1) * 8 + r) * 2048) + i * 32 + ln;
                        const uint4 a = xr[0], c = xr[128];
                        const uint32_t av[4] = {a.x, a.y, a.z, a.w}, cv[4] = {c.x, c.y, c.z, c.w};
#pragma unroll
                        for (int e = 0; e < 4; e++) {
                            const float lo = __uint_as_float(gw[i * 4 + e] << 16), hi = __uint_as_float(gw[i * 4 + e] & 0xffff0000u);
                            acc0 = fmaf(__uint_as_float(av[e] << 16), lo, acc0);
                            acc1 = fmaf(__uint_as_float(cv[e] << 16), lo, acc1);
                            acc0 = fmaf(__uint_as_float(av[e] & 0xffff0000u), hi, acc0);
                            acc1 = fmaf(__uint_as_float(cv[e] & 0xffff0000u), hi, acc1);
                        }
                    }
                    float t = (lane < 16 ? acc0 : acc1) + __shfl_xor_sync(0xffffffffu, lane < 16 ? acc1 : acc0, 16);
#pragma unroll
                    for (int o = 8; o > 0; o >>= 1) t += __shfl_xor_sync(0xffffffffu, t, o);
                    if ((lane & 15) == 0) gate_vals[(warp - 1) * 8 + r + (lane >> 4)] = t;
                }
                uint32_t t2;
                asm volatile("mov.u32 %0, %%tid.x;" : "=r"(t2));
                warp_arrive2(sempty - 16 + (t2 >> 5) * 16, sempty - 8 + (t2 >> 5) * 16);
                named_arrive(5, 96);
                if (tid == TRACE_GATE) PTRACE(9);
            }
            if (tid == TRACE_GATE) PTRACE(8);
        }
        if (warp < 3) {
            if (elect_one()) {
                const int w = warp - 1;
                uint32_t qn = 0, un = 0;
                prefetch_map(&p.qkv_st); prefetch_map(&p.st_par);
                for (int jb = 0; jb < MAX_JOBS; jb++) {
                    const int job = jobs[jb];
                    if (job < 0) break;
                    const int type = job >> 12, pl = type == T_O ? o_state(otile, 0) >> 1 : job & 0xFFF;
                    const CUtensorMap* map = &p.qkv_st;
                    int nq = 4, mt, ob0, ob1, flag, flag2 = -1;
                    bool par = false;
                    if (type <= T_O) {
                        const int n = pl >> 3;
                        mt = (pl & 7) * 2 + rank;
                        if (type == T_O)  {
                            map = &p.out_st; ob0 = (n & 3) * 4; ob1 = ob0 + 2; flag = -1;
                            for (uint32_t tries = 0; (int32_t)(ld_acquire(g_flags + F_OUT + pl * 2 + rank) - *epoch_word) < 0; tries++) {
                                __nanosleep(300);
                                if (tries > (1u << 22)) __trap();
                            }
                            fence_async_global();
                        }
                        else if (n < 16)  { ob0 = n * 4; ob1 = ob0 + 2; flag = F_Q + n * 32 + mt; flag2 = flag + 16; }
                        else if (n < 24)  {
                            mbar_wait(hout + w * 8, un++ & 1);
                            nq = ob0 = ob1 = 0; flag = F_H + mt * 8 + (n & 7);
                        } else if (n < 32) {
                            par = true; ob0 = 192 + (n & 7) * 2; ob1 = unit_head(n & 7) * 2;
                            flag = F_CTX + mt * 40 + 32 + (n & 7); flag2 = F_Q + ob1 * 8 + mt;
                        } else            { ob0 = n * 2; ob1 = ob0 + 64; flag = F_KV + (n - 32) * 16 + mt; }
                    } else {
                        nq = 2; mt = pl & 15; ob0 = ob1 = ((pl >> 4) & 31) * 2; flag = F_CTX + mt * 40 + ((pl >> 4) & 31);
                    }
                    for (int q = 0; q < nq; q++, qn++) {
                        const uint32_t slot = w * 2 + (qn & 1);
                        const int blk = (q < 2 ? ob0 : ob1) + (q & 1);
                        if (type == T_O && q == 2) {
                            mbar_wait(tfull + w * 8, 0);
                            fence_async_smem();
                            tma_reduce_add_3d(map, base + w * 8192, 0, mt * 128 + w * 64, ob1);
                            tma_reduce_add_3d(map, base + G_STAGE + w * 8192, 0, mt * 128 + w * 64, ob1 + 1);
                            bulk_commit();
                            break;
                        }
                        mbar_wait(sfull + slot * 8, (qn >> 1) & 1);
                        fence_async_smem();
                        if (type == T_O) {
                            tma_reduce_add_3d(map, stg + slot * 8192, 0, mt * 128 + w * 64, blk);
                        } else if (par) {
                            tma_store_par(&p.st_par, stg + slot * 8192, mt * 64, w, blk);
                        } else {
                            tma_store_3d(map, stg + slot * 8192, 0, mt * 128 + w * 64, blk, POL_STREAM);
                        }
                        bulk_commit();
                        if (type == T_O) continue;
                        if (!(q & 1)) continue;
                        bulk_wait_read<1>();
                        mbar_arrive(sempty + (slot ^ 1) * 8);
                        bulk_wait_read<0>();
                        mbar_arrive(sempty + slot * 8);
                    }
                    bulk_wait<0>();
                    END_MARK(jb);
                    if (flag >= 0) {
                        asm volatile("fence.release.gpu;" ::: "memory");
                        red_relaxed(g_flags + flag);
                        if (flag2 >= 0) red_relaxed(g_flags + flag2);
                    }
                }
            }
        } else {
            int jb = 0;
            for (int un = 0; (jobs[jb] >> 12) == T_P; jb++) {
                const int n = jobs[jb] >> 3, mt = (jobs[jb] & 7) * 2 + rank;
                if ((n >> 3) != 3) continue;
                wait_flags<200>(lane == 31 || (lane == 0 && mt > 0), lane == 31 ? F_GATE : F_H + max(mt - 1, 0) * 8 + (n & 7),
                                epoch1 * (lane == 31 ? GATE_COUNT : 2));
                if (lane == 0) mbar_arrive(lready + un * 8);
                un++;
            }
            if ((jobs[jb] >> 12) != T_A) {
                wait_flags<200>(lane == 0, F_GATE, epoch1 * GATE_COUNT);
                if (lane == 0) { mbar_arrive(aready); red_relaxed(g_flags + F_DONE); }
            } else {
                const int jh = jobs[jb] >> 4 & 31, jq = jobs[jb] & 15;
                wait_flags<100>(lane <= jq || lane >= 30, lane == 31 ? F_GATE : (lane == 30 ? F_Q + jh * 16 + jq : F_KV + jh * 16 + (lane & 15)),
                                epoch1 * (lane == 31 ? GATE_COUNT : 2));
                if (lane == 0) { mbar_arrive(aready); red_relaxed(g_flags + F_DONE); }
            int left = 0, nxt = jobs[jb];
            uint32_t ajob = 0;
#pragma unroll 1
            for (uint32_t astep = 0;; astep++) {
                if (left == 0) {
                    if ((nxt >> 12) != T_A) break;
                    left = (nxt & 15) + 1;
                    nxt = jobs[++jb];
                    mbar_wait(qfull + (ajob & 1) * 8, (ajob >> 1) & 1);
                    ajob++;
                }
                left--;
                mbar_wait(kfull + (astep & 1) * 8, (astep >> 1) & 1);
                named_sync(1, TURN_THREADS);
                named_sync(2, TURN_THREADS);
            }
            named_sync(1, TURN_THREADS);
            named_sync(2, TURN_THREADS);
            }
            if (jobs[jb] == (T_O << 12)) {
                mbar_wait(gatefull, 0);
                const int tile = o_state(otile, 0) >> 1;
                uint4* dst = reinterpret_cast<uint4*>(p.out) + ((tile & 7) * 256 + rank * 128) * (DM / 8) + (tile >> 3) * 32 + lane;
#pragma unroll 4
                for (int r = 0; r < 128; r++) {
                    dst[r * (DM / 8)] = make_uint4(0, 0, 0, 0);
                    if ((r & 3) == 3) __nanosleep(CLEAR_GAP_NS);
                }
                __threadfence();
                fence_async_global();
                __syncwarp();
                if (lane == 0) red_release(g_flags + F_OUT + tile * 2 + rank);
            }
        }
        } else {
            uint32_t gph = 1;
            int vrow = 0, vblk = 0;
            bool vsolo = false;
            auto load_kv = [&](uint32_t dst, uint32_t bar, int row, int blk, bool solo) INL {
                load_operand(dst, bar, &p.qkv_ld, &p.qkv_half, row, blk, rank, solo, POL_NORMAL);
            };
            auto load_v = [&](uint32_t t) INL {
                if (t == 0) mbar_wait(gempty + 24, gph);
                mbar_wait(vempty + (t & 1) * 8, ((t >> 1) & 1) ^ 1);
                load_kv(base + ((t & 1) ? OFF_V1 : OFF_V0), vfull + (t & 1) * 8, vrow, vblk, vsolo);
            };
            int jb = __ffs(__ballot_sync(0xffffffffu, lane <= MAX_JOBS && (jobs[min(lane, MAX_JOBS)] >> 12) != T_P)) - 1;
            int cur = uniform(jobs[jb]);
            auto announce = [&](uint32_t word, uint32_t v) INL {
                asm volatile("{\n.reg .pred p;\nsetp.lt.u32 p, %2, 2;\n@p red.relaxed.cluster.shared::cluster.max.u32 [%0], %1;\n}"
                             ::"r"(mapa(word, lane & 1)), "r"(v), "r"(lane) : "memory");
                __syncwarp();
            };
            uint32_t ticket = 0;
            auto draw_ticket = [&](int ojob) INL {
                asm volatile("{\n.reg .pred p;\nsetp.ne.u32 p, %2, 0;\n@p atom.relaxed.gpu.global.inc.u32 %0, [%1], 0x7fffffff;\n}"
                             : "+r"(ticket) : "l"(g_flags + F_TICKET + (ojob >> 5 & 1)), "r"((uint32_t)(rank == 0 && lane == 0)) : "memory");
                __syncwarp();
            };
            int pl = 0;
            uint32_t seen_a = 0, seen_b = 0;
            auto ask_ctx = [&]() INL {
                const uint32_t* f = g_flags + F_CTX + ((pl & 7) * 2 + rank) * 40;
                seen_a = ld_relaxed(f + lane); seen_b = ld_relaxed(f + 32 + (lane & 7));
            };
            auto open_tile = [&](int ojob) INL {
                if (rank == 0) {
                    const uint32_t t = uniform(ticket);
                    announce(otile, 2 * ((ojob & 32) ? 31 - t : t) + 1);
                }
                pl = (ojob & 32) | uniform(o_state(otile, 0) >> 1);
                ask_ctx();
            };
            const uint16_t* recs = reinterpret_cast<const uint16_t*>(rounds);
            uint32_t rec = uniform(recs[0]), nrec = uniform(recs[1]);
            int st0 = 4;
#pragma unroll 1
            for (int r = 2; rec != 0xFFFF; r++) {
                const uint32_t nnrec = recs[r];
                load_round(rec, st0, gph);
                gph ^= 1;
                st0 = 0;
                rec = nrec; nrec = uniform(nnrec);
                if (nrec == 0xFFFF || (rec & 8192)) {
                    if (nrec != 0xFFFF) {
                        prefetch_map(&p.qkv_ld); prefetch_map(&p.qkv_half);
                        if ((cur >> 12) == T_O) { prefetch_map(&p.wo_a); prefetch_map(&p.wo_b); prefetch_map(&p.out_st); }
                    } else if ((cur >> 12) == T_O) {
                        if (rec != 0xFFFF) {
                            mbar_wait(aready, 0);
                            draw_ticket(cur);
                        } else {
                            open_tile(cur);
                        }
                    }
                }
            }
            int nxt = cur;
            uint32_t astep = 0;
            if ((cur >> 12) == T_A) {
            {
                const int jh = cur >> 4 & 31, jq = cur & 15, j0 = (cur & 512) ? 0 : jq;
                mbar_wait(aready, 0);
                fence_async_global();
                mbar_wait(gempty, gph);
                load_operand(base + OFF_Q0, qfull, &p.qkv_ld, &p.qkv_ld, jq * 128, jh * 2, 0, true, POL_STREAM);
                PTRACE(17);
                mbar_wait(gempty + 8, gph);
                load_kv(base + OFF_K0, kfull, j0 * 128, 64 + jh * 2, j0 == jq && (jq & 1));
                PTRACE(16);
            }
            epoch1 = *epoch_word;
            jb++;
            nxt = uniform(jobs[jb]);
            int i = 0;
            uint32_t ajob = 1;
            bool q_issued = false;
#pragma unroll 1
            while (true) {
                const int qt = cur & 15;
                const bool last = i == qt;
                const int j = (cur & 512) ? i : qt - i, blk = (cur >> 4 & 31) * 2;
                const bool solo = j == qt && (qt & 1);
                {
                    const uint32_t sl = astep & 1;
                    if (astep == 0) {
                        mbar_wait(gempty + 16, gph);
                    } else {
                        mbar_wait(kempty + sl * 8, ((astep >> 1) & 1) ^ 1);
                        load_kv(base + (sl ? OFF_K1 : OFF_K0), kfull + sl * 8, j * 128, 64 + blk, solo);
                        if (astep == 1) PTRACE(14);
                        load_v(astep - 1);
                        if (astep == 1) PTRACE(15);
                    }
                }
                vrow = j * 128; vblk = 128 + blk; vsolo = solo;
                astep++;
                if ((nxt >> 12) != T_A) {
                    if (last) break;
                } else if (!q_issued && (last || i == 2 || (i > 2 && i >= qt - 2))) {
                    const int jh = nxt >> 4 & 31, jq = nxt & 15;
                    q_issued = wait_flags(lane <= jq || lane >= 30, lane == 31 ? F_GATE : (lane == 30 ? F_Q + jh * 16 + jq : F_KV + jh * 16 + (lane & 15)),
                                          epoch1 * (lane == 31 ? GATE_COUNT : 2), last);
                    if (q_issued) {
                        mbar_wait(qempty + (ajob & 1) * 8, ((ajob >> 1) & 1) ^ 1);
                        load_operand(base + ((ajob & 1) ? OFF_Q1 : OFF_Q0), qfull + (ajob & 1) * 8, &p.qkv_ld, &p.qkv_ld, jq * 128, jh * 2, 0, true, POL_STREAM);
                    }
                }
                i++;
                if (last) {
                    cur = nxt; jb++; nxt = uniform(jobs[jb]); i = 0; ajob++; q_issued = false;
                    if ((nxt >> 12) == T_O) { prefetch_map(&p.wo_a); prefetch_map(&p.wo_b); prefetch_map(&p.out_st); }
                }
            }
            if (nxt >= 0) draw_ticket(nxt);
            load_v(astep - 1);
            if (nxt >= 0) open_tile(nxt);
            }
            int nks = 0;
            if (nxt >= 0) {
                epoch1 = *epoch_word;
                const int m0 = (pl & 7) * 256 + rank * 128, nb = (pl >> 3 & 3) * 4 + rank * 2, part = pl >> 5 & 1;
                uint32_t ready_a = 0, ready_b = 0;
                uint32_t claim_even = 0, claim_odd = 0;
                const int head = o_head(pl), tail = o_tail(pl);
                int lim = head;
                bool known = false;
#pragma unroll 1
                for (int ks = 0;; ks++) {
                    const int st = ks & 3;
                    if (rank == 0) {
                        auto exchange = [&](uint32_t& claim) INL {
                            if (ks + 1 >= head) {
                                known = (uint32_t)uniform(claim) >= O_FLEX;
                                if (!known) lim = ks + 2;
                                announce(olim, known ? 2 * (lim + tail) + 1 : 2 * lim);
                            }
                            asm volatile("{\n.reg .pred p;\nsetp.ne.u32 p, %2, 0;\n@p atom.relaxed.gpu.global.inc.u32 %0, [%1], 0x7fffffff;\n}"
                                         : "+r"(claim) : "l"(g_flags + F_SPLIT + (pl & 31)), "r"((uint32_t)(!known && lane == 0)) : "memory");
                            __syncwarp();
                        };
                        if (!known && ks + 3 >= head) { if (ks & 1) exchange(claim_odd); else exchange(claim_even); }
                    } else if (!known && ks >= lim) {
                        const uint32_t v = uniform(o_state(olim, ks));
                        known = v & 1;
                        lim = (v >> 1) - (known ? tail : 0);
                    }
                    if (ks >= lim + tail) { nks = ks; break; }
                    if (ks == CLEAR_KS && !part) warp_arrive(gatefull);
                    int acol;
                    if (ks >= lim) acol = (part ? 64 - O_T1 : 200) + ks - lim;
                    else if (part) acol = ks < O_H1 ? O_F0 + ks : O_F0 + 2 * O_H1 + O_FLEX - 1 - ks;
                    else acol = ks < 8 ? 192 + ks : (ks < O_H0 ? ks - 8 : ks - 8 + O_H1);
                    for (uint32_t tries = 0; !(((acol < 192 ? ready_a : ready_b) >> (acol >> 1 & 31)) & 1); tries++) {
                        if (ks | tries) ask_ctx();
                        ready_a = __ballot_sync(0xffffffffu, (int32_t)(seen_a - epoch1 * 2) >= 0);
                        ready_b = __ballot_sync(0xffffffffu, (int32_t)(seen_b - epoch1 * 2) >= 0);
                        fence_acquire();
                        trap_if(tries > (1u << 22));
                    }
                    {
                        const uint32_t sa = base + st * G_STAGE;
                        if (ks < 4 && astep) mbar_wait((ks < 2 ? kempty : vempty) + ((astep - 1) & 1) * 8, ((astep - 1) >> 1) & 1);
                        else mbar_wait(gempty + st * 8, gph);
                        load_kstep(sa, sa + 16384 + rank * 16384, gfull + st * 8, G_STAGE, acol >= 192 ? &p.wo_b : &p.wo_a, acol & 63, nb,
                                   &p.qkv_half, m0, acol, 1);
                    }
                    if (st == 3) gph ^= 1;
                }
            }
            if (lane == 0) {
                if (nxt >= 0) for (int s = 0; s < 4; s++) mbar_wait(gempty + s * 8, gph ^ (s < (nks & 3)));
                else for (uint32_t t = astep; t < astep + 2; t++) {
                    mbar_wait(kempty + (t & 1) * 8, ((t >> 1) & 1) ^ 1);
                    mbar_wait(vempty + (t & 1) * 8, ((t >> 1) & 1) ^ 1);
                }
            }
        }
    }
}

typedef CUresult (*EncodeFn)(CUtensorMap*, CUtensorMapDataType, cuuint32_t, void*, const cuuint64_t*, const cuuint64_t*,
                             const cuuint32_t*, const cuuint32_t*, CUtensorMapInterleave, CUtensorMapSwizzle,
                             CUtensorMapL2promotion, CUtensorMapFloatOOBfill);

void make_map3(EncodeFn enc, CUtensorMap* m, const void* ptr, int rows, int cols, int box_rows, int box_blks, bool blocked = false) {
    cuuint64_t dims[3] = {64, (cuuint64_t)rows, (cuuint64_t)(cols / 64)};
    cuuint64_t strides[2] = {blocked ? 128 : (cuuint64_t)cols * 2, blocked ? (cuuint64_t)rows * 128 : 128};
    cuuint32_t box[3] = {64, (cuuint32_t)box_rows, (cuuint32_t)box_blks};
    cuuint32_t es[3] = {1, 1, 1};
    enc(m, CU_TENSOR_MAP_DATA_TYPE_BFLOAT16, 3, const_cast<void*>(ptr), dims, strides, box, es, CU_TENSOR_MAP_INTERLEAVE_NONE,
        CU_TENSOR_MAP_SWIZZLE_128B, CU_TENSOR_MAP_L2_PROMOTION_L2_256B, CU_TENSOR_MAP_FLOAT_OOB_FILL_NONE);
}

Params h_params;

const int16_t k_jobs[NUM_SMS][MAX_JOBS] = {
    {339,153,217,8890,8339,8802,8311,9042,8405,9008,8551,9134,8677,4128,-1,-1,-1,-1,-1,-1,-1,-1,-1,-1},
    {339,153,217,8891,8338,8803,8310,9043,8404,9009,8550,9135,8676,4128,-1,-1,-1,-1,-1,-1,-1,-1,-1,-1},
    {40,0,307,8888,8289,8720,8259,8854,8539,8898,8627,8998,8655,4128,-1,-1,-1,-1,-1,-1,-1,-1,-1,-1},
    {40,0,307,8889,8288,8721,8258,8855,8538,8899,8626,8999,8654,4128,-1,-1,-1,-1,-1,-1,-1,-1,-1,-1},
    {10,157,221,8706,8269,8820,8457,9006,8687,4128,-1,-1,-1,-1,-1,-1,-1,-1,-1,-1,-1,-1,-1,-1},
    {10,157,221,8707,8268,8821,8456,9007,8686,4128,-1,-1,-1,-1,-1,-1,-1,-1,-1,-1,-1,-1,-1,-1},
    {132,196,296,8730,8333,8940,8503,9082,8697,4128,-1,-1,-1,-1,-1,-1,-1,-1,-1,-1,-1,-1,-1,-1},
    {132,196,296,8731,8332,8941,8502,9083,8696,4128,-1,-1,-1,-1,-1,-1,-1,-1,-1,-1,-1,-1,-1,-1},
    {128,192,8758,8199,8774,8313,9026,8415,9130,8663,4128,-1,-1,-1,-1,-1,-1,-1,-1,-1,-1,-1,-1,-1},
    {128,192,8759,8198,8775,8312,9027,8414,9131,8662,4128,-1,-1,-1,-1,-1,-1,-1,-1,-1,-1,-1,-1,-1},
    {133,197,8742,8369,8704,8285,8768,8543,9022,8601,4128,-1,-1,-1,-1,-1,-1,-1,-1,-1,-1,-1,-1,-1},
    {133,197,8743,8368,8705,8284,8769,8542,9023,8600,4128,-1,-1,-1,-1,-1,-1,-1,-1,-1,-1,-1,-1,-1},
    {131,195,38,8708,8265,8932,8461,8896,8631,9076,8585,4128,-1,-1,-1,-1,-1,-1,-1,-1,-1,-1,-1,-1},
    {131,195,38,8709,8264,8933,8460,8897,8630,9077,8584,4128,-1,-1,-1,-1,-1,-1,-1,-1,-1,-1,-1,-1},
    {137,201,8750,8331,8816,8533,8912,8411,9078,8671,4128,-1,-1,-1,-1,-1,-1,-1,-1,-1,-1,-1,-1,-1},
    {137,201,8751,8330,8817,8532,8913,8410,9079,8670,4128,-1,-1,-1,-1,-1,-1,-1,-1,-1,-1,-1,-1,-1},
    {43,264,440,8744,8201,8858,8417,8954,8483,9016,8649,9152,8691,4128,-1,-1,-1,-1,-1,-1,-1,-1,-1,-1},
    {43,264,440,8745,8200,8859,8416,8955,8482,9017,8648,9153,8690,4128,-1,-1,-1,-1,-1,-1,-1,-1,-1,-1},
    {151,215,8876,8299,8964,8445,9146,8703,4128,-1,-1,-1,-1,-1,-1,-1,-1,-1,-1,-1,-1,-1,-1,-1},
    {151,215,8877,8298,8965,8444,9147,8702,4128,-1,-1,-1,-1,-1,-1,-1,-1,-1,-1,-1,-1,-1,-1,-1},
    {470,5,159,223,8772,8281,8936,8407,9066,8651,4128,-1,-1,-1,-1,-1,-1,-1,-1,-1,-1,-1,-1,-1},
    {470,5,159,223,8773,8280,8937,8406,9067,8650,4128,-1,-1,-1,-1,-1,-1,-1,-1,-1,-1,-1,-1,-1},
    {136,200,444,8760,8275,8848,8477,9040,8525,9148,8681,4128,-1,-1,-1,-1,-1,-1,-1,-1,-1,-1,-1,-1},
    {136,200,444,8761,8274,8849,8476,9041,8524,9149,8680,4128,-1,-1,-1,-1,-1,-1,-1,-1,-1,-1,-1,-1},
    {46,510,462,310,8764,8293,8862,8439,9064,8653,4128,-1,-1,-1,-1,-1,-1,-1,-1,-1,-1,-1,-1,-1},
    {46,510,462,310,8765,8292,8863,8438,9065,8652,4128,-1,-1,-1,-1,-1,-1,-1,-1,-1,-1,-1,-1,-1},
    {145,209,8894,8335,8942,8485,9098,8695,4128,-1,-1,-1,-1,-1,-1,-1,-1,-1,-1,-1,-1,-1,-1,-1},
    {145,209,8895,8334,8943,8484,9099,8694,4128,-1,-1,-1,-1,-1,-1,-1,-1,-1,-1,-1,-1,-1,-1,-1},
    {140,204,8878,8329,8934,8441,9070,8685,4128,-1,-1,-1,-1,-1,-1,-1,-1,-1,-1,-1,-1,-1,-1,-1},
    {140,204,8879,8328,8935,8440,9071,8684,4128,-1,-1,-1,-1,-1,-1,-1,-1,-1,-1,-1,-1,-1,-1,-1},
    {146,210,504,8884,8301,8966,8527,9128,8603,4128,-1,-1,-1,-1,-1,-1,-1,-1,-1,-1,-1,-1,-1,-1},
    {146,210,504,8885,8300,8967,8526,9129,8602,4128,-1,-1,-1,-1,-1,-1,-1,-1,-1,-1,-1,-1,-1,-1},
    {14,6,8868,8245,8806,8267,8938,8547,9000,8611,9108,8643,4128,-1,-1,-1,-1,-1,-1,-1,-1,-1,-1,-1},
    {14,6,8869,8244,8807,8266,8939,8546,9001,8610,9109,8642,4128,-1,-1,-1,-1,-1,-1,-1,-1,-1,-1,-1},
    {144,208,8748,8211,8836,8463,9004,8591,4128,-1,-1,-1,-1,-1,-1,-1,-1,-1,-1,-1,-1,-1,-1,-1},
    {144,208,8749,8210,8837,8462,9005,8590,4128,-1,-1,-1,-1,-1,-1,-1,-1,-1,-1,-1,-1,-1,-1,-1},
    {12,4,8740,8243,8724,8287,8930,8435,8900,8517,9086,8659,4128,-1,-1,-1,-1,-1,-1,-1,-1,-1,-1,-1},
    {12,4,8741,8242,8725,8286,8931,8434,8901,8516,9087,8658,4128,-1,-1,-1,-1,-1,-1,-1,-1,-1,-1,-1},
    {143,207,8866,8353,8752,8205,8830,8409,9056,8561,9140,8581,9104,8679,4128,-1,-1,-1,-1,-1,-1,-1,-1,-1},
    {143,207,8867,8352,8753,8204,8831,8408,9057,8560,9141,8580,9105,8678,4128,-1,-1,-1,-1,-1,-1,-1,-1,-1},
    {147,211,8872,8297,8834,8459,9030,8437,9100,8665,4128,-1,-1,-1,-1,-1,-1,-1,-1,-1,-1,-1,-1,-1},
    {147,211,8873,8296,8835,8458,9031,8436,9101,8664,4128,-1,-1,-1,-1,-1,-1,-1,-1,-1,-1,-1,-1,-1},
    {41,1,8766,8327,8828,8399,9126,8667,4128,-1,-1,-1,-1,-1,-1,-1,-1,-1,-1,-1,-1,-1,-1,-1},
    {41,1,8767,8326,8829,8398,9127,8666,4128,-1,-1,-1,-1,-1,-1,-1,-1,-1,-1,-1,-1,-1,-1,-1},
    {150,214,8882,8223,8832,8473,8980,8413,9094,8669,4128,-1,-1,-1,-1,-1,-1,-1,-1,-1,-1,-1,-1,-1},
    {150,214,8883,8222,8833,8472,8981,8412,9095,8668,4128,-1,-1,-1,-1,-1,-1,-1,-1,-1,-1,-1,-1,-1},
    {141,205,33,8726,8341,8976,8479,9024,8449,9136,8501,9144,8683,4128,-1,-1,-1,-1,-1,-1,-1,-1,-1,-1},
    {141,205,33,8727,8340,8977,8478,9025,8448,9137,8500,9145,8682,4128,-1,-1,-1,-1,-1,-1,-1,-1,-1,-1},
    {277,405,152,216,8718,8475,8902,8403,9150,8661,4128,-1,-1,-1,-1,-1,-1,-1,-1,-1,-1,-1,-1,-1},
    {277,405,152,216,8719,8474,8903,8402,9151,8660,4128,-1,-1,-1,-1,-1,-1,-1,-1,-1,-1,-1,-1,-1},
    {139,203,8886,8203,8856,8433,9032,8393,9080,8599,4128,-1,-1,-1,-1,-1,-1,-1,-1,-1,-1,-1,-1,-1},
    {139,203,8887,8202,8857,8432,9033,8392,9081,8598,4128,-1,-1,-1,-1,-1,-1,-1,-1,-1,-1,-1,-1,-1},
    {149,213,8746,8303,8982,8397,9084,8645,4128,-1,-1,-1,-1,-1,-1,-1,-1,-1,-1,-1,-1,-1,-1,-1},
    {149,213,8747,8302,8983,8396,9085,8644,4128,-1,-1,-1,-1,-1,-1,-1,-1,-1,-1,-1,-1,-1,-1,-1},
    {138,202,8870,8221,8860,8395,9060,8607,4128,-1,-1,-1,-1,-1,-1,-1,-1,-1,-1,-1,-1,-1,-1,-1},
    {138,202,8871,8220,8861,8394,9061,8606,4128,-1,-1,-1,-1,-1,-1,-1,-1,-1,-1,-1,-1,-1,-1,-1},
    {134,198,8738,8225,8728,8283,8962,8541,8992,8499,9074,8609,9124,8595,9184,8693,4128,-1,-1,-1,-1,-1,-1,-1},
    {134,198,8739,8224,8729,8282,8963,8540,8993,8498,9075,8608,9125,8594,9185,8692,4128,-1,-1,-1,-1,-1,-1,-1},
    {142,206,8874,8271,8818,8447,9068,8647,4128,-1,-1,-1,-1,-1,-1,-1,-1,-1,-1,-1,-1,-1,-1,-1},
    {142,206,8875,8270,8819,8446,9069,8646,4128,-1,-1,-1,-1,-1,-1,-1,-1,-1,-1,-1,-1,-1,-1,-1},
    {47,498,506,306,8892,8277,8784,8467,9048,8535,9020,8579,9088,8657,9186,8689,4128,-1,-1,-1,-1,-1,-1,-1},
    {47,498,506,306,8893,8276,8785,8466,9049,8534,9021,8578,9089,8656,9187,8688,4128,-1,-1,-1,-1,-1,-1,-1},
    {148,212,8762,8279,8826,8523,9002,8605,4128,-1,-1,-1,-1,-1,-1,-1,-1,-1,-1,-1,-1,-1,-1,-1},
    {148,212,8763,8278,8827,8522,9003,8604,4128,-1,-1,-1,-1,-1,-1,-1,-1,-1,-1,-1,-1,-1,-1,-1},
    {276,404,268,500,450,490,374,390,430,380,356,412,168,232,9018,8701,-1,-1,-1,-1,-1,-1,-1,-1},
    {276,404,268,500,450,490,374,390,430,380,356,412,168,232,9019,8700,-1,-1,-1,-1,-1,-1,-1,-1},
    {11,403,459,507,329,393,369,377,417,361,433,167,231,9132,8699,-1,-1,-1,-1,-1,-1,-1,-1,-1},
    {11,403,459,507,329,393,369,377,417,361,433,167,231,9133,8698,-1,-1,-1,-1,-1,-1,-1,-1,-1},
    {350,486,502,262,302,334,318,87,52,100,179,243,4096,-1,-1,-1,-1,-1,-1,-1,-1,-1,-1,-1},
    {350,486,502,262,302,334,318,87,52,100,179,243,4096,-1,-1,-1,-1,-1,-1,-1,-1,-1,-1,-1},
    {340,158,222,492,60,108,76,172,236,4096,-1,-1,-1,-1,-1,-1,-1,-1,-1,-1,-1,-1,-1,-1},
    {340,158,222,492,60,108,76,172,236,4096,-1,-1,-1,-1,-1,-1,-1,-1,-1,-1,-1,-1,-1,-1},
    {42,3,35,59,107,360,408,181,245,4096,-1,-1,-1,-1,-1,-1,-1,-1,-1,-1,-1,-1,-1,-1},
    {42,3,35,59,107,360,408,181,245,4096,-1,-1,-1,-1,-1,-1,-1,-1,-1,-1,-1,-1,-1,-1},
    {45,156,220,396,85,109,93,180,244,4096,-1,-1,-1,-1,-1,-1,-1,-1,-1,-1,-1,-1,-1,-1},
    {45,156,220,396,85,109,93,180,244,4096,-1,-1,-1,-1,-1,-1,-1,-1,-1,-1,-1,-1,-1,-1},
    {466,482,266,258,37,69,53,77,183,247,4096,-1,-1,-1,-1,-1,-1,-1,-1,-1,-1,-1,-1,-1},
    {466,482,266,258,37,69,53,77,183,247,4096,-1,-1,-1,-1,-1,-1,-1,-1,-1,-1,-1,-1,-1},
    {471,407,463,442,290,322,314,386,478,382,366,414,182,246,4096,-1,-1,-1,-1,-1,-1,-1,-1,-1},
    {471,407,463,442,290,322,314,386,478,382,366,414,182,246,4096,-1,-1,-1,-1,-1,-1,-1,-1,-1},
    {469,349,485,501,445,333,317,373,477,423,439,415,173,237,4096,-1,-1,-1,-1,-1,-1,-1,-1,-1},
    {469,349,485,501,445,333,317,373,477,423,439,415,173,237,4096,-1,-1,-1,-1,-1,-1,-1,-1,-1},
    {8,269,309,453,449,489,385,425,422,358,92,188,252,4096,-1,-1,-1,-1,-1,-1,-1,-1,-1,-1},
    {8,269,309,453,449,489,385,425,422,358,92,188,252,4096,-1,-1,-1,-1,-1,-1,-1,-1,-1,-1},
    {343,287,487,263,303,455,495,391,51,91,160,224,4096,-1,-1,-1,-1,-1,-1,-1,-1,-1,-1,-1},
    {343,287,487,263,303,455,495,391,51,91,160,224,4096,-1,-1,-1,-1,-1,-1,-1,-1,-1,-1,-1},
    {464,272,480,456,288,488,392,61,379,363,435,176,240,4096,-1,-1,-1,-1,-1,-1,-1,-1,-1,-1},
    {464,272,480,456,288,488,392,61,379,363,435,176,240,4096,-1,-1,-1,-1,-1,-1,-1,-1,-1,-1},
    {336,280,400,256,448,320,312,384,424,416,352,432,472,171,235,4096,-1,-1,-1,-1,-1,-1,-1,-1},
    {336,280,400,256,448,320,312,384,424,416,352,432,472,171,235,4096,-1,-1,-1,-1,-1,-1,-1,-1},
    {337,273,265,155,219,368,376,479,359,102,184,248,4096,-1,-1,-1,-1,-1,-1,-1,-1,-1,-1,-1},
    {337,273,265,155,219,368,376,479,359,102,184,248,4096,-1,-1,-1,-1,-1,-1,-1,-1,-1,-1,-1},
    {468,284,508,260,300,324,332,388,104,72,174,238,4096,-1,-1,-1,-1,-1,-1,-1,-1,-1,-1,-1},
    {468,284,508,260,300,324,332,388,104,72,174,238,4096,-1,-1,-1,-1,-1,-1,-1,-1,-1,-1,-1},
    {338,281,2,34,66,110,78,175,239,4096,-1,-1,-1,-1,-1,-1,-1,-1,-1,-1,-1,-1,-1,-1},
    {338,281,2,34,66,110,78,175,239,4096,-1,-1,-1,-1,-1,-1,-1,-1,-1,-1,-1,-1,-1,-1},
    {130,194,39,63,55,95,103,97,4096,-1,-1,-1,-1,-1,-1,-1,-1,-1,-1,-1,-1,-1,-1,-1},
    {130,194,39,63,55,95,103,97,4096,-1,-1,-1,-1,-1,-1,-1,-1,-1,-1,-1,-1,-1,-1,-1},
    {135,199,454,494,67,83,365,413,191,255,4096,-1,-1,-1,-1,-1,-1,-1,-1,-1,-1,-1,-1,-1},
    {135,199,454,494,67,83,365,413,191,255,4096,-1,-1,-1,-1,-1,-1,-1,-1,-1,-1,-1,-1,-1},
    {348,484,460,308,292,452,316,372,428,420,476,101,187,251,4096,-1,-1,-1,-1,-1,-1,-1,-1,-1},
    {348,484,460,308,292,452,316,372,428,420,476,101,187,251,4096,-1,-1,-1,-1,-1,-1,-1,-1,-1},
    {13,154,218,58,106,74,178,242,4096,-1,-1,-1,-1,-1,-1,-1,-1,-1,-1,-1,-1,-1,-1,-1},
    {13,154,218,58,106,74,178,242,4096,-1,-1,-1,-1,-1,-1,-1,-1,-1,-1,-1,-1,-1,-1,-1},
    {465,481,457,505,289,328,71,111,79,166,230,4096,-1,-1,-1,-1,-1,-1,-1,-1,-1,-1,-1,-1},
    {465,481,457,505,289,328,71,111,79,166,230,4096,-1,-1,-1,-1,-1,-1,-1,-1,-1,-1,-1,-1},
    {44,270,446,294,326,65,81,89,161,225,4096,-1,-1,-1,-1,-1,-1,-1,-1,-1,-1,-1,-1,-1},
    {44,270,446,294,326,65,81,89,161,225,4096,-1,-1,-1,-1,-1,-1,-1,-1,-1,-1,-1,-1,-1},
    {9,511,503,295,327,375,399,381,437,353,409,473,169,233,4096,-1,-1,-1,-1,-1,-1,-1,-1,-1},
    {9,511,503,295,327,375,399,381,437,353,409,473,169,233,4096,-1,-1,-1,-1,-1,-1,-1,-1,-1},
    {347,283,483,259,291,491,331,371,431,383,367,99,186,250,4096,-1,-1,-1,-1,-1,-1,-1,-1,-1},
    {347,283,483,259,291,491,331,371,431,383,367,99,186,250,4096,-1,-1,-1,-1,-1,-1,-1,-1,-1},
    {274,282,458,261,293,493,397,389,429,421,357,75,189,253,4096,-1,-1,-1,-1,-1,-1,-1,-1,-1},
    {274,282,458,261,293,493,397,389,429,421,357,75,189,253,4096,-1,-1,-1,-1,-1,-1,-1,-1,-1},
    {278,286,406,32,64,56,48,88,170,234,4096,-1,-1,-1,-1,-1,-1,-1,-1,-1,-1,-1,-1,-1},
    {278,286,406,32,64,56,48,88,170,234,4096,-1,-1,-1,-1,-1,-1,-1,-1,-1,-1,-1,-1,-1},
    {279,351,271,447,298,330,394,370,426,378,354,434,164,228,4096,-1,-1,-1,-1,-1,-1,-1,-1,-1},
    {279,351,271,447,298,330,394,370,426,378,354,434,164,228,4096,-1,-1,-1,-1,-1,-1,-1,-1,-1},
    {344,345,497,257,297,321,313,82,50,90,98,96,4096,-1,-1,-1,-1,-1,-1,-1,-1,-1,-1,-1},
    {344,345,497,257,297,321,313,82,50,90,98,96,4096,-1,-1,-1,-1,-1,-1,-1,-1,-1,-1,-1},
    {129,193,311,335,319,86,438,364,436,163,227,4096,-1,-1,-1,-1,-1,-1,-1,-1,-1,-1,-1,-1},
    {129,193,311,335,319,86,438,364,436,163,227,4096,-1,-1,-1,-1,-1,-1,-1,-1,-1,-1,-1,-1},
    {341,285,509,461,301,325,398,80,418,362,410,474,177,241,4096,-1,-1,-1,-1,-1,-1,-1,-1,-1},
    {341,285,509,461,301,325,398,80,418,362,410,474,177,241,4096,-1,-1,-1,-1,-1,-1,-1,-1,-1},
    {342,275,267,499,299,451,395,57,49,73,185,249,4096,-1,-1,-1,-1,-1,-1,-1,-1,-1,-1,-1},
    {342,275,267,499,299,451,395,57,49,73,185,249,4096,-1,-1,-1,-1,-1,-1,-1,-1,-1,-1,-1},
    {346,402,496,304,443,323,315,387,427,419,355,411,165,229,4096,-1,-1,-1,-1,-1,-1,-1,-1,-1},
    {346,402,496,304,443,323,315,387,427,419,355,411,165,229,4096,-1,-1,-1,-1,-1,-1,-1,-1,-1},
    {15,401,305,441,70,62,54,94,190,254,4096,-1,-1,-1,-1,-1,-1,-1,-1,-1,-1,-1,-1,-1},
    {15,401,305,441,70,62,54,94,190,254,4096,-1,-1,-1,-1,-1,-1,-1,-1,-1,-1,-1,-1,-1},
    {467,7,36,68,84,105,475,162,226,4096,-1,-1,-1,-1,-1,-1,-1,-1,-1,-1,-1,-1,-1,-1},
    {467,7,36,68,84,105,475,162,226,4096,-1,-1,-1,-1,-1,-1,-1,-1,-1,-1,-1,-1,-1,-1},
};

void build_rounds() {
    for (int c = 0; c < NUM_SMS / 2; c++) {
        const int16_t* jobs = h_params.jobs[2 * c];
        int nr = 0, prev_key = -1, last = 0;
        for (int j = 0; (jobs[j] >> 12) == T_P; j++) {
            const int n = jobs[j] >> 3, a = n >= 32, unit = n >= 16 && n < 32 ? (n >> 3) - 1 : 0, cnt = a ? 2 : 4;
            const int key = (jobs[j] & 7) | a << 3 | (unit > 0) << 4;
            const int wm = n < 16 ? 0 : (n < 32 ? 1 : n >> 4 & 1), col = n < 16 ? n : (n < 32 ? n & 7 : n & 15);
            const bool keep = key == prev_key, final_tile = (jobs[j + 1] >> 12) != T_P;
            const int k0 = keep ? last : 0;
            for (int r = 0; r < cnt; r++) {
                last = (k0 + r) % cnt;
                h_params.rounds[c][nr++] = (uint16_t)((key & 15) | wm << 4 | col << 6 | last << 10 | (keep && r == 0) << 12 | (final_tile && r == 0) << 13 | unit << 14);
            }
            prev_key = key;
        }
        while (nr < MAX_ROUNDS) h_params.rounds[c][nr++] = 0xFFFF;
        {
            const uint32_t rec = h_params.rounds[c][0], col = rec >> 6 & 15, unit = rec >> 14;
            for (uint32_t r = 0; r < 2; r++) {
                uint32_t wm[2], wb[2];
                for (uint32_t h = 0; h < 2; h++) {
                    wm[h] = 2 + ((rec & 8) ? 2 + h : ((rec >> 15) && h ? 0 : rec >> 4 & 1));
                    wb[h] = (rec & 8) ? (col + (rec & 16)) * 2
                                      : (unit == 0 ? col * 4 + h * 2 : (unit == 1 ? 16 + h * 16 + col * 2 : (h ? unit_head(col) : col) * 2));
                }
                const uint32_t am = unit ? 6 : (rec >> 3 & 1), arow = unit ? (rec & 7) * 128 + r * 64 : (rec & 7) * 256 + r * 128;
                h_params.first[2 * c + r] = make_uint2((unit ? 1 : 0) | am << 7 | wm[0] << 11 | wm[1] << 15 | arow << 20, wb[0] | wb[1] << 16);
            }
        }
    }
}

void build_schedule() {
    for (int c = 0; c < NUM_SMS; c++) {
        for (int j = 0; j < MAX_JOBS; j++) h_params.jobs[c][j] = k_jobs[c][j];
    }
    build_rounds();
}

}

extern "C" void kernel_launch(void* const* d_in, const int* in_sizes, int n_in, void* d_out, int out_size) {
    (void)in_sizes; (void)n_in; (void)out_size;
    static EncodeFn enc = nullptr;
    if (!enc) {
        cudaDriverEntryPointQueryResult qr;
        void* fn = nullptr;
        cudaGetDriverEntryPoint("cuTensorMapEncodeTiled", &fn, cudaEnableDefault, &qr);
        enc = (EncodeFn)fn;
        cudaFuncSetAttribute(fused_kernel, cudaFuncAttributeMaxDynamicSharedMemorySize, SMEM_BYTES);
        build_schedule();
    }
    void* qkv;
    cudaGetSymbolAddress(&qkv, g_qkv);
    Params& p = h_params;
    make_map3(enc, &p.amap[0], d_in[0], SEQ, DM, 128, 1);
    make_map3(enc, &p.amap[1], d_in[1], SEQ, DC, 128, 1);
    make_map3(enc, &p.wmap[0], d_in[2], DM, 4096, 64, 2);
    make_map3(enc, &p.wmap[2], d_in[3], DC, 4096, 64, 2);
    make_map3(enc, &p.wmap[3], d_in[4], DC, 4096, 64, 2);
    make_map3(enc, &p.wmap[1], d_in[7], DM, 3072, 64, 2);
    make_map3(enc, &p.wo_a, d_in[5], 4096, DM, 64, 2);
    make_map3(enc, &p.wo_b, d_in[8], DM, DM, 64, 2);
    make_map3(enc, &p.qkv_st, qkv, SEQ, QKV_W, 64, 1, true);
    make_map3(enc, &p.qkv_ld, qkv, SEQ, QKV_W, 128, 2, true);
    make_map3(enc, &p.qkv_half, qkv, SEQ, QKV_W, 128, 1, true);
    {
        cuuint64_t dims[4] = {64, SEQ / 2, 2, QKV_W / 64}, strides[3] = {256, 128, (cuuint64_t)SEQ * 128};
        cuuint32_t box[4] = {64, 64, 1, 1}, es[4] = {1, 1, 1, 1};
        enc(&p.st_par, CU_TENSOR_MAP_DATA_TYPE_BFLOAT16, 4, qkv, dims, strides, box, es, CU_TENSOR_MAP_INTERLEAVE_NONE,
            CU_TENSOR_MAP_SWIZZLE_128B, CU_TENSOR_MAP_L2_PROMOTION_L2_256B, CU_TENSOR_MAP_FLOAT_OOB_FILL_NONE);
        dims[3] = DM / 64; strides[0] = DM * 4; strides[1] = DM * 2; strides[2] = 128; box[2] = 2;
        enc(&p.x_par, CU_TENSOR_MAP_DATA_TYPE_BFLOAT16, 4, d_in[0], dims, strides, box, es, CU_TENSOR_MAP_INTERLEAVE_NONE,
            CU_TENSOR_MAP_SWIZZLE_128B, CU_TENSOR_MAP_L2_PROMOTION_L2_256B, CU_TENSOR_MAP_FLOAT_OOB_FILL_NONE);
    }
    make_map3(enc, &p.out_st, d_out, SEQ, DM, 64, 1);
    p.xp = (const __nv_bfloat16*)d_in[0];
    p.gate_w = (const __nv_bfloat16*)d_in[9];
    p.out = (__nv_bfloat16*)d_out;
    fused_kernel<<<NUM_SMS, 384, SMEM_BYTES, cudaStreamPerThread>>>(p);
}
```

```cpp
#include <cuda_runtime.h>
#include <cuda_bf16.h>
#include <cuda.h>
#include <stdint.h>

#define INL __attribute__((always_inline))

namespace {

constexpr int SEQ = 2048;
constexpr int DM = 1024;
constexpr int DC = 512;
constexpr int QKV_W = 13312;
constexpr int NUM_SMS = 132;
constexpr int GATE_DELAY_SHORT_NS = 1000, GATE_DELAY_LONG_NS = 3000;
constexpr int CLEAR_KS = 44, CLEAR_GAP_NS = 100;
constexpr float K_SCALE = 0.08838834764831845f * 1.4426950408889634f;

__device__ __align__(1024) __nv_bfloat16 g_qkv[(size_t)SEQ * QKV_W];
__device__ float g_gate[SEQ];
__device__ uint4 g_halo[16 * 8 * 2 * 5 * 4 * 32];

constexpr int F_Q = 0;
constexpr int F_KV = 1792;
constexpr int F_H = 768;
constexpr int F_CTX = 960;
constexpr int F_GATE = 1600;
constexpr int F_DONE = 1632;
constexpr int F_SPLIT = 1664;
constexpr int F_TICKET = 1696;
constexpr int F_OUT = 1728;
constexpr int GATE_COUNT = NUM_SMS;
__device__ uint32_t g_flags[2304];

#define END_MARK(slot)
#define TRACE_MARK(k, w, i)
#define GTRACE(w)
#define KTRACE(w)
#define PTRACE(i)
#define TRACE_GATE 32
#define TRACE_TID 128

__device__ __forceinline__ uint32_t smem_u32(const void* p) { return (uint32_t)__cvta_generic_to_shared(p); }
__device__ __forceinline__ void mbar_init(uint32_t bar, uint32_t cnt) {
    asm volatile("mbarrier.init.shared::cta.b64 [%0], %1;" ::"r"(bar), "r"(cnt));
}
__device__ __forceinline__ void mbar_arrive(uint32_t bar) {
    asm volatile("mbarrier.arrive.shared::cta.b64 _, [%0];" ::"r"(bar) : "memory");
}
__device__ __forceinline__ bool elect_one() {
    uint32_t r;
    asm volatile("{\n.reg .pred p;\nelect.sync _|p, 0xffffffff;\nselp.b32 %0, 1, 0, p;\n}" : "=r"(r));
    return r != 0;
}
__device__ __forceinline__ uint32_t mapa(uint32_t addr, uint32_t cta) {
    uint32_t r;
    asm("mapa.shared::cluster.u32 %0, %1, %2;" : "=r"(r) : "r"(addr), "r"(cta));
    return r;
}
__device__ __forceinline__ void warp_arrive(uint32_t bar, bool pred = true) {
    asm volatile("{\n.reg .pred p, q;\nsetp.ne.u32 q, %1, 0;\nelect.sync _|p, 0xffffffff;\nand.pred p, p, q;\n"
                 "@p mbarrier.arrive.shared::cta.b64 _, [%0];\n}" ::"r"(bar), "r"((uint32_t)pred) : "memory");
}
__device__ __forceinline__ void warp_arrive2(uint32_t bar0, uint32_t bar1) {
    asm volatile("{\n.reg .pred p;\nelect.sync _|p, 0xffffffff;\n@p mbarrier.arrive.shared::cta.b64 _, [%0];\n"
                 "@p mbarrier.arrive.shared::cta.b64 _, [%1];\n}" ::"r"(bar0), "r"(bar1) : "memory");
}
__device__ __forceinline__ void warp_arrive_pair(uint32_t bar, uint32_t peer_bar, bool pred = true) {
    asm volatile("{\n.reg .pred p, q;\nsetp.ne.u32 q, %2, 0;\nelect.sync _|p, 0xffffffff;\nand.pred p, p, q;\n"
                 "@p mbarrier.arrive.shared::cluster.b64 _, [%1];\n@p mbarrier.arrive.shared::cta.b64 _, [%0];\n}"
                 ::"r"(bar), "r"(peer_bar), "r"((uint32_t)pred) : "memory");
}
__device__ __forceinline__ void mbar_expect_tx(uint32_t bar, uint32_t bytes) {
    asm volatile("mbarrier.arrive.expect_tx.shared::cta.b64 _, [%0], %1;" ::"r"(bar), "r"(bytes) : "memory");
}
constexpr int WAIT_HINT_NS = 20000, WAIT_TRIES = 200000;
__device__ __forceinline__ void mbar_wait(uint32_t bar, uint32_t parity) {
    asm volatile("{\n.reg .pred p;\n.reg .u32 c;\n"
                 "mbarrier.try_wait.parity.shared::cta.b64 p, [%0], %1;\n@p bra DONE;\nmov.u32 c, 0;\n"
                 "SPIN:\nmbarrier.try_wait.parity.shared::cta.b64 p, [%0], %1, %2;\n@p bra DONE;\n"
                 "add.u32 c, c, 1;\nsetp.lt.u32 p, c, %3;\n@p bra SPIN;\ntrap;\nDONE:\n}"
                 ::"r"(bar), "r"(parity), "n"(WAIT_HINT_NS), "n"(WAIT_TRIES) : "memory");
}
__device__ __forceinline__ void mbar_wait_hot(uint32_t bar, uint32_t parity) {
    asm volatile("{\n.reg .pred p, q;\n.reg .u32 c;\n.reg .u64 z;\nmov.u32 c, 0;\nmov.u64 z, 0;\n"
                 "SPIN:\nmbarrier.try_wait.parity.shared::cta.b64 p, [%0], %1;\n"
                 "add.u32 c, c, 1;\nsetp.lt.and.u32 q, c, 4194304, !p;\n@q bra SPIN;\n@!p st.global.u32 [z], c;\n}"
                 ::"r"(bar), "r"(parity) : "memory");
}
constexpr uint64_t POL_STREAM = 0x12F0000000000000ull;
constexpr uint64_t POL_NORMAL = 0x1000000000000000ull;
__device__ __forceinline__ void tma_load_3d(uint32_t dst, const CUtensorMap* map, uint32_t bar, int c0, int c1, int c2, uint64_t pol = POL_NORMAL) {
    asm volatile("cp.async.bulk.tensor.3d.shared::cluster.global.mbarrier::complete_tx::bytes.L2::cache_hint [%0], [%1, {%3, %4, %5}], [%2], %6;"
                 ::"r"(dst), "l"(map), "r"(bar), "r"(c0), "r"(c1), "r"(c2), "l"(pol) : "memory");
}
__device__ __forceinline__ void load_kstep(uint32_t sa, uint32_t sw, uint32_t bar, uint32_t bytes, const CUtensorMap* wmap, int wk, int wblk,
                                           const CUtensorMap* amap, int arow, int kc, uint32_t amode) {
    asm volatile("{\n.reg .pred p, q, r;\n.reg .b32 k;\nelect.sync _|p, 0xffffffff;\nsetp.eq.and.u32 q, %9, 1, p;\nsetp.eq.and.u32 r, %9, 2, p;\nshl.b32 k, %12, 6;\n"
                 "@p mbarrier.arrive.expect_tx.shared::cta.b64 _, [%2], %3;\n"
                 "@p cp.async.bulk.tensor.3d.shared::cluster.global.mbarrier::complete_tx::bytes.multicast::cluster.L2::cache_hint [%1], [%4, {0, k, %5}], [%2], %10, %11;\n"
                 "@q cp.async.bulk.tensor.3d.shared::cluster.global.mbarrier::complete_tx::bytes.L2::cache_hint [%0], [%6, {0, %7, %8}], [%2], %11;\n"
                 "@r cp.async.bulk.tensor.4d.shared::cluster.global.mbarrier::complete_tx::bytes.L2::cache_hint [%0], [%6, {0, %7, 0, %8}], [%2], %11;\n}"
                 ::"r"(sa), "r"(sw), "r"(bar), "r"(bytes), "l"(wmap), "r"(wblk), "l"(amap), "r"(arow), "r"(kc), "r"(amode), "h"((uint16_t)3), "l"(POL_NORMAL), "r"(wk) : "memory");
}
__device__ __forceinline__ void load_operand(uint32_t dst, uint32_t bar, const CUtensorMap* full, const CUtensorMap* half, int row, int blk,
                                             uint32_t rank, bool solo, uint64_t pol) {
    asm volatile("{\n.reg .pred p, q, r;\n.reg .b32 d, b;\nelect.sync _|p, 0xffffffff;\nsetp.ne.and.u32 q, %7, 0, p;\nsetp.eq.and.u32 r, %7, 0, p;\n"
                 "mad.lo.u32 d, %6, 16384, %0;\nadd.u32 b, %5, %6;\n"
                 "@p mbarrier.arrive.expect_tx.shared::cta.b64 _, [%1], 32768;\n"
                 "@q cp.async.bulk.tensor.3d.shared::cluster.global.mbarrier::complete_tx::bytes.L2::cache_hint [%0], [%2, {0, %4, %5}], [%1], %9;\n"
                 "@r cp.async.bulk.tensor.3d.shared::cluster.global.mbarrier::complete_tx::bytes.multicast::cluster.L2::cache_hint [d], [%3, {0, %4, b}], [%1], %8, %9;\n}"
                 ::"r"(dst), "r"(bar), "l"(full), "l"(half), "r"(row), "r"(blk), "r"(rank), "r"((uint32_t)solo), "h"((uint16_t)3), "l"(pol) : "memory");
}
__device__ __forceinline__ void tma_store_par(const CUtensorMap* map, uint32_t src, int pair, int parity, int blk) {
    asm volatile("cp.async.bulk.tensor.4d.global.shared::cta.bulk_group.L2::cache_hint [%0, {0, %2, %3, %4}], [%1], %5;"
                 ::"l"(map), "r"(src), "r"(pair), "r"(parity), "r"(blk), "l"(POL_STREAM) : "memory");
}
__device__ __forceinline__ void tma_store_3d(const CUtensorMap* map, uint32_t src, int c0, int c1, int c2, uint64_t pol) {
    asm volatile("cp.async.bulk.tensor.3d.global.shared::cta.bulk_group.L2::cache_hint [%0, {%2, %3, %4}], [%1], %5;"
                 ::"l"(map), "r"(src), "r"(c0), "r"(c1), "r"(c2), "l"(pol) : "memory");
}
__device__ __forceinline__ void tma_reduce_add_3d(const CUtensorMap* map, uint32_t src, int c0, int c1, int c2) {
    asm volatile("cp.reduce.async.bulk.tensor.3d.global.shared::cta.add.tile.bulk_group [%0, {%2, %3, %4}], [%1];"
                 ::"l"(map), "r"(src), "r"(c0), "r"(c1), "r"(c2) : "memory");
}
__device__ __forceinline__ void bulk_commit() { asm volatile("cp.async.bulk.commit_group;" ::: "memory"); }
template <int N> __device__ __forceinline__ void bulk_wait_read() { asm volatile("cp.async.bulk.wait_group.read %0;" ::"n"(N) : "memory"); }
template <int N> __device__ __forceinline__ void bulk_wait() { asm volatile("cp.async.bulk.wait_group %0;" ::"n"(N) : "memory"); }
__device__ __forceinline__ void fence_async_smem() { asm volatile("fence.proxy.async.shared::cta;" ::: "memory"); }
__device__ __forceinline__ void fence_async_global() { asm volatile("fence.proxy.async.global;" ::: "memory"); }
__device__ __forceinline__ uint32_t ld_acquire(const uint32_t* p) {
    uint32_t v;
    asm volatile("ld.acquire.gpu.global.u32 %0, [%1];" : "=r"(v) : "l"(p) : "memory");
    return v;
}
__device__ __forceinline__ uint32_t ld_relaxed(const uint32_t* p) {
    uint32_t v;
    asm volatile("ld.relaxed.gpu.global.u32 %0, [%1];" : "=r"(v) : "l"(p) : "memory");
    return v;
}
__device__ __forceinline__ void fence_acquire() { asm volatile("fence.acquire.gpu;\nfence.proxy.async.global;" ::: "memory"); }
__device__ __forceinline__ void red_release(uint32_t* p) {
    asm volatile("red.release.gpu.global.add.u32 [%0], 1;" ::"l"(p) : "memory");
}
__device__ __forceinline__ void red_relaxed(uint32_t* p) {
    asm volatile("red.relaxed.gpu.global.add.u32 [%0], 1;" ::"l"(p) : "memory");
}
__device__ __forceinline__ void prefetch_map(const CUtensorMap* map) { asm volatile("prefetch.tensormap [%0];" ::"l"(map) : "memory"); }
__device__ __forceinline__ void trap_if(bool c) { asm volatile("{\n.reg .pred p;\nsetp.ne.u32 p, %0, 0;\n@p trap;\n}" ::"r"((uint32_t)c)); }
__device__ __forceinline__ void setup_arrive() { asm volatile("barrier.cluster.arrive.relaxed.aligned;" ::: "memory"); }
__device__ __forceinline__ void setup_wait() { asm volatile("barrier.cluster.wait.aligned;" ::: "memory"); }
__device__ __forceinline__ uint32_t cluster_rank() { uint32_t r; asm("mov.u32 %0, %%cluster_ctarank;" : "=r"(r)); return r; }
__device__ __forceinline__ void named_sync(int id, int n) { asm volatile("bar.sync %0, %1;" ::"r"(id), "r"(n) : "memory"); }
__device__ __forceinline__ void named_arrive(int id, int n) { asm volatile("bar.arrive %0, %1;" ::"r"(id), "r"(n) : "memory"); }
__device__ __forceinline__ void named_sync_if(bool c, int id, int n) {
    asm volatile("{\n.reg .pred p;\nsetp.ne.u32 p, %0, 0;\n@p bar.sync %1, %2;\n}" ::"r"((uint32_t)c), "r"(id), "r"(n) : "memory");
}
__device__ __forceinline__ void named_arrive_if(bool c, int id, int n) {
    asm volatile("{\n.reg .pred p;\nsetp.ne.u32 p, %0, 0;\n@p bar.arrive %1, %2;\n}" ::"r"((uint32_t)c), "r"(id), "r"(n) : "memory");
}
template <int V> struct IC { static constexpr int v = V; };
template <int N> __device__ __forceinline__ void reg_dec() { asm volatile("setmaxnreg.dec.sync.aligned.u32 %0;" ::"n"(N)); }
template <int N> __device__ __forceinline__ void reg_inc() { asm volatile("setmaxnreg.inc.sync.aligned.u32 %0;" ::"n"(N)); }

__device__ __forceinline__ void wg_fence() { asm volatile("wgmma.fence.sync.aligned;" ::: "memory"); }
__device__ __forceinline__ void wg_commit() { asm volatile("wgmma.commit_group.sync.aligned;" ::: "memory"); }
template <int N> __device__ __forceinline__ void wg_wait() { asm volatile("wgmma.wait_group.sync.aligned %0;" ::"n"(N) : "memory"); }
template <int N> __device__ __forceinline__ void fence_regs(float (&r)[N]) {
#pragma unroll
    for (int i = 0; i < N; i++) asm volatile("" : "+f"(r[i])::"memory");
}
template <int N> __device__ __forceinline__ void fence_regs(uint32_t (&r)[N]) {
#pragma unroll
    for (int i = 0; i < N; i++) asm volatile("" : "+r"(r[i])::"memory");
}
__device__ __forceinline__ uint32_t desc_lo(uint32_t addr, uint32_t lbo) { return ((addr & 0x3FFFF) >> 4) | ((lbo >> 4) << 16); }
__device__ __forceinline__ int uniform(int v) { return __shfl_sync(0xffffffffu, v, 0); }
__device__ __forceinline__ uint32_t pack_bf16(float lo, float hi) {
    uint32_t r;
    asm("cvt.rn.bf16x2.f32 %0, %1, %2;" : "=r"(r) : "f"(hi), "f"(lo));
    return r;
}
__device__ __forceinline__ uint32_t mul_bf16x2(uint32_t x, uint32_t y) {
    uint32_t r;
    asm("mul.rn.bf16x2 %0, %1, %2;" : "=r"(r) : "r"(x), "r"(y));
    return r;
}
__device__ __forceinline__ void stmatrix_x4(uint32_t addr, uint32_t r0, uint32_t r1, uint32_t r2, uint32_t r3) {
    asm volatile("stmatrix.sync.aligned.m8n8.x4.shared.b16 [%0], {%1, %2, %3, %4};"
                 ::"r"(addr), "r"(r0), "r"(r1), "r"(r2), "r"(r3) : "memory");
}
__device__ __forceinline__ void stmatrix_x4(uint32_t addr, uint32_t r0, uint32_t r1, uint32_t r2, uint32_t r3, bool trans) {
    asm volatile("{\n.reg .pred p;\nsetp.ne.u32 p, %5, 0;\n@p stmatrix.sync.aligned.m8n8.x4.trans.shared.b16 [%0], {%1, %2, %3, %4};\n"
                 "@!p stmatrix.sync.aligned.m8n8.x4.shared.b16 [%0], {%1, %2, %3, %4};\n}"
                 ::"r"(addr), "r"(r0), "r"(r1), "r"(r2), "r"(r3), "r"((uint32_t)trans) : "memory");
}
__device__ __forceinline__ void ldmatrix_x4_t(uint32_t addr, uint32_t (&r)[4]) {
    asm volatile("ldmatrix.sync.aligned.m8n8.x4.trans.shared.b16 {%0, %1, %2, %3}, [%4];"
                 : "=r"(r[0]), "=r"(r[1]), "=r"(r[2]), "=r"(r[3]) : "r"(addr) : "memory");
}
__device__ __forceinline__ void mma_16816(float (&d)[4], uint32_t a0, uint32_t a1, uint32_t a2, uint32_t a3, uint32_t b0, uint32_t b1) {
    asm("mma.sync.aligned.m16n8k16.row.col.f32.bf16.bf16.f32 {%0, %1, %2, %3}, {%4, %5, %6, %7}, {%8, %9}, {%0, %1, %2, %3};"
        : "+f"(d[0]), "+f"(d[1]), "+f"(d[2]), "+f"(d[3]) : "r"(a0), "r"(a1), "r"(a2), "r"(a3), "r"(b0), "r"(b1));
}
__device__ __forceinline__ void order_after(float v, uint32_t scratch) {
    asm volatile("{\n.reg .pred p;\nsetp.gt.f32 p, %0, 0f70000000;\n@p st.shared.u32 [%1], 0;\n}" ::"f"(v), "r"(scratch) : "memory");
}
__device__ __forceinline__ float rcp(float x) { float y; asm("rcp.approx.ftz.f32 %0, %1;" : "=f"(y) : "f"(x)); return y; }
__device__ __forceinline__ float ex2(float x) { float y; asm("ex2.approx.ftz.f32 %0, %1;" : "=f"(y) : "f"(x)); return y; }

template <int OA, int OB>
__device__ __forceinline__ void wgmma_ss_n256(float (&d0)[64], float (&d1)[64], uint32_t da, uint32_t db, uint32_t ha, uint32_t hb) {
    asm volatile("{\n.reg .b32 ta, tb;\n.reg .b64 da, db;\nadd.u32 ta, %128, %130;\nadd.u32 tb, %129, %131;\n"
        "mov.b64 da, {ta, %132};\nmov.b64 db, {tb, %133};\n"
        "wgmma.mma_async.sync.aligned.m64n256k16.f32.bf16.bf16 {%0, %1, %2, %3, %4, %5, %6, %7, %8, %9, %10, %11, %12, %13, %14, %15, %16, %17, %18, %19, %20, %21, %22, %23, %24, %25, %26, %27, %28, %29, %30, %31, %32, %33, %34, %35, %36, %37, %38, %39, %40, %41, %42, %43, %44, %45, %46, %47, %48, %49, %50, %51, %52, %53, %54, %55, %56, %57, %58, %59, %60, %61, %62, %63, %64, %65, %66, %67, %68, %69, %70, %71, %72, %73, %74, %75, %76, %77, %78, %79, %80, %81, %82, %83, %84, %85, %86, %87, %88, %89, %90, %91, %92, %93, %94, %95, %96, %97, %98, %99, %100, %101, %102, %103, %104, %105, %106, %107, %108, %109, %110, %111, %112, %113, %114, %115, %116, %117, %118, %119, %120, %121, %122, %123, %124, %125, %126, %127}, da, db, 1, 1, 1, 0, 1;\n}\n"
        : "+f"(d0[0]), "+f"(d0[1]), "+f"(d0[2]), "+f"(d0[3]), "+f"(d0[4]), "+f"(d0[5]), "+f"(d0[6]), "+f"(d0[7]), "+f"(d0[8]), "+f"(d0[9]), "+f"(d0[10]), "+f"(d0[11]), "+f"(d0[12]), "+f"(d0[13]), "+f"(d0[14]), "+f"(d0[15]), "+f"(d0[16]), "+f"(d0[17]), "+f"(d0[18]), "+f"(d0[19]), "+f"(d0[20]), "+f"(d0[21]), "+f"(d0[22]), "+f"(d0[23]), "+f"(d0[24]), "+f"(d0[25]), "+f"(d0[26]), "+f"(d0[27]), "+f"(d0[28]), "+f"(d0[29]), "+f"(d0[30]), "+f"(d0[31]), "+f"(d0[32]), "+f"(d0[33]), "+f"(d0[34]), "+f"(d0[35]), "+f"(d0[36]), "+f"(d0[37]), "+f"(d0[38]), "+f"(d0[39]), "+f"(d0[40]), "+f"(d0[41]), "+f"(d0[42]), "+f"(d0[43]), "+f"(d0[44]), "+f"(d0[45]), "+f"(d0[46]), "+f"(d0[47]), "+f"(d0[48]), "+f"(d0[49]), "+f"(d0[50]), "+f"(d0[51]), "+f"(d0[52]), "+f"(d0[53]), "+f"(d0[54]), "+f"(d0[55]), "+f"(d0[56]), "+f"(d0[57]), "+f"(d0[58]), "+f"(d0[59]), "+f"(d0[60]), "+f"(d0[61]), "+f"(d0[62]), "+f"(d0[63]), "+f"(d1[0]), "+f"(d1[1]), "+f"(d1[2]), "+f"(d1[3]), "+f"(d1[4]), "+f"(d1[5]), "+f"(d1[6]), "+f"(d1[7]), "+f"(d1[8]), "+f"(d1[9]), "+f"(d1[10]), "+f"(d1[11]), "+f"(d1[12]), "+f"(d1[13]), "+f"(d1[14]), "+f"(d1[15]), "+f"(d1[16]), "+f"(d1[17]), "+f"(d1[18]), "+f"(d1[19]), "+f"(d1[20]), "+f"(d1[21]), "+f"(d1[22]), "+f"(d1[23]), "+f"(d1[24]), "+f"(d1[25]), "+f"(d1[26]), "+f"(d1[27]), "+f"(d1[28]), "+f"(d1[29]), "+f"(d1[30]), "+f"(d1[31]), "+f"(d1[32]), "+f"(d1[33]), "+f"(d1[34]), "+f"(d1[35]), "+f"(d1[36]), "+f"(d1[37]), "+f"(d1[38]), "+f"(d1[39]), "+f"(d1[40]), "+f"(d1[41]), "+f"(d1[42]), "+f"(d1[43]), "+f"(d1[44]), "+f"(d1[45]), "+f"(d1[46]), "+f"(d1[47]), "+f"(d1[48]), "+f"(d1[49]), "+f"(d1[50]), "+f"(d1[51]), "+f"(d1[52]), "+f"(d1[53]), "+f"(d1[54]), "+f"(d1[55]), "+f"(d1[56]), "+f"(d1[57]), "+f"(d1[58]), "+f"(d1[59]), "+f"(d1[60]), "+f"(d1[61]), "+f"(d1[62]), "+f"(d1[63])
        : "r"(da), "r"(db), "n"(OA), "n"(OB), "r"(ha), "r"(hb));
}

__device__ __forceinline__ void wgmma_ss_n256_init(float (&d0)[64], float (&d1)[64], uint32_t da, uint32_t db, uint32_t ha, uint32_t hb) {
    asm volatile("{\n.reg .b64 da, db;\n"
        "mov.b64 da, {%128, %130};\nmov.b64 db, {%129, %131};\n"
        "wgmma.mma_async.sync.aligned.m64n256k16.f32.bf16.bf16 {%0, %1, %2, %3, %4, %5, %6, %7, %8, %9, %10, %11, %12, %13, %14, %15, %16, %17, %18, %19, %20, %21, %22, %23, %24, %25, %26, %27, %28, %29, %30, %31, %32, %33, %34, %35, %36, %37, %38, %39, %40, %41, %42, %43, %44, %45, %46, %47, %48, %49, %50, %51, %52, %53, %54, %55, %56, %57, %58, %59, %60, %61, %62, %63, %64, %65, %66, %67, %68, %69, %70, %71, %72, %73, %74, %75, %76, %77, %78, %79, %80, %81, %82, %83, %84, %85, %86, %87, %88, %89, %90, %91, %92, %93, %94, %95, %96, %97, %98, %99, %100, %101, %102, %103, %104, %105, %106, %107, %108, %109, %110, %111, %112, %113, %114, %115, %116, %117, %118, %119, %120, %121, %122, %123, %124, %125, %126, %127}, da, db, 0, 1, 1, 0, 1;\n}\n"
        : "=f"(d0[0]), "=f"(d0[1]), "=f"(d0[2]), "=f"(d0[3]), "=f"(d0[4]), "=f"(d0[5]), "=f"(d0[6]), "=f"(d0[7]), "=f"(d0[8]), "=f"(d0[9]), "=f"(d0[10]), "=f"(d0[11]), "=f"(d0[12]), "=f"(d0[13]), "=f"(d0[14]), "=f"(d0[15]), "=f"(d0[16]), "=f"(d0[17]), "=f"(d0[18]), "=f"(d0[19]), "=f"(d0[20]), "=f"(d0[21]), "=f"(d0[22]), "=f"(d0[23]), "=f"(d0[24]), "=f"(d0[25]), "=f"(d0[26]), "=f"(d0[27]), "=f"(d0[28]), "=f"(d0[29]), "=f"(d0[30]), "=f"(d0[31]), "=f"(d0[32]), "=f"(d0[33]), "=f"(d0[34]), "=f"(d0[35]), "=f"(d0[36]), "=f"(d0[37]), "=f"(d0[38]), "=f"(d0[39]), "=f"(d0[40]), "=f"(d0[41]), "=f"(d0[42]), "=f"(d0[43]), "=f"(d0[44]), "=f"(d0[45]), "=f"(d0[46]), "=f"(d0[47]), "=f"(d0[48]), "=f"(d0[49]), "=f"(d0[50]), "=f"(d0[51]), "=f"(d0[52]), "=f"(d0[53]), "=f"(d0[54]), "=f"(d0[55]), "=f"(d0[56]), "=f"(d0[57]), "=f"(d0[58]), "=f"(d0[59]), "=f"(d0[60]), "=f"(d0[61]), "=f"(d0[62]), "=f"(d0[63]), "=f"(d1[0]), "=f"(d1[1]), "=f"(d1[2]), "=f"(d1[3]), "=f"(d1[4]), "=f"(d1[5]), "=f"(d1[6]), "=f"(d1[7]), "=f"(d1[8]), "=f"(d1[9]), "=f"(d1[10]), "=f"(d1[11]), "=f"(d1[12]), "=f"(d1[13]), "=f"(d1[14]), "=f"(d1[15]), "=f"(d1[16]), "=f"(d1[17]), "=f"(d1[18]), "=f"(d1[19]), "=f"(d1[20]), "=f"(d1[21]), "=f"(d1[22]), "=f"(d1[23]), "=f"(d1[24]), "=f"(d1[25]), "=f"(d1[26]), "=f"(d1[27]), "=f"(d1[28]), "=f"(d1[29]), "=f"(d1[30]), "=f"(d1[31]), "=f"(d1[32]), "=f"(d1[33]), "=f"(d1[34]), "=f"(d1[35]), "=f"(d1[36]), "=f"(d1[37]), "=f"(d1[38]), "=f"(d1[39]), "=f"(d1[40]), "=f"(d1[41]), "=f"(d1[42]), "=f"(d1[43]), "=f"(d1[44]), "=f"(d1[45]), "=f"(d1[46]), "=f"(d1[47]), "=f"(d1[48]), "=f"(d1[49]), "=f"(d1[50]), "=f"(d1[51]), "=f"(d1[52]), "=f"(d1[53]), "=f"(d1[54]), "=f"(d1[55]), "=f"(d1[56]), "=f"(d1[57]), "=f"(d1[58]), "=f"(d1[59]), "=f"(d1[60]), "=f"(d1[61]), "=f"(d1[62]), "=f"(d1[63])
        : "r"(da), "r"(db), "r"(ha), "r"(hb));
}

template <int TB, int OA, int OB>
__device__ __forceinline__ void wgmma_ss_n128_init(float (&d)[64], uint32_t da, uint32_t db, uint32_t ha, uint32_t hb) {
    asm volatile("{\n.reg .b32 ta, tb;\n.reg .b64 da, db;\nadd.u32 ta, %64, %66;\nadd.u32 tb, %65, %67;\n"
        "mov.b64 da, {ta, %69};\nmov.b64 db, {tb, %70};\n"
        "wgmma.mma_async.sync.aligned.m64n128k16.f32.bf16.bf16 {%0, %1, %2, %3, %4, %5, %6, %7, %8, %9, %10, %11, %12, %13, %14, %15, %16, %17, %18, %19, %20, %21, %22, %23, %24, %25, %26, %27, %28, %29, %30, %31, %32, %33, %34, %35, %36, %37, %38, %39, %40, %41, %42, %43, %44, %45, %46, %47, %48, %49, %50, %51, %52, %53, %54, %55, %56, %57, %58, %59, %60, %61, %62, %63}, da, db, 0, 1, 1, 0, %68;\n}\n"
        : "=f"(d[0]), "=f"(d[1]), "=f"(d[2]), "=f"(d[3]), "=f"(d[4]), "=f"(d[5]), "=f"(d[6]), "=f"(d[7]), "=f"(d[8]), "=f"(d[9]), "=f"(d[10]), "=f"(d[11]), "=f"(d[12]), "=f"(d[13]), "=f"(d[14]), "=f"(d[15]), "=f"(d[16]), "=f"(d[17]), "=f"(d[18]), "=f"(d[19]), "=f"(d[20]), "=f"(d[21]), "=f"(d[22]), "=f"(d[23]), "=f"(d[24]), "=f"(d[25]), "=f"(d[26]), "=f"(d[27]), "=f"(d[28]), "=f"(d[29]), "=f"(d[30]), "=f"(d[31]), "=f"(d[32]), "=f"(d[33]), "=f"(d[34]), "=f"(d[35]), "=f"(d[36]), "=f"(d[37]), "=f"(d[38]), "=f"(d[39]), "=f"(d[40]), "=f"(d[41]), "=f"(d[42]), "=f"(d[43]), "=f"(d[44]), "=f"(d[45]), "=f"(d[46]), "=f"(d[47]), "=f"(d[48]), "=f"(d[49]), "=f"(d[50]), "=f"(d[51]), "=f"(d[52]), "=f"(d[53]), "=f"(d[54]), "=f"(d[55]), "=f"(d[56]), "=f"(d[57]), "=f"(d[58]), "=f"(d[59]), "=f"(d[60]), "=f"(d[61]), "=f"(d[62]), "=f"(d[63])
        : "r"(da), "r"(db), "n"(OA), "n"(OB), "n"(TB), "r"(ha), "r"(hb));
}

template <int OA, int OB>
__device__ __forceinline__ void wgmma_ss_n128_tb0(float (&d)[64], uint32_t da, uint32_t db, int scale_d, uint32_t ha, uint32_t hb) {
    asm volatile("{\n.reg .pred p;\n.reg .b32 ta, tb;\n.reg .b64 da, db;\nsetp.ne.b32 p, %66, 0;\nadd.u32 ta, %64, %67;\nadd.u32 tb, %65, %68;\n"
        "mov.b64 da, {ta, %69};\nmov.b64 db, {tb, %70};\n"
        "wgmma.mma_async.sync.aligned.m64n128k16.f32.bf16.bf16 "
        "{%0, %1, %2, %3, %4, %5, %6, %7, %8, %9, %10, %11, %12, %13, %14, %15, %16, %17, %18, %19, %20, %21, %22, %23, %24, %25, %26, %27, %28, %29, %30, %31, %32, %33, %34, %35, %36, %37, %38, %39, %40, %41, %42, %43, %44, %45, %46, %47, %48, %49, %50, %51, %52, %53, %54, %55, %56, %57, %58, %59, %60, %61, %62, %63}, da, db, p, 1, 1, 0, 0;\n}\n"
        : "+f"(d[0]), "+f"(d[1]), "+f"(d[2]), "+f"(d[3]), "+f"(d[4]), "+f"(d[5]), "+f"(d[6]), "+f"(d[7]), "+f"(d[8]), "+f"(d[9]), "+f"(d[10]), "+f"(d[11]), "+f"(d[12]), "+f"(d[13]), "+f"(d[14]), "+f"(d[15]), "+f"(d[16]), "+f"(d[17]), "+f"(d[18]), "+f"(d[19]), "+f"(d[20]), "+f"(d[21]), "+f"(d[22]), "+f"(d[23]), "+f"(d[24]), "+f"(d[25]), "+f"(d[26]), "+f"(d[27]), "+f"(d[28]), "+f"(d[29]), "+f"(d[30]), "+f"(d[31]), "+f"(d[32]), "+f"(d[33]), "+f"(d[34]), "+f"(d[35]), "+f"(d[36]), "+f"(d[37]), "+f"(d[38]), "+f"(d[39]), "+f"(d[40]), "+f"(d[41]), "+f"(d[42]), "+f"(d[43]), "+f"(d[44]), "+f"(d[45]), "+f"(d[46]), "+f"(d[47]), "+f"(d[48]), "+f"(d[49]), "+f"(d[50]), "+f"(d[51]), "+f"(d[52]), "+f"(d[53]), "+f"(d[54]), "+f"(d[55]), "+f"(d[56]), "+f"(d[57]), "+f"(d[58]), "+f"(d[59]), "+f"(d[60]), "+f"(d[61]), "+f"(d[62]), "+f"(d[63])
        : "r"(da), "r"(db), "r"(scale_d), "n"(OA), "n"(OB), "r"(ha), "r"(hb));
}

template <int OB>
__device__ __forceinline__ void wgmma_rs_n128_tb1(float (&d)[64], uint32_t a0, uint32_t a1, uint32_t a2, uint32_t a3, uint32_t db, int scale_d, uint32_t hb) {
    asm volatile("{\n.reg .pred p;\n.reg .b32 tb;\n.reg .b64 db;\nsetp.ne.b32 p, %69, 0;\nadd.u32 tb, %68, %70;\n"
        "mov.b64 db, {tb, %71};\n"
        "wgmma.mma_async.sync.aligned.m64n128k16.f32.bf16.bf16 "
        "{%0, %1, %2, %3, %4, %5, %6, %7, %8, %9, %10, %11, %12, %13, %14, %15, %16, %17, %18, %19, %20, %21, %22, %23, %24, %25, %26, %27, %28, %29, %30, %31, %32, %33, %34, %35, %36, %37, %38, %39, %40, %41, %42, %43, %44, %45, %46, %47, %48, %49, %50, %51, %52, %53, %54, %55, %56, %57, %58, %59, %60, %61, %62, %63}, {%64, %65, %66, %67}, db, p, 1, 1, 1;\n}\n"
        : "+f"(d[0]), "+f"(d[1]), "+f"(d[2]), "+f"(d[3]), "+f"(d[4]), "+f"(d[5]), "+f"(d[6]), "+f"(d[7]), "+f"(d[8]), "+f"(d[9]), "+f"(d[10]), "+f"(d[11]), "+f"(d[12]), "+f"(d[13]), "+f"(d[14]), "+f"(d[15]), "+f"(d[16]), "+f"(d[17]), "+f"(d[18]), "+f"(d[19]), "+f"(d[20]), "+f"(d[21]), "+f"(d[22]), "+f"(d[23]), "+f"(d[24]), "+f"(d[25]), "+f"(d[26]), "+f"(d[27]), "+f"(d[28]), "+f"(d[29]), "+f"(d[30]), "+f"(d[31]), "+f"(d[32]), "+f"(d[33]), "+f"(d[34]), "+f"(d[35]), "+f"(d[36]), "+f"(d[37]), "+f"(d[38]), "+f"(d[39]), "+f"(d[40]), "+f"(d[41]), "+f"(d[42]), "+f"(d[43]), "+f"(d[44]), "+f"(d[45]), "+f"(d[46]), "+f"(d[47]), "+f"(d[48]), "+f"(d[49]), "+f"(d[50]), "+f"(d[51]), "+f"(d[52]), "+f"(d[53]), "+f"(d[54]), "+f"(d[55]), "+f"(d[56]), "+f"(d[57]), "+f"(d[58]), "+f"(d[59]), "+f"(d[60]), "+f"(d[61]), "+f"(d[62]), "+f"(d[63])
        : "r"(a0), "r"(a1), "r"(a2), "r"(a3), "r"(db), "r"(scale_d), "n"(OB), "r"(hb));
}

__device__ __forceinline__ uint32_t stage_addr(uint32_t block, int warp, int lane) {
    return block + (warp * 16 + (lane & 7) + ((lane >> 3) & 1) * 8) * 128 + (((lane >> 4) ^ (lane & 7)) << 4);
}
template <int OFF, int N>
__device__ __forceinline__ void stage_packed_64x64(uint32_t a0, int off, const uint32_t (&v)[N]) {
#pragma unroll
    for (int j = 0; j < 8; j += 2) {
        uint32_t a = a0;
        if (j) asm volatile("xor.b32 %0, %1, %2;" : "=r"(a) : "r"(a0), "r"(j << 4));
        stmatrix_x4(a + off, v[OFF + j * 2], v[OFF + j * 2 + 1], v[OFF + j * 2 + 2], v[OFF + j * 2 + 3]);
    }
}

template <int OFF, int N>
__device__ __forceinline__ void stage_packed_64x64(const uint32_t (&a)[4], int off, const uint32_t (&v)[N]) {
#pragma unroll
    for (int j = 0; j < 4; j++) stmatrix_x4(a[j] + off, v[OFF + j * 4], v[OFF + j * 4 + 1], v[OFF + j * 4 + 2], v[OFF + j * 4 + 3]);
}

template <int OFF, int N>
__device__ __forceinline__ void stage_packed_64x64(const uint32_t (&a)[4], int off, const uint32_t (&v)[N], bool trans) {
#pragma unroll
    for (int j = 0; j < 4; j++) stmatrix_x4(a[j] + off, v[OFF + j * 4], v[OFF + j * 4 + 1], v[OFF + j * 4 + 2], v[OFF + j * 4 + 3], trans);
}

constexpr int MAX_JOBS = 24;
constexpr int MAX_ROUNDS = 44;
constexpr int T_P = 0, T_O = 1, T_A = 2;
constexpr int HQ_A = 4, HQ_B = 28;
__host__ __device__ constexpr int unit_head(int g) { return g + (g < 4 ? HQ_A : HQ_B - 4); }
constexpr int G_STAGE = 49152;
constexpr int OFF_Q0 = 0, OFF_K0 = 32768, OFF_Q1 = 65536, OFF_K1 = 98304, OFF_V0 = 131072, OFF_V1 = 163840;
constexpr int OFF_STG = 196608;
constexpr int OFF_BAR = 229376;
constexpr int SMEM_BYTES = OFF_BAR + 640;
constexpr int TURN_THREADS = 288;

struct Params {
    CUtensorMap amap[2];
    CUtensorMap wmap[4];
    CUtensorMap x_par, wo_a, wo_b, qkv_st, qkv_ld, qkv_half, st_par, out_st;
    const __nv_bfloat16* xp;
    const __nv_bfloat16* gate_w;
    __nv_bfloat16* out;
    uint2 first[NUM_SMS];
    int16_t jobs[NUM_SMS][MAX_JOBS];
    uint16_t rounds[NUM_SMS / 2][MAX_ROUNDS];
};

constexpr int O_STAGGER = 4;
constexpr int O_F0 = 35, O_H1 = 5;
constexpr int O_FLEX = 16, O_H0 = O_F0 + 8, O_T0 = 8, O_T1 = 64 - O_F0 - O_FLEX - O_H1;
__device__ __forceinline__ int o_head(int job) { return (job & 32) ? O_H1 : O_H0; }
__device__ __forceinline__ int o_tail(int job) { return (job & 32) ? O_T1 : O_T0; }
__device__ __forceinline__ uint32_t o_state(uint32_t word, int have) {
    uint32_t v;
    asm volatile("{\n.reg .pred p, q;\n.reg .u32 c, t;\nmov.u32 c, 0;\n"
                 "SPIN:\nld.volatile.shared.u32 %0, [%1];\nand.b32 t, %0, 1;\nsetp.ne.u32 q, t, 0;\nsetp.gt.or.u32 p, %0, %2, q;\n@p bra DONE;\n"
                 "add.u32 c, c, 1;\nsetp.lt.u32 q, c, 16777216;\n@q bra SPIN;\ntrap;\nDONE:\n}"
                 : "=r"(v) : "r"(word), "r"(2 * have + 1) : "memory");
    return v;
}

template <class T> __device__ __forceinline__ T* page_ptr(int off) {
    extern __shared__ __align__(1024) uint8_t smem_raw[];
    return *reinterpret_cast<T* volatile*>(smem_raw + OFF_BAR + off);
}
template <int SLEEP_NS = 0>
__device__ __forceinline__ bool wait_flags(bool active, int idx, uint32_t target, bool block = true) {
    for (uint32_t tries = 0;; tries++) {
        const bool ok = !active | ((int32_t)(ld_acquire(g_flags + idx) - target) >= 0);
        if (__all_sync(0xffffffffu, ok)) break;
        if (!block) return false;
        if (SLEEP_NS) __nanosleep(SLEEP_NS);
        trap_if(tries > (1u << 22));
    }
    fence_async_global();
    return true;
}

__global__ void __cluster_dims__(2, 1, 1) __launch_bounds__(384, 1)
fused_kernel(const __grid_constant__ Params p) {
    extern __shared__ __align__(1024) uint8_t smem_raw[];
    const uint32_t base = smem_u32(smem_raw);
    const uint32_t bars = base + OFF_BAR;
    const uint32_t gfull = bars, gempty = bars + 32, sfull = bars + 64, sempty = bars + 96;
    const uint32_t qfull = bars + 128, qempty = bars + 144, kfull = bars + 160, kempty = bars + 176;
    const uint32_t vfull = bars + 192, vempty = bars + 208, lready = bars + 224, hout = bars + 240;
    const uint32_t tfull = bars + 256, aready = bars + 272, gatefull = bars + 280;
    const uint32_t otile = bars + 528;
    const uint32_t olim = bars + 504;
    const uint32_t stg = base + OFF_STG;
    uint32_t* rounds = reinterpret_cast<uint32_t*>(smem_raw + OFF_BAR + 416);
    const uint32_t rank = cluster_rank();
    int* jobs = reinterpret_cast<int*>(smem_raw + OFF_BAR + 312);
    auto w_map = [&](uint32_t rec, uint32_t half) INL { return &p.wmap[(rec & 8) ? 2 + half : ((rec >> 15) && half ? 0 : rec >> 4 & 1)]; };
    auto w_blk = [&](uint32_t rec, uint32_t half) INL -> int {
        const int col = rec >> 6 & 15;
        if (rec & 8) return (col + (rec & 16)) * 2;
        return rec >> 14 == 0 ? col * 4 + half * 2 : (rec >> 14 == 1 ? 16 + half * 16 + col * 2 : (half ? unit_head(col) : col) * 2);
    };
    auto load_round = [&](uint32_t rec, int st0, uint32_t parity) INL {
        const CUtensorMap* wm = w_map(rec, rank);
        const CUtensorMap* am = rec >> 14 ? &p.x_par : &p.amap[rec >> 3 & 1];
        const int wb = w_blk(rec, rank), kc0 = (rec >> 10 & 3) * 4, arow = ((rec & 7) * 256 + rank * 128) >> (rec >> 14 ? 1 : 0);
        const uint32_t bytes = (rec & 4096) ? G_STAGE - 16384 : G_STAGE, amode = (rec & 4096) ? 0 : (rec >> 14 ? 2 : 1);
#pragma unroll 1
        for (int st = st0; st < 4; st++) {
            const uint32_t sa = base + st * G_STAGE;
            mbar_wait(gempty + st * 8, parity);
            load_kstep(sa, sa + 16384 + rank * 16384, gfull + st * 8, bytes, wm, kc0 + st, wb, am, arow, kc0 + st, amode);
        }
    };
    if (threadIdx.x < 32) {
        if (elect_one()) {
            const uint2 r = p.first[blockIdx.x];
            mbar_init(gfull, 1);
            fence_async_smem();
            const char* maps;
            asm("mov.b64 %0, %1;" : "=l"(maps) : "l"(&p.amap[0]));
            asm volatile("{\n.reg .pred q;\nsetp.eq.u32 q, %8, 0;\n"
                         "mbarrier.arrive.expect_tx.shared::cta.b64 _, [%1], 49152;\n"
                         "cp.async.bulk.tensor.3d.shared::cluster.global.mbarrier::complete_tx::bytes.L2::cache_hint [%9], [%3, {0, 0, %6}], [%1], %11;\n"
                         "cp.async.bulk.tensor.3d.shared::cluster.global.mbarrier::complete_tx::bytes.L2::cache_hint [%10], [%4, {0, 0, %7}], [%1], %11;\n"
                         "@q cp.async.bulk.tensor.3d.shared::cluster.global.mbarrier::complete_tx::bytes.L2::cache_hint [%0], [%2, {0, %5, 0}], [%1], %11;\n"
                         "@!q cp.async.bulk.tensor.4d.shared::cluster.global.mbarrier::complete_tx::bytes.L2::cache_hint [%0], [%2, {0, %5, 0, 0}], [%1], %11;\n}"
                         ::"r"(base), "r"(gfull), "l"(maps + (r.x & 0x780)), "l"(maps + (r.x >> 4 & 0x780)), "l"(maps + (r.x >> 8 & 0x780)),
                           "r"(r.x >> 20), "r"(r.y & 0xffff), "r"(r.y >> 16), "r"(r.x & 1), "r"(base + 16384), "r"(base + 32768), "l"(POL_NORMAL) : "memory");
            asm volatile("fence.mbarrier_init.release.cluster;" ::: "memory");
        }
        __syncwarp();
    }
    const int tid = threadIdx.x, warp = uniform(tid >> 5), lane = tid & 31, wg = warp >> 2;
    if (warp == 1) {
        if (elect_one()) {
#pragma unroll
            for (int i = 1; i < 39; i++)
                mbar_init(bars + i * 8, (0x0CC000F0ull >> i & 1) ? 16 : ((0x300000F00ull >> i & 1) ? 4 : ((0xC0000ull >> i & 1) ? 8 : 1)));
            asm volatile("fence.mbarrier_init.release.cluster;" ::: "memory");
            fence_async_smem();
        }
        __syncwarp();
    }
    setup_arrive();
    if (warp > 3) {
        reg_inc<232>();
        named_sync(0, 352);
        const int w = wg - 1, wwarp = warp & 3;
        const uint32_t slot_a = stage_addr(stg + w * 16384, wwarp, lane);
        const uint32_t bars_peer = uniform(mapa(bars, rank ^ 1));
        auto arrive_pair = [&](uint32_t bar, bool pred = true) INL { warp_arrive_pair(bar, bars_peer + (bar - bars), pred); };
        uint32_t gph = 0;
        uint32_t sph = 1;
        int jb = 0;
        int job = uniform(jobs[0]);
        auto next_job = [&]() INL { jb++; job = uniform(jobs[jb]); };
        auto desc_hi = [&]() INL {
            uint32_t v;
            asm volatile("ld.volatile.shared.b32 %0, [%1];\nadd.u32 %0, %0, 0x40000041;" : "=r"(v) : "r"(bars + 312 + MAX_JOBS * 4));
            return (uint32_t)uniform(v);
        };
        auto slot_wait = [&](int q) INL { mbar_wait(sempty + (w * 2 + (q & 1)) * 8, (q >> 1) ^ sph ^ 1); };
        auto signal = [&](int q) INL {
            __syncwarp();
            warp_arrive(sfull + (w * 2 + (q & 1)) * 8);
        };
        uint32_t pk[64];
        float O[64];
        uint32_t slot4[4];
        bool ptrans = false;
        auto stage_quarter = [&](const int Q) INL {
            slot_wait(Q);
            if (Q == 0) stage_packed_64x64<0>(slot4, 0, pk, ptrans);
            if (Q == 1) stage_packed_64x64<16>(slot4, 8192, pk, ptrans);
            if (Q == 2) stage_packed_64x64<32>(slot4, 0, pk);
            if (Q == 3) stage_packed_64x64<48>(slot4, 8192, pk);
        };
        auto stage_pair = [&]() INL {
            slot_wait(1);
            stage_packed_64x64<0>(slot4, 0, pk, ptrans);
            stage_packed_64x64<16>(slot4, 8192, pk, ptrans);
        };
        auto signal_both = [&]() INL {
            __syncwarp();
            warp_arrive2(sfull + w * 16, sfull + w * 16 + 8);
        };
        uint32_t un = 0;
        auto lane_id = [&]() INL { uint32_t ln; asm volatile("mov.u32 %0, %%laneid;" : "=r"(ln)); return ln; };
        auto v_addr = [&](uint32_t ln) INL { return stg + w * 16384 + (wwarp * 16 + (ln & 7)) * 128 + (((ln >> 3) ^ (ln & 7)) << 4); };
        auto v_off = [&](uint32_t a, const int h) INL { return (a ^ ((h & 1) * 64)) + (h >> 1) * 8192; };
        auto halo_ptr = [&](int mt, int g, int slot, uint32_t ln) INL { return page_ptr<uint4>(512) + (((mt * 8 + g) * 2 + w) * 5 + slot) * 128 + ln; };
        auto pack_k = [&](const float (&acc)[64]) INL {
#pragma unroll
            for (int j = 0; j < 16; j++) { pk[j] = pack_bf16(acc[4 * j], acc[4 * j + 1]); pk[16 + j] = pack_bf16(acc[4 * j + 2], acc[4 * j + 3]); }
        };
        auto unit_export = [&](int cur) INL {
            const uint32_t ln = lane_id();
            uint4* dst = halo_ptr((cur & 7) * 2 + rank, cur >> 3 & 7, wwarp, ln);
            slot_wait(1);
            stage_packed_64x64<32>(slot4, 0, pk);
            stage_packed_64x64<48>(slot4, 8192, pk);
#pragma unroll
            for (int h = 0; h < 4; h++) __stcg(dst + h * 32, make_uint4(pk[16 + h * 4], pk[17 + h * 4], pk[18 + h * 4], pk[19 + h * 4]));
            __syncwarp();
            if (wwarp == 3) {
                const uint32_t va = v_addr(ln) + 1024;
#pragma unroll
                for (int h = 0; h < 4; h++) {
                    uint32_t t[4];
                    ldmatrix_x4_t(v_off(va, h), t);
                    pk[32 + h * 4] = t[0]; pk[33 + h * 4] = t[1]; pk[34 + h * 4] = t[2]; pk[35 + h * 4] = t[3];
                }
#pragma unroll
                for (int h = 0; h < 4; h++) __stcg(dst + 128 + h * 32, make_uint4(pk[32 + h * 4], pk[33 + h * 4], pk[34 + h * 4], pk[35 + h * 4]));
                __syncwarp();
                warp_arrive(hout + w * 8);
            }
        };
        auto unit_import = [&](int cur) INL {
            const uint32_t ln = lane_id();
            const int mt = (cur & 7) * 2 + rank;
            mbar_wait(lready + un * 8, 0);
            un++;
            const uint4* src = halo_ptr(wwarp ? mt : max(mt - 1, 0), cur >> 3 & 7, (wwarp + 3) & 3, ln);
#pragma unroll
            for (int h = 0; h < 4; h++) {
                const uint4 t = __ldcg(src + h * 32);
                pk[32 + h * 4] = t.x; pk[33 + h * 4] = t.y; pk[34 + h * 4] = t.z; pk[35 + h * 4] = t.w;
            }
            if (wwarp) {
                const uint32_t va = v_addr(ln) - 1024;
#pragma unroll
                for (int h = 0; h < 4; h++) {
                    uint32_t t[4];
                    ldmatrix_x4_t(v_off(va, h), t);
                    pk[48 + h * 4] = t[0]; pk[49 + h * 4] = t[1]; pk[50 + h * 4] = t[2]; pk[51 + h * 4] = t[3];
                }
            } else {
#pragma unroll
                for (int h = 0; h < 4; h++) {
                    const uint4 t = __ldcg(src + 128 + h * 32);
                    pk[48 + h * 4] = t.x; pk[49 + h * 4] = t.y; pk[50 + h * 4] = t.z; pk[51 + h * 4] = t.w;
                }
            }
        };
        auto unit_attend = [&](const float (&q)[64], int cur) INL {
            const float cs = 0.17677669529663687f * 1.4426950408889634f;
            const uint32_t ln = lane_id();
            const int g = ln >> 2, c2 = (ln & 3) * 2, mt = (cur & 7) * 2 + rank;
            uint32_t qf[32], vo[8][4];
#pragma unroll
            for (int i = 0; i < 32; i++) qf[i] = pack_bf16(q[2 * i], q[2 * i + 1]);
            fence_regs(qf);
            const float* gp = page_ptr<float>(520) + mt * 128 + wwarp * 32 + g * 2 + w;
            const float lg0 = 1.f - __ldcg(gp), lg1 = 1.f - __ldcg(gp + 16);
            const uint32_t va = stg + w * 16384 + (wwarp * 16 + (ln & 7) + (ln >> 4) * 8) * 128 + ((((ln >> 3) & 1) ^ (ln & 7)) << 4);
#pragma unroll
            for (int i = 0; i < 8; i++) ldmatrix_x4_t((va ^ ((i & 3) * 32)) + (i >> 2) * 8192, vo[i]);
            const bool m0 = c2 > g, m1 = c2 + 1 > g, first = mt + wwarp == 0;
            const uint32_t mk = (m0 ? 0xffffu : 0u) | (m1 ? 0xffff0000u : 0u);
#pragma unroll
            for (int h = 0; h < 4; h++) {
                float s[3][4] = {};
#pragma unroll
                for (int k = 0; k < 2; k++) {
                    const int i = h * 8 + k * 4, j = h * 4 + k * 2;
                    mma_16816(s[0], qf[i], qf[i + 1], qf[i + 2], qf[i + 3], pk[32 + j], pk[33 + j]);
                    mma_16816(s[1], qf[i], qf[i + 1], qf[i + 2], qf[i + 3], pk[j], pk[j + 1]);
                    mma_16816(s[2], qf[i], qf[i + 1], qf[i + 2], qf[i + 3], pk[16 + j], pk[17 + j]);
                }
                if (first) s[0][0] = s[0][1] = -INFINITY;
                float u0 = m0 ? s[0][0] : s[1][0], u1 = m1 ? s[0][1] : s[1][1], v0 = m0 ? s[1][2] : s[2][2], v1 = m1 ? s[1][3] : s[2][3];
                float mu = fmaxf(u0, u1), mv = fmaxf(v0, v1);
                mu = fmaxf(mu, __shfl_xor_sync(0xffffffffu, mu, 1)); mv = fmaxf(mv, __shfl_xor_sync(0xffffffffu, mv, 1));
                mu = fmaxf(mu, __shfl_xor_sync(0xffffffffu, mu, 2)); mv = fmaxf(mv, __shfl_xor_sync(0xffffffffu, mv, 2));
                mu *= -cs; mv *= -cs;
                u0 = ex2(fmaf(u0, cs, mu)); u1 = ex2(fmaf(u1, cs, mu)); v0 = ex2(fmaf(v0, cs, mv)); v1 = ex2(fmaf(v1, cs, mv));
                float lu = u0 + u1, lv = v0 + v1;
                lu += __shfl_xor_sync(0xffffffffu, lu, 1); lv += __shfl_xor_sync(0xffffffffu, lv, 1);
                lu += __shfl_xor_sync(0xffffffffu, lu, 2); lv += __shfl_xor_sync(0xffffffffu, lv, 2);
                const float su = lg0 * rcp(lu), sv = lg1 * rcp(lv);
                const uint32_t pu = pack_bf16(u0 * su, u1 * su), pv = pack_bf16(v0 * sv, v1 * sv);
#pragma unroll
                for (int d = 0; d < 2; d++) {
                    const uint32_t (&vv)[4] = vo[h * 2 + d];
                    float oa[4] = {}, ob[4] = {};
                    mma_16816(oa, pk[48 + h * 4 + d * 2], pk[49 + h * 4 + d * 2], vv[0], vv[1], pu & mk, pu & ~mk);
                    mma_16816(ob, vv[0], vv[1], vv[2], vv[3], pv & mk, pv & ~mk);
                    qf[h * 8 + d * 4] = pack_bf16(oa[0], oa[1]); qf[h * 8 + d * 4 + 1] = pack_bf16(ob[0], ob[1]);
                    qf[h * 8 + d * 4 + 2] = pack_bf16(oa[2], oa[3]); qf[h * 8 + d * 4 + 3] = pack_bf16(ob[2], ob[3]);
                }
            }
#pragma unroll
            for (int i = 0; i < 32; i++) pk[i] = qf[i];
            named_sync(3 + w, 128);
        };
        auto pack_half = [&](const float (&acc)[64], const int OFF, float scale) INL {
#pragma unroll
            for (int i = 0; i < 32; i++) pk[OFF + i] = pack_bf16(acc[2 * i] * scale, acc[2 * i + 1] * scale);
        };
        auto gemm_run = [&]() INL {
                float acc0[64], acc1[64];
#pragma unroll
                for (int i = 0; i < 64; i++) pk[i] = 0;
#pragma unroll
                for (int j = 0; j < 4; j++) asm volatile("xor.b32 %0, %1, %2;" : "=r"(slot4[j]) : "r"(slot_a), "r"(j << 5));
                const uint32_t dA = desc_lo(base + w * 8192, 0), dB = desc_lo(base + 16384, 8192);
                const uint32_t gh_a = desc_hi(), gh_b = desc_hi();
                auto wait_full = [&](int st) INL { mbar_wait_hot(gfull + st * 8, gph); };
                auto release = [&](int st) INL { arrive_pair(gempty + st * 8); };
                bool pend = false;
                auto kstep = [&](auto st_, const int Q, bool ending = false) INL {
                    constexpr int st = decltype(st_)::v, OA = st * (G_STAGE >> 4);
                    const bool held = st == 2 && ending && w;
                    if (st == 2 && __builtin_expect(held, 0)) {
                        wg_wait<0>();
                        release(1);
                        named_sync(6, 256);
                    }
                    wait_full(st);
                    wg_fence();
                    wgmma_ss_n256<OA, OA>(acc0, acc1, dA, dB, gh_a, gh_b);
                    wg_commit();
                    wg_wait<1>();
                    arrive_pair(gempty + ((st + 3) & 3) * 8, !held);
                    wg_fence();
                    wgmma_ss_n256<OA + 2, OA + 128>(acc0, acc1, dA, dB, gh_a, gh_b);
                    wgmma_ss_n256<OA + 4, OA + 256>(acc0, acc1, dA, dB, gh_a, gh_b);
                    if (st == 3) named_arrive_if(ending && !w, 6, 256);
                    wgmma_ss_n256<OA + 6, OA + 384>(acc0, acc1, dA, dB, gh_a, gh_b);
                    wg_commit();
                    if (Q >= 0) { stage_quarter(Q); signal(Q); }
                    KTRACE(w);
                };
                wait_full(0);
                GTRACE(w);
                while (true) {
                    wg_fence();
                    wgmma_ss_n256_init(acc0, acc1, dA, dB, gh_a, gh_b);
                    wgmma_ss_n256<2, 128>(acc0, acc1, dA, dB, gh_a, gh_b);
                    wgmma_ss_n256<4, 256>(acc0, acc1, dA, dB, gh_a, gh_b);
                    wgmma_ss_n256<6, 384>(acc0, acc1, dA, dB, gh_a, gh_b);
                    wg_commit();
                    KTRACE(w);
                    const int cur = job;
                    const bool is_o = cur >= (T_O << 12), unit2 = (cur >> 6) == 3;
                    const int tail = o_tail(cur);
                    int lim = is_o ? o_head(cur) + tail : (cur < 256 ? 16 : 8);
                    int left = unit2 ? 11 : lim - (is_o ? O_STAGGER + 1 : 1);
                    bool imp = unit2;
                    next_job();
                    if (__builtin_expect(unit2, 0)) { if (tid == TRACE_TID) PTRACE(4); unit_export(cur); if (tid == TRACE_TID) PTRACE(5); }
                    if (pend) {
                        kstep(IC<1>{}, 0);
                        kstep(IC<2>{}, -1);
                        kstep(IC<3>{}, 1);
                        GTRACE(w);
                        gph ^= 1;
                        kstep(IC<0>{}, -1);
                        kstep(IC<1>{}, 2);
                        kstep(IC<2>{}, 3, left == 7);
                        kstep(IC<3>{}, -1, left == 7);
                        GTRACE(w);
                        gph ^= 1;
                        left -= 7;
                        if (left > 0) { kstep(IC<0>{}, -1); left--; }
                    }
                    int last_st = 3;
#pragma unroll 1
                    while (left > 0) {
                        auto ends = [&]() INL -> bool {
                            if (__builtin_expect(--left > 0, 1)) return false;
                            if (is_o) {
                                const uint32_t v = uniform(o_state(olim, lim - tail));
                                const int n = (v >> 1) + ((v & 1) ? 0 : tail);
                                left = n - lim; lim = n;
                            }
                            return left == 0;
                        };
                        kstep(IC<1>{}, -1);
                        if (ends()) { last_st = 1; break; }
                        kstep(IC<2>{}, -1, left == 2 && !is_o && !imp);
                        if (ends()) { last_st = 2; break; }
                        kstep(IC<3>{}, -1, left == 1 && !is_o && !imp);
                        GTRACE(w);
                        gph ^= 1;
                        if (ends()) {
                            if (!imp) break;
                            if (tid == TRACE_TID) PTRACE(6);
                            unit_import(cur);
                            if (tid == TRACE_TID) PTRACE(7);
                            imp = false; left = 4;
                        }
                        kstep(IC<0>{}, -1);
                        if (ends()) { last_st = 0; break; }
                    }
                    if (is_o) {
                        if (w) {
                            wg_wait<0>();
                            release(last_st);
                            named_sync(6, 256);
                        }
#pragma unroll 1
                        for (int i = 1; i <= O_STAGGER; i++) {
                            const int st = (last_st + i) & 3;
                            if (i > 1 && st == 0) gph ^= 1;
                            wait_full(st);
                            const uint32_t a = dA + st * (G_STAGE >> 4), b = dB + st * (G_STAGE >> 4);
                            wg_fence();
                            wgmma_ss_n256<0, 0>(acc0, acc1, a, b, gh_a, gh_b);
                            wgmma_ss_n256<2, 128>(acc0, acc1, a, b, gh_a, gh_b);
                            wgmma_ss_n256<4, 256>(acc0, acc1, a, b, gh_a, gh_b);
                            wgmma_ss_n256<6, 384>(acc0, acc1, a, b, gh_a, gh_b);
                            wg_commit();
                            named_arrive_if(!w && i == O_STAGGER, 6, 256);
                            wg_wait<1>();
                            arrive_pair(gempty + last_st * 8, i == 1 && !w);
                        }
                        slot_wait(1);
                        wg_wait<0>();
                        fence_regs(acc0);
                        fence_regs(acc1);
                        auto put = [&](const float (&acc)[64], const int Q, int off) INL {
#pragma unroll
                            for (int j = 0; j < 4; j++) {
                                const float* o = acc + Q * 32 + j * 8;
                                stmatrix_x4(slot4[j] + off, pack_bf16(o[0], o[1]), pack_bf16(o[2], o[3]), pack_bf16(o[4], o[5]), pack_bf16(o[6], o[7]));
                            }
                        };
                        put(acc0, 0, 0);
                        signal(0);
                        put(acc0, 1, 8192);
                        signal(1);
                        put(acc1, 0, -OFF_STG - w * 8192);
                        put(acc1, 1, G_STAGE - OFF_STG - w * 8192);
                        __syncwarp();
                        warp_arrive(tfull + w * 8);
#pragma unroll
                        for (int i = 1; i <= O_STAGGER; i++) release((last_st + i) & 3);
                        GTRACE(w);
#pragma unroll
                        for (int i = 0; i < 64; i++) O[i] = 0.f;
                        break;
                    }
                    if (tid == 128 && !is_o) PTRACE(12);
                    ptrans = unit2;
                    if (tid == TRACE_TID && unit2) PTRACE(1);
                    named_arrive_if(w && job >= (T_A << 12), 1, TURN_THREADS);
                    wg_wait<0>();
                    fence_regs(acc0);
                    fence_regs(acc1);
                    release(3);
                    if (tid == TRACE_TID && unit2) PTRACE(2);
                    if (__builtin_expect(unit2, 0)) { unit_attend(acc0, cur); if (tid == TRACE_TID) PTRACE(3); }
                    else if (__builtin_expect((cur >> 6) == 2, 0)) pack_k(acc0);
                    else if (cur < 128) pack_half(acc0, 0, 1.f);
                    else pack_half(acc0, 0, K_SCALE);
                    if (job >= (T_A << 12)) {
                        stage_pair();
                        signal_both();
#pragma unroll
                        for (int i = 0; i < 64; i++) asm volatile("mov.b32 %0, %1;" : "=f"(O[i]) : "f"(acc1[i]));
                        break;
                    }
                    pack_half(acc1, 32, 1.f);
                    fence_regs(pk);
                    wait_full(0);
                    pend = (cur >> 6) != 2;
                }
        };
        setup_wait();
#pragma unroll 1
        while (true) {
        gemm_run();
        if (job < 0) break;
        if (tid == 128) PTRACE(11);
        GTRACE(w);
        {
            {
                sph ^= 1;
                uint32_t step = ~0u, ajob = ~0u;
                const uint32_t dh_a = desc_hi(), dh_b = desc_hi(), dh_v = desc_hi();
                const int r0 = w * 64 + wwarp * 16 + (lane >> 2);
                float S[64];
                uint32_t P[32] = {};
                fence_regs(P);
                float m0 = 0.f, m1 = 0.f, l0 = 0.25f, l1 = 0.25f, g0 = 1.f, g1 = 1.f, e0 = 0.f, e1 = 0.f;
                constexpr float SUM_MAX = 1.1529215e18f;
                float sum_max = SUM_MAX;
                float sum_min = (lane & 3) == 0 ? 8.6736174e-19f : -1.f;
                asm volatile("" : "+f"(sum_min));
                int rem = 0;
                int maskrem = 0;
                uint32_t starts = 1;
                auto issue_S = [&]() INL {
                    const uint32_t da = desc_lo(base + OFF_Q0 + w * 8192, 0) + (ajob & 1) * ((OFF_Q1 - OFF_Q0) >> 4);
                    const uint32_t db = desc_lo(base + OFF_K0, 0) + (step & 1) * ((OFF_K1 - OFF_K0) >> 4);
                    wg_fence();
                    wgmma_ss_n128_init<0, 0, 0>(S, da, db, dh_a, dh_b);
                    wgmma_ss_n128_tb0<2, 2>(S, da, db, 1, dh_a, dh_b);
                    wgmma_ss_n128_tb0<4, 4>(S, da, db, 1, dh_a, dh_b);
                    wgmma_ss_n128_tb0<6, 6>(S, da, db, 1, dh_a, dh_b);
                    wgmma_ss_n128_tb0<1024, 1024>(S, da, db, 1, dh_a, dh_b);
                    wgmma_ss_n128_tb0<1026, 1026>(S, da, db, 1, dh_a, dh_b);
                    wgmma_ss_n128_tb0<1028, 1028>(S, da, db, 1, dh_a, dh_b);
                    wgmma_ss_n128_tb0<1030, 1030>(S, da, db, 1, dh_a, dh_b);
                    wg_commit();
                };
                auto issue_PV = [&](uint32_t t, int pass) INL {
                    const uint32_t db = desc_lo(base + OFF_V0, 16384) + (t & 1) * ((OFF_V1 - OFF_V0) >> 4);
                    mbar_wait_hot(vfull + (t & 1) * 8, (t >> 1) & 1);
                    wg_fence();
                    wgmma_rs_n128_tb1<0>(O, P[0], P[1], P[2], P[3], db, !(starts & 2), dh_v);
                    wgmma_rs_n128_tb1<128>(O, P[4], P[5], P[6], P[7], db, 1, dh_v);
                    wgmma_rs_n128_tb1<256>(O, P[8], P[9], P[10], P[11], db, 1, dh_v);
                    wgmma_rs_n128_tb1<384>(O, P[12], P[13], P[14], P[15], db, 1, dh_v);
                    if (pass) named_arrive(pass, TURN_THREADS);
                    wgmma_rs_n128_tb1<512>(O, P[16], P[17], P[18], P[19], db, 1, dh_v);
                    wgmma_rs_n128_tb1<640>(O, P[20], P[21], P[22], P[23], db, 1, dh_v);
                    wgmma_rs_n128_tb1<768>(O, P[24], P[25], P[26], P[27], db, 1, dh_v);
                    wgmma_rs_n128_tb1<896>(O, P[28], P[29], P[30], P[31], db, 1, dh_v);
                    wg_commit();
                };
                auto pv_done = [&](uint32_t t) INL {
                    wg_wait<0>();
                    fence_regs(O);
                    arrive_pair(vempty + (t & 1) * 8, t != ~0u);
                };
                auto row_max = [&](float& a0, float& a1) INL {
                    a0 = fmaxf(S[0], S[1]); a1 = fmaxf(S[2], S[3]);
#pragma unroll
                    for (int j = 1; j < 16; j++) {
                        a0 = fmaxf(a0, fmaxf(S[j * 4], S[j * 4 + 1]));
                        a1 = fmaxf(a1, fmaxf(S[j * 4 + 2], S[j * 4 + 3]));
                    }
                    a0 = fmaxf(a0, __shfl_xor_sync(0xffffffffu, a0, 1));
                    a1 = fmaxf(a1, __shfl_xor_sync(0xffffffffu, a1, 1));
                    a0 = fmaxf(a0, __shfl_xor_sync(0xffffffffu, a0, 2));
                    a1 = fmaxf(a1, __shfl_xor_sync(0xffffffffu, a1, 2));
                };
                auto mask_diag = [&]() INL {
                    const int d = (r0 & 63) - (lane & 3) * 2;
                    auto mask_block = [&](const int J0) INL {
                        bool up0 = false, up1 = false;
#pragma unroll
                        for (int j = 0; j < 8; j++) {
                            const bool c0 = j * 8 > d, c1 = j * 8 + 1 > d;
                            if (c0) S[(J0 + j) * 4] = -INFINITY;
                            if (c1) S[(J0 + j) * 4 + 1] = -INFINITY;
                            if (up0) S[(J0 + j) * 4 + 2] = -INFINITY;
                            if (up1) S[(J0 + j) * 4 + 3] = -INFINITY;
                            up0 = c0; up1 = c1;
                        }
                    };
                    if (w) {
                        mask_block(8);
                    } else {
                        mask_block(0);
#pragma unroll
                        for (int i = 32; i < 64; i++) S[i] = -INFINITY;
                    }
                };
                auto exp_part = [&](float& t0, float& t1, const int J0, const int J1, const bool SUB) INL {
#pragma unroll
                    for (int j = J0; j < J1; j++) {
                        const float e0 = ex2(SUB ? S[j * 4] - m0 : S[j * 4]), e1 = ex2(SUB ? S[j * 4 + 1] - m0 : S[j * 4 + 1]);
                        const float e2 = ex2(SUB ? S[j * 4 + 2] - m1 : S[j * 4 + 2]), e3 = ex2(SUB ? S[j * 4 + 3] - m1 : S[j * 4 + 3]);
                        t0 = (j ? t0 : l0) + (e0 + e1);
                        t1 = (j ? t1 : l1) + (e2 + e3);
                        P[j * 2] = pack_bf16(e0, e1);
                        P[j * 2 + 1] = pack_bf16(e2, e3);
                    }
                };
                auto exp_head = [&](float& t0, float& t1, auto j1_) INL {
                    constexpr int J1 = decltype(j1_)::v;
                    float E[J1 * 4];
#pragma unroll
                    for (int j = 0; j < J1; j++) {
#pragma unroll
                        for (int e = 0; e < 4; e++) E[j * 4 + e] = ex2(S[j * 4 + e]);
                        t0 = (j ? t0 : l0) + (E[j * 4] + E[j * 4 + 1]);
                        t1 = (j ? t1 : l1) + (E[j * 4 + 2] + E[j * 4 + 3]);
                    }
                    order_after(t0 + t1, bars + 508);
                    pv_done(step - 1);
                    fence_regs(P);
                    fence_regs(S);
                    fence_regs(E);
#pragma unroll
                    for (int i = 0; i < J1 * 2; i++) P[i] = pack_bf16(E[i * 2], E[i * 2 + 1]);
                };
                auto close_job = [&]() INL {
                    l0 += __shfl_xor_sync(0xffffffffu, l0, 1); l1 += __shfl_xor_sync(0xffffffffu, l1, 1);
                    l0 += __shfl_xor_sync(0xffffffffu, l0, 2); l1 += __shfl_xor_sync(0xffffffffu, l1, 2);
                    e0 = g0 * rcp(l0); e1 = g1 * rcp(l1);
                };
                auto put_O = [&]() INL {
                    mbar_wait_hot(sempty + (w * 2 + 1) * 8, sph ^ 1);
                    uint32_t a[4];
#pragma unroll
                    for (int j = 0; j < 4; j++) asm volatile("xor.b32 %0, %1, %2;" : "=r"(a[j]) : "r"(slot_a), "r"(j << 5));
                    const uint32_t h0 = pack_bf16(e0, e0), h1 = pack_bf16(e1, e1);
#pragma unroll
                    for (int q = 0; q < 8; q++) {
                        const float* o = O + q * 8;
                        stmatrix_x4(a[q & 3] + (q >> 2) * 8192, mul_bf16x2(pack_bf16(o[0], o[1]), h0), mul_bf16x2(pack_bf16(o[2], o[3]), h1),
                                    mul_bf16x2(pack_bf16(o[4], o[5]), h0), mul_bf16x2(pack_bf16(o[6], o[7]), h1));
                    }
                    sph ^= 1;
                    signal_both();
                };
                auto exp_plain = [&](float& t0, float& t1) INL {
                    exp_head(t0, t1, IC<6>{});
                    exp_part(t0, t1, 6, 16, false);
                    fence_regs(P);
                };
                auto exp_diag = [&](float& t0, float& t1) INL {
                    const int d = warp - 4, dd = (r0 & 7) - (int)(slot_a >> 6 & 6);
                    auto tri = [&](const int B) INL {
                        if (0 > dd) S[8 * B] = S[8 * B + 6] = -INFINITY;
                        if (1 > dd) S[8 * B + 1] = S[8 * B + 7] = -INFINITY;
                        S[8 * B + 4] = S[8 * B + 5] = -INFINITY;
                        asm volatile("" ::: "memory");
                    };
                    auto blocks = [&](const int B) INL {
                        auto zero = [&](const int B0) INL {
#pragma unroll
                            for (int i = 4 * B0; i < 4 * B + 12; i++) P[i] = 0;
                            asm volatile("" ::: "memory");
                        };
                        auto block = [&](const int B0) INL { exp_part(t0, t1, 2 * B0, 2 * B0 + 2, false); asm volatile("" ::: "memory"); };
                        if (d < B) zero(B);
                        else {
                            block(B);
                            if (d < B + 1) zero(B + 1);
                            else {
                                block(B + 1);
                                if (d < B + 2) zero(B + 2); else block(B + 2);
                            }
                        }
                    };
                    if (d > 3) {
                        if (d < 6) { if (d == 4) tri(4); else tri(5); } else { if (d == 6) tri(6); else tri(7); }
                        exp_head(t0, t1, IC<5>{});
                        exp_part(t0, t1, 5, 10, false);
                        blocks(5);
                    } else {
                        if (d < 2) { if (d == 0) tri(0); else tri(1); } else { if (d == 2) tri(2); else tri(3); }
                        exp_head(t0, t1, IC<2>{});
#pragma unroll
                        for (int i = 16; i < 32; i++) P[i] = 0;
                        blocks(1);
                    }
                    fence_regs(P);
                };
                auto unsafe_tile = [&](float t0, float t1) INL -> bool {
                    const bool unsafe = !(t0 + t1 <= sum_max) | !(fminf(t0, t1) >= sum_min);
                    return __any_sync(0xffffffffu, unsafe);
                };
                auto redo_tile = [&](float& t0, float& t1, bool fresh) INL {
                    wg_wait<0>();
                    fence_regs(O);
                    if (rem == maskrem) mask_diag();
                    float a0, a1;
                    row_max(a0, a1);
                    if (!fresh) { a0 = fmaxf(a0, m0); a1 = fmaxf(a1, m1); }
                    const float c0 = fresh ? 1.f : ex2(m0 - a0), c1 = fresh ? 1.f : ex2(m1 - a1);
                    m0 = a0; m1 = a1; sum_max = -1.f;
                    l0 *= c0; l1 *= c1;
#pragma unroll
                    for (int j = 0; j < 16; j++) { O[j * 4] *= c0; O[j * 4 + 1] *= c0; O[j * 4 + 2] *= c1; O[j * 4 + 3] *= c1; }
                    exp_part(t0, t1, 0, 16, true);
                };
                auto finish = [&]() INL {
                    if (starts & 2) put_O();
                    named_sync(1 + w, TURN_THREADS);
                    TRACE_MARK(0, w, step + 1);
                    issue_PV(step, w == 0 ? 2 : 0);
                    close_job();
                    pv_done(step);
                    put_O();
                };
                int njob;
                auto open_job = [&]() INL {
                    ajob++; rem = (job & 15) + 1; maskrem = (job & 512) ? 0 : job & 15;
                    njob = jobs[jb + 1];
                };
                auto do_step = [&]() INL -> bool {
                    float t0, t1;
                    const bool fresh = starts & 1, pending = starts & 2;
                    rem--; step++;
                    named_sync(1 + w, TURN_THREADS);
                    TRACE_MARK(0, w, step);
                    issue_S();
                    uint32_t ob[18];
#pragma unroll
                    for (int i = 0; i < 18; i++) asm volatile("" : "=r"(ob[i]));
                    if (__builtin_expect(pending || fresh, 0)) {
                        if (pending) {
                            const uint32_t h0 = pack_bf16(e0, e0), h1 = pack_bf16(e1, e1);
                            mbar_wait_hot(sempty + (w * 2 + 1) * 8, sph ^ 1);
#pragma unroll
                            for (int q = 0; q < 4; q++) {
                                const float* o = O + q * 8;
                                uint32_t a;
                                asm volatile("xor.b32 %0, %1, %2;" : "=r"(a) : "r"(slot_a), "r"(q << 5));
                                stmatrix_x4(a, mul_bf16x2(pack_bf16(o[0], o[1]), h0), mul_bf16x2(pack_bf16(o[2], o[3]), h1),
                                            mul_bf16x2(pack_bf16(o[4], o[5]), h0), mul_bf16x2(pack_bf16(o[6], o[7]), h1));
                            }
#pragma unroll
                            for (int i = 0; i < 16; i++) ob[i] = pack_bf16(O[32 + 2 * i], O[33 + 2 * i]);
                            ob[16] = h0; ob[17] = h1;
                            fence_regs(ob);
                        }
                        if (fresh) {
                            close_job();
                            g0 = __ldcg(g_gate + (job & 15) * 128 + r0); g1 = __ldcg(g_gate + (job & 15) * 128 + r0 + 8);
                            l0 = 0.f; l1 = 0.f; m0 = 0.f; m1 = 0.f; sum_max = SUM_MAX;
                            if (step == 0) {
                                wg_fence();
                                wg_commit();
                                named_arrive(2 - w, TURN_THREADS);
                                goto issued;
                            }
                        }
                    }
                    issue_PV(step - 1, 2 - w);
                    if (__builtin_expect(pending, 0)) {
#pragma unroll
                        for (int q = 0; q < 4; q++) {
                            uint32_t a;
                            asm volatile("xor.b32 %0, %1, %2;" : "=r"(a) : "r"(slot_a), "r"(q << 5));
                            stmatrix_x4(a + 8192, mul_bf16x2(ob[q * 4], ob[16]), mul_bf16x2(ob[q * 4 + 1], ob[17]),
                                        mul_bf16x2(ob[q * 4 + 2], ob[16]), mul_bf16x2(ob[q * 4 + 3], ob[17]));
                        }
                        sph ^= 1;
                        signal_both();
                    }
                issued:
                    starts = (starts << 1 & 2) | (rem == 0);
                    TRACE_MARK(1, w, step);
                    wg_wait<1>();
                    fence_regs(S);
                    arrive_pair(kempty + (step & 1) * 8);
                    TRACE_MARK(2, w, step);
                    warp_arrive(qempty + (ajob & 1) * 8, rem == 0);
                    bool bad;
                    if (__builtin_expect(rem != maskrem, 1)) {
                        exp_plain(t0, t1);
                        bad = unsafe_tile(t0, t1);
                        if (__builtin_expect(!bad && rem != 0, 1)) {
                            l0 = t0; l1 = t1;
                            TRACE_MARK(3, w, step);
                            return true;
                        }
                    } else {
                        exp_diag(t0, t1);
                        bad = unsafe_tile(t0, t1);
                    }
                    if (bad) redo_tile(t0, t1, fresh);
                    l0 = t0; l1 = t1;
                    TRACE_MARK(3, w, step);
                    if (rem == 0) {
                        jb++;
                        job = uniform(njob);
                        if ((job >> 12) != T_A) return false;
                        open_job();
                    }
                    return true;
                };
                open_job();
#pragma unroll 1
                while (do_step()) {}
                finish();
            }
        }
        GTRACE(w);
        jb = uniform(jb); job = uniform(job); sph = uniform(sph); gph = uniform(gph);
        if (job < 0) break;
        }
    } else {
        reg_dec<40>();
        if (base & 1023) __trap();
        if (warp == 0) {
            const uint2 r = p.first[blockIdx.x];
            const char* maps = reinterpret_cast<const char*>(&p.amap[0]);
            const CUtensorMap* wm = reinterpret_cast<const CUtensorMap*>(maps + (r.x >> (rank ? 8 : 4) & 0x780));
            const CUtensorMap* am = reinterpret_cast<const CUtensorMap*>(maps + (r.x & 0x780));
            const int wb = rank ? r.y >> 16 : r.y & 0xffff;
            setup_wait();
#pragma unroll 1
            for (int st = 1; st < 4; st++) {
                const uint32_t sa = base + st * G_STAGE;
                load_kstep(sa, sa + 16384 + rank * 16384, gfull + st * 8, G_STAGE, wm, st, wb, am, r.x >> 20, st, 1 + (r.x & 1));
            }
            named_sync(7, 96);
        } else {
            if (warp == 2) {
                const int jl = lane < MAX_JOBS ? p.jobs[blockIdx.x][lane] : -1;
                if (lane <= MAX_JOBS) jobs[lane] = jl;
                if ((jl >> 12) == T_O) *reinterpret_cast<volatile uint32_t*>(smem_raw + OFF_BAR + 504) = 2 * o_head(jl);
                if (lane == 31) *reinterpret_cast<volatile uint32_t*>(smem_raw + OFF_BAR + 528) = 0;
            } else if (warp == 3) {
                if (lane == 31) *reinterpret_cast<ulonglong2*>(smem_raw + OFF_BAR + 512) = make_ulonglong2((uint64_t)g_halo, (uint64_t)g_gate);
                if (lane < MAX_ROUNDS / 2) rounds[lane] = reinterpret_cast<const uint32_t*>(p.rounds[blockIdx.x >> 1])[lane];
            }
            named_arrive_if(warp > 1, 7, 96);
            named_sync(0, 352);
            setup_wait();
        }
        volatile uint32_t* epoch_word = reinterpret_cast<volatile uint32_t*>(smem_raw + OFF_BAR + 532);
        uint32_t epoch1 = 0;
        if (warp > 0) {
        if (warp == 3) { epoch1 = uniform(ld_acquire(g_flags + F_DONE)) / NUM_SMS + 1; if (lane == 0) *epoch_word = epoch1; }
        {
            if (warp == 1 && elect_one()) {
#pragma unroll
                for (int i = 0; i < 7; i++) prefetch_map(&p.amap[0] + i);
            }
            __syncwarp();
            if (warp < 3) __nanosleep(jobs[0] < 256 ? GATE_DELAY_LONG_NS : GATE_DELAY_SHORT_NS);
            if (tid == TRACE_GATE) PTRACE(10);
            float* gate_vals = reinterpret_cast<float*>(smem_raw + OFF_BAR + 576);
            if (warp == 3) {
                if (blockIdx.x == 0) g_flags[F_SPLIT + lane] = g_flags[F_TICKET + lane] = 0;
                named_sync(5, 96);
                if (lane < 16 && blockIdx.x + lane * NUM_SMS < SEQ) g_gate[blockIdx.x + lane * NUM_SMS] = 1.f / (1.f + __expf(-gate_vals[lane]));
                if (tid == TRACE_GATE) PTRACE(9);
                __threadfence();
                __syncwarp();
                if (lane == 0) red_release(g_flags + F_GATE);
            } else {
                const uint32_t bar = gatefull + (warp - 1) * 16;
                auto fetch = [&](int r) INL {
                    if (lane == 0) mbar_expect_tx(bar + (r & 2) * 4, 4096);
                    __syncwarp();
                    if (lane < 2) asm volatile("cp.async.bulk.shared::cluster.global.mbarrier::complete_tx::bytes [%0], [%1], 2048, [%2];"
                                               ::"r"(stg + ((warp - 1) * 8 + r + lane) * 2048), "l"(p.xp + (size_t)min((int)blockIdx.x + ((warp - 1) * 8 + r + lane) * NUM_SMS, SEQ - 1) * DM), "r"(bar + (r & 2) * 4) : "memory");
                };
                fetch(0); fetch(2);
                uint32_t gw[16];
#pragma unroll
                for (int i = 0; i < 4; i++) {
                    const uint4 t = __ldg(reinterpret_cast<const uint4*>(p.gate_w) + i * 32 + lane);
                    gw[i * 4] = t.x; gw[i * 4 + 1] = t.y; gw[i * 4 + 2] = t.z; gw[i * 4 + 3] = t.w;
                }
#pragma unroll 1
                for (int r = 0; r < 8; r += 2) {
                    mbar_wait(bar + (r & 2) * 4, r >> 2);
                    if (r < 4) fetch(r + 4);
                    fence_regs(gw);
                    float acc0 = 0.f, acc1 = 0.f;
                    uint32_t ln;
                    asm volatile("mov.u32 %0, %%laneid;" : "=r"(ln));
#pragma unroll
                    for (int i = 0; i < 4; i++) {
                        const uint4* xr = reinterpret_cast<const uint4*>(smem_raw + OFF_STG + ((warp - 1) * 8 + r) * 2048) + i * 32 + ln;
                        const uint4 a = xr[0], c = xr[128];
                        const uint32_t av[4] = {a.x, a.y, a.z, a.w}, cv[4] = {c.x, c.y, c.z, c.w};
#pragma unroll
                        for (int e = 0; e < 4; e++) {
                            const float lo = __uint_as_float(gw[i * 4 + e] << 16), hi = __uint_as_float(gw[i * 4 + e] & 0xffff0000u);
                            acc0 = fmaf(__uint_as_float(av[e] << 16), lo, acc0);
                            acc1 = fmaf(__uint_as_float(cv[e] << 16), lo, acc1);
                            acc0 = fmaf(__uint_as_float(av[e] & 0xffff0000u), hi, acc0);
                            acc1 = fmaf(__uint_as_float(cv[e] & 0xffff0000u), hi, acc1);
                        }
                    }
                    float t = (lane < 16 ? acc0 : acc1) + __shfl_xor_sync(0xffffffffu, lane < 16 ? acc1 : acc0, 16);
#pragma unroll
                    for (int o = 8; o > 0; o >>= 1) t += __shfl_xor_sync(0xffffffffu, t, o);
                    if ((lane & 15) == 0) gate_vals[(warp - 1) * 8 + r + (lane >> 4)] = t;
                }
                uint32_t t2;
                asm volatile("mov.u32 %0, %%tid.x;" : "=r"(t2));
                warp_arrive2(sempty - 16 + (t2 >> 5) * 16, sempty - 8 + (t2 >> 5) * 16);
                named_arrive(5, 96);
                if (tid == TRACE_GATE) PTRACE(9);
            }
            if (tid == TRACE_GATE) PTRACE(8);
        }
        if (warp < 3) {
            if (elect_one()) {
                const int w = warp - 1;
                uint32_t qn = 0, un = 0;
                prefetch_map(&p.qkv_st); prefetch_map(&p.st_par);
                for (int jb = 0; jb < MAX_JOBS; jb++) {
                    const int job = jobs[jb];
                    if (job < 0) break;
                    const int type = job >> 12, pl = type == T_O ? o_state(otile, 0) >> 1 : job & 0xFFF;
                    const CUtensorMap* map = &p.qkv_st;
                    int nq = 4, mt, ob0, ob1, flag, flag2 = -1;
                    bool par = false;
                    if (type <= T_O) {
                        const int n = pl >> 3;
                        mt = (pl & 7) * 2 + rank;
                        if (type == T_O)  {
                            map = &p.out_st; ob0 = (n & 3) * 4; ob1 = ob0 + 2; flag = -1;
                            for (uint32_t tries = 0; (int32_t)(ld_acquire(g_flags + F_OUT + pl * 2 + rank) - *epoch_word) < 0; tries++) {
                                __nanosleep(300);
                                if (tries > (1u << 22)) __trap();
                            }
                            fence_async_global();
                        }
                        else if (n < 16)  { ob0 = n * 4; ob1 = ob0 + 2; flag = F_Q + n * 32 + mt; flag2 = flag + 16; }
                        else if (n < 24)  {
                            mbar_wait(hout + w * 8, un++ & 1);
                            nq = ob0 = ob1 = 0; flag = F_H + mt * 8 + (n & 7);
                        } else if (n < 32) {
                            par = true; ob0 = 192 + (n & 7) * 2; ob1 = unit_head(n & 7) * 2;
                            flag = F_CTX + mt * 40 + 32 + (n & 7); flag2 = F_Q + ob1 * 8 + mt;
                        } else            { ob0 = n * 2; ob1 = ob0 + 64; flag = F_KV + (n - 32) * 16 + mt; }
                    } else {
                        nq = 2; mt = pl & 15; ob0 = ob1 = ((pl >> 4) & 31) * 2; flag = F_CTX + mt * 40 + ((pl >> 4) & 31);
                    }
                    for (int q = 0; q < nq; q++, qn++) {
                        const uint32_t slot = w * 2 + (qn & 1);
                        const int blk = (q < 2 ? ob0 : ob1) + (q & 1);
                        if (type == T_O && q == 2) {
                            mbar_wait(tfull + w * 8, 0);
                            fence_async_smem();
                            tma_reduce_add_3d(map, base + w * 8192, 0, mt * 128 + w * 64, ob1);
                            tma_reduce_add_3d(map, base + G_STAGE + w * 8192, 0, mt * 128 + w * 64, ob1 + 1);
                            bulk_commit();
                            break;
                        }
                        mbar_wait(sfull + slot * 8, (qn >> 1) & 1);
                        fence_async_smem();
                        if (type == T_O) {
                            tma_reduce_add_3d(map, stg + slot * 8192, 0, mt * 128 + w * 64, blk);
                        } else if (par) {
                            tma_store_par(&p.st_par, stg + slot * 8192, mt * 64, w, blk);
                        } else {
                            tma_store_3d(map, stg + slot * 8192, 0, mt * 128 + w * 64, blk, POL_STREAM);
                        }
                        bulk_commit();
                        if (type == T_O) continue;
                        if (!(q & 1)) continue;
                        bulk_wait_read<1>();
                        mbar_arrive(sempty + (slot ^ 1) * 8);
                        bulk_wait_read<0>();
                        mbar_arrive(sempty + slot * 8);
                    }
                    bulk_wait<0>();
                    END_MARK(jb);
                    if (flag >= 0) {
                        asm volatile("fence.release.gpu;" ::: "memory");
                        red_relaxed(g_flags + flag);
                        if (flag2 >= 0) red_relaxed(g_flags + flag2);
                    }
                }
            }
        } else {
            int jb = 0;
            for (int un = 0; (jobs[jb] >> 12) == T_P; jb++) {
                const int n = jobs[jb] >> 3, mt = (jobs[jb] & 7) * 2 + rank;
                if ((n >> 3) != 3) continue;
                wait_flags<200>(lane == 31 || (lane == 0 && mt > 0), lane == 31 ? F_GATE : F_H + max(mt - 1, 0) * 8 + (n & 7),
                                epoch1 * (lane == 31 ? GATE_COUNT : 2));
                if (lane == 0) mbar_arrive(lready + un * 8);
                un++;
            }
            if ((jobs[jb] >> 12) != T_A) {
                wait_flags<200>(lane == 0, F_GATE, epoch1 * GATE_COUNT);
                if (lane == 0) { mbar_arrive(aready); red_relaxed(g_flags + F_DONE); }
            } else {
                const int jh = jobs[jb] >> 4 & 31, jq = jobs[jb] & 15;
                wait_flags<100>(lane <= jq || lane >= 30, lane == 31 ? F_GATE : (lane == 30 ? F_Q + jh * 16 + jq : F_KV + jh * 16 + (lane & 15)),
                                epoch1 * (lane == 31 ? GATE_COUNT : 2));
                if (lane == 0) { mbar_arrive(aready); red_relaxed(g_flags + F_DONE); }
            int left = 0, nxt = jobs[jb];
            uint32_t ajob = 0;
#pragma unroll 1
            for (uint32_t astep = 0;; astep++) {
                if (left == 0) {
                    if ((nxt >> 12) != T_A) break;
                    left = (nxt & 15) + 1;
                    nxt = jobs[++jb];
                    mbar_wait(qfull + (ajob & 1) * 8, (ajob >> 1) & 1);
                    ajob++;
                }
                left--;
                mbar_wait(kfull + (astep & 1) * 8, (astep >> 1) & 1);
                named_sync(1, TURN_THREADS);
                named_sync(2, TURN_THREADS);
            }
            named_sync(1, TURN_THREADS);
            named_sync(2, TURN_THREADS);
            }
            if (jobs[jb] == (T_O << 12)) {
                mbar_wait(gatefull, 0);
                const int tile = o_state(otile, 0) >> 1;
                uint4* dst = reinterpret_cast<uint4*>(p.out) + ((tile & 7) * 256 + rank * 128) * (DM / 8) + (tile >> 3) * 32 + lane;
#pragma unroll 4
                for (int r = 0; r < 128; r++) {
                    dst[r * (DM / 8)] = make_uint4(0, 0, 0, 0);
                    if ((r & 3) == 3) __nanosleep(CLEAR_GAP_NS);
                }
                __threadfence();
                fence_async_global();
                __syncwarp();
                if (lane == 0) red_release(g_flags + F_OUT + tile * 2 + rank);
            }
        }
        } else {
            uint32_t gph = 1;
            int vrow = 0, vblk = 0;
            bool vsolo = false;
            auto load_kv = [&](uint32_t dst, uint32_t bar, int row, int blk, bool solo) INL {
                load_operand(dst, bar, &p.qkv_ld, &p.qkv_half, row, blk, rank, solo, POL_NORMAL);
            };
            auto load_v = [&](uint32_t t) INL {
                if (t == 0) mbar_wait(gempty + 24, gph);
                mbar_wait(vempty + (t & 1) * 8, ((t >> 1) & 1) ^ 1);
                load_kv(base + ((t & 1) ? OFF_V1 : OFF_V0), vfull + (t & 1) * 8, vrow, vblk, vsolo);
            };
            int jb = __ffs(__ballot_sync(0xffffffffu, lane <= MAX_JOBS && (jobs[min(lane, MAX_JOBS)] >> 12) != T_P)) - 1;
            int cur = uniform(jobs[jb]);
            auto announce = [&](uint32_t word, uint32_t v) INL {
                asm volatile("{\n.reg .pred p;\nsetp.lt.u32 p, %2, 2;\n@p red.relaxed.cluster.shared::cluster.max.u32 [%0], %1;\n}"
                             ::"r"(mapa(word, lane & 1)), "r"(v), "r"(lane) : "memory");
                __syncwarp();
            };
            uint32_t ticket = 0;
            auto draw_ticket = [&](int ojob) INL {
                asm volatile("{\n.reg .pred p;\nsetp.ne.u32 p, %2, 0;\n@p atom.relaxed.gpu.global.inc.u32 %0, [%1], 0x7fffffff;\n}"
                             : "+r"(ticket) : "l"(g_flags + F_TICKET + (ojob >> 5 & 1)), "r"((uint32_t)(rank == 0 && lane == 0)) : "memory");
                __syncwarp();
            };
            int pl = 0;
            uint32_t seen_a = 0, seen_b = 0;
            auto ask_ctx = [&]() INL {
                const uint32_t* f = g_flags + F_CTX + ((pl & 7) * 2 + rank) * 40;
                seen_a = ld_relaxed(f + lane); seen_b = ld_relaxed(f + 32 + (lane & 7));
            };
            auto open_tile = [&](int ojob) INL {
                if (rank == 0) {
                    const uint32_t t = uniform(ticket);
                    announce(otile, 2 * ((ojob & 32) ? 31 - t : t) + 1);
                }
                pl = (ojob & 32) | uniform(o_state(otile, 0) >> 1);
                ask_ctx();
            };
            const uint16_t* recs = reinterpret_cast<const uint16_t*>(rounds);
            uint32_t rec = uniform(recs[0]), nrec = uniform(recs[1]);
            int st0 = 4;
#pragma unroll 1
            for (int r = 2; rec != 0xFFFF; r++) {
                const uint32_t nnrec = recs[r];
                load_round(rec, st0, gph);
                gph ^= 1;
                st0 = 0;
                rec = nrec; nrec = uniform(nnrec);
                if (nrec == 0xFFFF || (rec & 8192)) {
                    if (nrec != 0xFFFF) {
                        prefetch_map(&p.qkv_ld); prefetch_map(&p.qkv_half);
                        if ((cur >> 12) == T_O) { prefetch_map(&p.wo_a); prefetch_map(&p.wo_b); prefetch_map(&p.out_st); }
                    } else if ((cur >> 12) == T_O) {
                        if (rec != 0xFFFF) {
                            mbar_wait(aready, 0);
                            draw_ticket(cur);
                        } else {
                            open_tile(cur);
                        }
                    }
                }
            }
            int nxt = cur;
            uint32_t astep = 0;
            if ((cur >> 12) == T_A) {
            {
                const int jh = cur >> 4 & 31, jq = cur & 15, j0 = (cur & 512) ? 0 : jq;
                mbar_wait(aready, 0);
                fence_async_global();
                mbar_wait(gempty, gph);
                load_operand(base + OFF_Q0, qfull, &p.qkv_ld, &p.qkv_ld, jq * 128, jh * 2, 0, true, POL_STREAM);
                PTRACE(17);
                mbar_wait(gempty + 8, gph);
                load_kv(base + OFF_K0, kfull, j0 * 128, 64 + jh * 2, j0 == jq && (jq & 1));
                PTRACE(16);
            }
            epoch1 = *epoch_word;
            jb++;
            nxt = uniform(jobs[jb]);
            int i = 0;
            uint32_t ajob = 1;
            bool q_issued = false;
#pragma unroll 1
            while (true) {
                const int qt = cur & 15;
                const bool last = i == qt;
                const int j = (cur & 512) ? i : qt - i, blk = (cur >> 4 & 31) * 2;
                const bool solo = j == qt && (qt & 1);
                {
                    const uint32_t sl = astep & 1;
                    if (astep == 0) {
                        mbar_wait(gempty + 16, gph);
                    } else {
                        mbar_wait(kempty + sl * 8, ((astep >> 1) & 1) ^ 1);
                        load_kv(base + (sl ? OFF_K1 : OFF_K0), kfull + sl * 8, j * 128, 64 + blk, solo);
                        if (astep == 1) PTRACE(14);
                        load_v(astep - 1);
                        if (astep == 1) PTRACE(15);
                    }
                }
                vrow = j * 128; vblk = 128 + blk; vsolo = solo;
                astep++;
                if ((nxt >> 12) != T_A) {
                    if (last) break;
                } else if (!q_issued && (last || i == 2 || (i > 2 && i >= qt - 2))) {
                    const int jh = nxt >> 4 & 31, jq = nxt & 15;
                    q_issued = wait_flags(lane <= jq || lane >= 30, lane == 31 ? F_GATE : (lane == 30 ? F_Q + jh * 16 + jq : F_KV + jh * 16 + (lane & 15)),
                                          epoch1 * (lane == 31 ? GATE_COUNT : 2), last);
                    if (q_issued) {
                        mbar_wait(qempty + (ajob & 1) * 8, ((ajob >> 1) & 1) ^ 1);
                        load_operand(base + ((ajob & 1) ? OFF_Q1 : OFF_Q0), qfull + (ajob & 1) * 8, &p.qkv_ld, &p.qkv_ld, jq * 128, jh * 2, 0, true, POL_STREAM);
                    }
                }
                i++;
                if (last) {
                    cur = nxt; jb++; nxt = uniform(jobs[jb]); i = 0; ajob++; q_issued = false;
                    if ((nxt >> 12) == T_O) { prefetch_map(&p.wo_a); prefetch_map(&p.wo_b); prefetch_map(&p.out_st); }
                }
            }
            if (nxt >= 0) draw_ticket(nxt);
            load_v(astep - 1);
            if (nxt >= 0) open_tile(nxt);
            }
            int nks = 0;
            if (nxt >= 0) {
                epoch1 = *epoch_word;
                const int m0 = (pl & 7) * 256 + rank * 128, nb = (pl >> 3 & 3) * 4 + rank * 2, part = pl >> 5 & 1;
                uint32_t ready_a = 0, ready_b = 0;
                uint32_t claim_even = 0, claim_odd = 0;
                const int head = o_head(pl), tail = o_tail(pl);
                int lim = head;
                bool known = false;
#pragma unroll 1
                for (int ks = 0;; ks++) {
                    const int st = ks & 3;
                    if (rank == 0) {
                        auto exchange = [&](uint32_t& claim) INL {
                            if (ks + 1 >= head) {
                                known = (uint32_t)uniform(claim) >= O_FLEX;
                                if (!known) lim = ks + 2;
                                announce(olim, known ? 2 * (lim + tail) + 1 : 2 * lim);
                            }
                            asm volatile("{\n.reg .pred p;\nsetp.ne.u32 p, %2, 0;\n@p atom.relaxed.gpu.global.inc.u32 %0, [%1], 0x7fffffff;\n}"
                                         : "+r"(claim) : "l"(g_flags + F_SPLIT + (pl & 31)), "r"((uint32_t)(!known && lane == 0)) : "memory");
                            __syncwarp();
                        };
                        if (!known && ks + 3 >= head) { if (ks & 1) exchange(claim_odd); else exchange(claim_even); }
                    } else if (!known && ks >= lim) {
                        const uint32_t v = uniform(o_state(olim, ks));
                        known = v & 1;
                        lim = (v >> 1) - (known ? tail : 0);
                    }
                    if (ks >= lim + tail) { nks = ks; break; }
                    if (ks == CLEAR_KS && !part) warp_arrive(gatefull);
                    int acol;
                    if (ks >= lim) acol = (part ? 64 - O_T1 : 200) + ks - lim;
                    else if (part) acol = ks < O_H1 ? O_F0 + ks : O_F0 + 2 * O_H1 + O_FLEX - 1 - ks;
                    else acol = ks < 8 ? 192 + ks : (ks < O_H0 ? ks - 8 : ks - 8 + O_H1);
                    for (uint32_t tries = 0; !(((acol < 192 ? ready_a : ready_b) >> (acol >> 1 & 31)) & 1); tries++) {
                        if (ks | tries) ask_ctx();
                        ready_a = __ballot_sync(0xffffffffu, (int32_t)(seen_a - epoch1 * 2) >= 0);
                        ready_b = __ballot_sync(0xffffffffu, (int32_t)(seen_b - epoch1 * 2) >= 0);
                        fence_acquire();
                        trap_if(tries > (1u << 22));
                    }
                    {
                        const uint32_t sa = base + st * G_STAGE;
                        if (ks < 4 && astep) mbar_wait((ks < 2 ? kempty : vempty) + ((astep - 1) & 1) * 8, ((astep - 1) >> 1) & 1);
                        else mbar_wait(gempty + st * 8, gph);
                        load_kstep(sa, sa + 16384 + rank * 16384, gfull + st * 8, G_STAGE, acol >= 192 ? &p.wo_b : &p.wo_a, acol & 63, nb,
                                   &p.qkv_half, m0, acol, 1);
                    }
                    if (st == 3) gph ^= 1;
                }
            }
            if (lane == 0) {
                if (nxt >= 0) for (int s = 0; s < 4; s++) mbar_wait(gempty + s * 8, gph ^ (s < (nks & 3)));
                else for (uint32_t t = astep; t < astep + 2; t++) {
                    mbar_wait(kempty + (t & 1) * 8, ((t >> 1) & 1) ^ 1);
                    mbar_wait(vempty + (t & 1) * 8, ((t >> 1) & 1) ^ 1);
                }
            }
        }
    }
}

typedef CUresult (*EncodeFn)(CUtensorMap*, CUtensorMapDataType, cuuint32_t, void*, const cuuint64_t*, const cuuint64_t*,
                             const cuuint32_t*, const cuuint32_t*, CUtensorMapInterleave, CUtensorMapSwizzle,
                             CUtensorMapL2promotion, CUtensorMapFloatOOBfill);

void make_map3(EncodeFn enc, CUtensorMap* m, const void* ptr, int rows, int cols, int box_rows, int box_blks, bool blocked = false) {
    cuuint64_t dims[3] = {64, (cuuint64_t)rows, (cuuint64_t)(cols / 64)};
    cuuint64_t strides[2] = {blocked ? 128 : (cuuint64_t)cols * 2, blocked ? (cuuint64_t)rows * 128 : 128};
    cuuint32_t box[3] = {64, (cuuint32_t)box_rows, (cuuint32_t)box_blks};
    cuuint32_t es[3] = {1, 1, 1};
    enc(m, CU_TENSOR_MAP_DATA_TYPE_BFLOAT16, 3, const_cast<void*>(ptr), dims, strides, box, es, CU_TENSOR_MAP_INTERLEAVE_NONE,
        CU_TENSOR_MAP_SWIZZLE_128B, CU_TENSOR_MAP_L2_PROMOTION_L2_256B, CU_TENSOR_MAP_FLOAT_OOB_FILL_NONE);
}

Params h_params;

const int16_t k_jobs[NUM_SMS][MAX_JOBS] = {
    {339,153,217,8890,8339,8802,8311,9042,8405,9008,8551,9134,8677,4128,-1,-1,-1,-1,-1,-1,-1,-1,-1,-1},
    {339,153,217,8891,8338,8803,8310,9043,8404,9009,8550,9135,8676,4128,-1,-1,-1,-1,-1,-1,-1,-1,-1,-1},
    {40,0,307,8888,8289,8720,8259,8854,8539,8898,8627,8998,8655,4128,-1,-1,-1,-1,-1,-1,-1,-1,-1,-1},
    {40,0,307,8889,8288,8721,8258,8855,8538,8899,8626,8999,8654,4128,-1,-1,-1,-1,-1,-1,-1,-1,-1,-1},
    {10,157,221,8706,8269,8820,8457,9006,8687,4128,-1,-1,-1,-1,-1,-1,-1,-1,-1,-1,-1,-1,-1,-1},
    {10,157,221,8707,8268,8821,8456,9007,8686,4128,-1,-1,-1,-1,-1,-1,-1,-1,-1,-1,-1,-1,-1,-1},
    {132,196,296,8730,8333,8940,8503,9082,8697,4128,-1,-1,-1,-1,-1,-1,-1,-1,-1,-1,-1,-1,-1,-1},
    {132,196,296,8731,8332,8941,8502,9083,8696,4128,-1,-1,-1,-1,-1,-1,-1,-1,-1,-1,-1,-1,-1,-1},
    {128,192,8758,8199,8774,8313,9026,8415,9130,8663,4128,-1,-1,-1,-1,-1,-1,-1,-1,-1,-1,-1,-1,-1},
    {128,192,8759,8198,8775,8312,9027,8414,9131,8662,4128,-1,-1,-1,-1,-1,-1,-1,-1,-1,-1,-1,-1,-1},
    {133,197,8742,8369,8704,8285,8768,8543,9022,8601,4128,-1,-1,-1,-1,-1,-1,-1,-1,-1,-1,-1,-1,-1},
    {133,197,8743,8368,8705,8284,8769,8542,9023,8600,4128,-1,-1,-1,-1,-1,-1,-1,-1,-1,-1,-1,-1,-1},
    {131,195,38,8708,8265,8932,8461,8896,8631,9076,8585,4128,-1,-1,-1,-1,-1,-1,-1,-1,-1,-1,-1,-1},
    {131,195,38,8709,8264,8933,8460,8897,8630,9077,8584,4128,-1,-1,-1,-1,-1,-1,-1,-1,-1,-1,-1,-1},
    {137,201,8750,8331,8816,8533,8912,8411,9078,8671,4128,-1,-1,-1,-1,-1,-1,-1,-1,-1,-1,-1,-1,-1},
    {137,201,8751,8330,8817,8532,8913,8410,9079,8670,4128,-1,-1,-1,-1,-1,-1,-1,-1,-1,-1,-1,-1,-1},
    {43,264,440,8744,8201,8858,8417,8954,8483,9016,8649,9152,8691,4128,-1,-1,-1,-1,-1,-1,-1,-1,-1,-1},
    {43,264,440,8745,8200,8859,8416,8955,8482,9017,8648,9153,8690,4128,-1,-1,-1,-1,-1,-1,-1,-1,-1,-1},
    {151,215,8876,8299,8964,8445,9146,8703,4128,-1,-1,-1,-1,-1,-1,-1,-1,-1,-1,-1,-1,-1,-1,-1},
    {151,215,8877,8298,8965,8444,9147,8702,4128,-1,-1,-1,-1,-1,-1,-1,-1,-1,-1,-1,-1,-1,-1,-1},
    {470,5,159,223,8772,8281,8936,8407,9066,8651,4128,-1,-1,-1,-1,-1,-1,-1,-1,-1,-1,-1,-1,-1},
    {470,5,159,223,8773,8280,8937,8406,9067,8650,4128,-1,-1,-1,-1,-1,-1,-1,-1,-1,-1,-1,-1,-1},
    {136,200,444,8760,8275,8848,8477,9040,8525,9148,8681,4128,-1,-1,-1,-1,-1,-1,-1,-1,-1,-1,-1,-1},
    {136,200,444,8761,8274,8849,8476,9041,8524,9149,8680,4128,-1,-1,-1,-1,-1,-1,-1,-1,-1,-1,-1,-1},
    {46,510,462,310,8764,8293,8862,8439,9064,8653,4128,-1,-1,-1,-1,-1,-1,-1,-1,-1,-1,-1,-1,-1},
    {46,510,462,310,8765,8292,8863,8438,9065,8652,4128,-1,-1,-1,-1,-1,-1,-1,-1,-1,-1,-1,-1,-1},
    {145,209,8894,8335,8942,8485,9098,8695,4128,-1,-1,-1,-1,-1,-1,-1,-1,-1,-1,-1,-1,-1,-1,-1},
    {145,209,8895,8334,8943,8484,9099,8694,4128,-1,-1,-1,-1,-1,-1,-1,-1,-1,-1,-1,-1,-1,-1,-1},
    {140,204,8878,8329,8934,8441,9070,8685,4128,-1,-1,-1,-1,-1,-1,-1,-1,-1,-1,-1,-1,-1,-1,-1},
    {140,204,8879,8328,8935,8440,9071,8684,4128,-1,-1,-1,-1,-1,-1,-1,-1,-1,-1,-1,-1,-1,-1,-1},
    {146,210,504,8884,8301,8966,8527,9128,8603,4128,-1,-1,-1,-1,-1,-1,-1,-1,-1,-1,-1,-1,-1,-1},
    {146,210,504,8885,8300,8967,8526,9129,8602,4128,-1,-1,-1,-1,-1,-1,-1,-1,-1,-1,-1,-1,-1,-1},
    {14,6,8868,8245,8806,8267,8938,8547,9000,8611,9108,8643,4128,-1,-1,-1,-1,-1,-1,-1,-1,-1,-1,-1},
    {14,6,8869,8244,8807,8266,8939,8546,9001,8610,9109,8642,4128,-1,-1,-1,-1,-1,-1,-1,-1,-1,-1,-1},
    {144,208,8748,8211,8836,8463,9004,8591,4128,-1,-1,-1,-1,-1,-1,-1,-1,-1,-1,-1,-1,-1,-1,-1},
    {144,208,8749,8210,8837,8462,9005,8590,4128,-1,-1,-1,-1,-1,-1,-1,-1,-1,-1,-1,-1,-1,-1,-1},
    {12,4,8740,8243,8724,8287,8930,8435,8900,8517,9086,8659,4128,-1,-1,-1,-1,-1,-1,-1,-1,-1,-1,-1},
    {12,4,8741,8242,8725,8286,8931,8434,8901,8516,9087,8658,4128,-1,-1,-1,-1,-1,-1,-1,-1,-1,-1,-1},
    {143,207,8866,8353,8752,8205,8830,8409,9056,8561,9140,8581,9104,8679,4128,-1,-1,-1,-1,-1,-1,-1,-1,-1},
    {143,207,8867,8352,8753,8204,8831,8408,9057,8560,9141,8580,9105,8678,4128,-1,-1,-1,-1,-1,-1,-1,-1,-1},
    {147,211,8872,8297,8834,8459,9030,8437,9100,8665,4128,-1,-1,-1,-1,-1,-1,-1,-1,-1,-1,-1,-1,-1},
    {147,211,8873,8296,8835,8458,9031,8436,9101,8664,4128,-1,-1,-1,-1,-1,-1,-1,-1,-1,-1,-1,-1,-1},
    {41,1,8766,8327,8828,8399,9126,8667,4128,-1,-1,-1,-1,-1,-1,-1,-1,-1,-1,-1,-1,-1,-1,-1},
    {41,1,8767,8326,8829,8398,9127,8666,4128,-1,-1,-1,-1,-1,-1,-1,-1,-1,-1,-1,-1,-1,-1,-1},
    {150,214,8882,8223,8832,8473,8980,8413,9094,8669,4128,-1,-1,-1,-1,-1,-1,-1,-1,-1,-1,-1,-1,-1},
    {150,214,8883,8222,8833,8472,8981,8412,9095,8668,4128,-1,-1,-1,-1,-1,-1,-1,-1,-1,-1,-1,-1,-1},
    {141,205,33,8726,8341,8976,8479,9024,8449,9136,8501,9144,8683,4128,-1,-1,-1,-1,-1,-1,-1,-1,-1,-1},
    {141,205,33,8727,8340,8977,8478,9025,8448,9137,8500,9145,8682,4128,-1,-1,-1,-1,-1,-1,-1,-1,-1,-1},
    {277,405,152,216,8718,8475,8902,8403,9150,8661,4128,-1,-1,-1,-1,-1,-1,-1,-1,-1,-1,-1,-1,-1},
    {277,405,152,216,8719,8474,8903,8402,9151,8660,4128,-1,-1,-1,-1,-1,-1,-1,-1,-1,-1,-1,-1,-1},
    {139,203,8886,8203,8856,8433,9032,8393,9080,8599,4128,-1,-1,-1,-1,-1,-1,-1,-1,-1,-1,-1,-1,-1},
    {139,203,8887,8202,8857,8432,9033,8392,9081,8598,4128,-1,-1,-1,-1,-1,-1,-1,-1,-1,-1,-1,-1,-1},
    {149,213,8746,8303,8982,8397,9084,8645,4128,-1,-1,-1,-1,-1,-1,-1,-1,-1,-1,-1,-1,-1,-1,-1},
    {149,213,8747,8302,8983,8396,9085,8644,4128,-1,-1,-1,-1,-1,-1,-1,-1,-1,-1,-1,-1,-1,-1,-1},
    {138,202,8870,8221,8860,8395,9060,8607,4128,-1,-1,-1,-1,-1,-1,-1,-1,-1,-1,-1,-1,-1,-1,-1},
    {138,202,8871,8220,8861,8394,9061,8606,4128,-1,-1,-1,-1,-1,-1,-1,-1,-1,-1,-1,-1,-1,-1,-1},
    {134,198,8738,8225,8728,8283,8962,8541,8992,8499,9074,8609,9124,8595,9184,8693,4128,-1,-1,-1,-1,-1,-1,-1},
    {134,198,8739,8224,8729,8282,8963,8540,8993,8498,9075,8608,9125,8594,9185,8692,4128,-1,-1,-1,-1,-1,-1,-1},
    {142,206,8874,8271,8818,8447,9068,8647,4128,-1,-1,-1,-1,-1,-1,-1,-1,-1,-1,-1,-1,-1,-1,-1},
    {142,206,8875,8270,8819,8446,9069,8646,4128,-1,-1,-1,-1,-1,-1,-1,-1,-1,-1,-1,-1,-1,-1,-1},
    {47,498,506,306,8892,8277,8784,8467,9048,8535,9020,8579,9088,8657,9186,8689,4128,-1,-1,-1,-1,-1,-1,-1},
    {47,498,506,306,8893,8276,8785,8466,9049,8534,9021,8578,9089,8656,9187,8688,4128,-1,-1,-1,-1,-1,-1,-1},
    {148,212,8762,8279,8826,8523,9002,8605,4128,-1,-1,-1,-1,-1,-1,-1,-1,-1,-1,-1,-1,-1,-1,-1},
    {148,212,8763,8278,8827,8522,9003,8604,4128,-1,-1,-1,-1,-1,-1,-1,-1,-1,-1,-1,-1,-1,-1,-1},
    {276,404,268,500,450,490,374,390,430,380,356,412,168,232,9018,8701,-1,-1,-1,-1,-1,-1,-1,-1},
    {276,404,268,500,450,490,374,390,430,380,356,412,168,232,9019,8700,-1,-1,-1,-1,-1,-1,-1,-1},
    {11,403,459,507,329,393,369,377,417,361,433,167,231,9132,8699,-1,-1,-1,-1,-1,-1,-1,-1,-1},
    {11,403,459,507,329,393,369,377,417,361,433,167,231,9133,8698,-1,-1,-1,-1,-1,-1,-1,-1,-1},
    {350,486,502,262,302,334,318,87,52,100,179,243,4096,-1,-1,-1,-1,-1,-1,-1,-1,-1,-1,-1},
    {350,486,502,262,302,334,318,87,52,100,179,243,4096,-1,-1,-1,-1,-1,-1,-1,-1,-1,-1,-1},
    {340,158,222,492,60,108,76,172,236,4096,-1,-1,-1,-1,-1,-1,-1,-1,-1,-1,-1,-1,-1,-1},
    {340,158,222,492,60,108,76,172,236,4096,-1,-1,-1,-1,-1,-1,-1,-1,-1,-1,-1,-1,-1,-1},
    {42,3,35,59,107,360,408,181,245,4096,-1,-1,-1,-1,-1,-1,-1,-1,-1,-1,-1,-1,-1,-1},
    {42,3,35,59,107,360,408,181,245,4096,-1,-1,-1,-1,-1,-1,-1,-1,-1,-1,-1,-1,-1,-1},
    {45,156,220,396,85,109,93,180,244,4096,-1,-1,-1,-1,-1,-1,-1,-1,-1,-1,-1,-1,-1,-1},
    {45,156,220,396,85,109,93,180,244,4096,-1,-1,-1,-1,-1,-1,-1,-1,-1,-1,-1,-1,-1,-1},
    {466,482,266,258,37,69,53,77,183,247,4096,-1,-1,-1,-1,-1,-1,-1,-1,-1,-1,-1,-1,-1},
    {466,482,266,258,37,69,53,77,183,247,4096,-1,-1,-1,-1,-1,-1,-1,-1,-1,-1,-1,-1,-1},
    {471,407,463,442,290,322,314,386,478,382,366,414,182,246,4096,-1,-1,-1,-1,-1,-1,-1,-1,-1},
    {471,407,463,442,290,322,314,386,478,382,366,414,182,246,4096,-1,-1,-1,-1,-1,-1,-1,-1,-1},
    {469,349,485,501,445,333,317,373,477,423,439,415,173,237,4096,-1,-1,-1,-1,-1,-1,-1,-1,-1},
    {469,349,485,501,445,333,317,373,477,423,439,415,173,237,4096,-1,-1,-1,-1,-1,-1,-1,-1,-1},
    {8,269,309,453,449,489,385,425,422,358,92,188,252,4096,-1,-1,-1,-1,-1,-1,-1,-1,-1,-1},
    {8,269,309,453,449,489,385,425,422,358,92,188,252,4096,-1,-1,-1,-1,-1,-1,-1,-1,-1,-1},
    {343,287,487,263,303,455,495,391,51,91,160,224,4096,-1,-1,-1,-1,-1,-1,-1,-1,-1,-1,-1},
    {343,287,487,263,303,455,495,391,51,91,160,224,4096,-1,-1,-1,-1,-1,-1,-1,-1,-1,-1,-1},
    {464,272,480,456,288,488,392,61,379,363,435,176,240,4096,-1,-1,-1,-1,-1,-1,-1,-1,-1,-1},
    {464,272,480,456,288,488,392,61,379,363,435,176,240,4096,-1,-1,-1,-1,-1,-1,-1,-1,-1,-1},
    {336,280,400,256,448,320,312,384,424,416,352,432,472,171,235,4096,-1,-1,-1,-1,-1,-1,-1,-1},
    {336,280,400,256,448,320,312,384,424,416,352,432,472,171,235,4096,-1,-1,-1,-1,-1,-1,-1,-1},
    {337,273,265,155,219,368,376,479,359,102,184,248,4096,-1,-1,-1,-1,-1,-1,-1,-1,-1,-1,-1},
    {337,273,265,155,219,368,376,479,359,102,184,248,4096,-1,-1,-1,-1,-1,-1,-1,-1,-1,-1,-1},
    {468,284,508,260,300,324,332,388,104,72,174,238,4096,-1,-1,-1,-1,-1,-1,-1,-1,-1,-1,-1},
    {468,284,508,260,300,324,332,388,104,72,174,238,4096,-1,-1,-1,-1,-1,-1,-1,-1,-1,-1,-1},
    {338,281,2,34,66,110,78,175,239,4096,-1,-1,-1,-1,-1,-1,-1,-1,-1,-1,-1,-1,-1,-1},
    {338,281,2,34,66,110,78,175,239,4096,-1,-1,-1,-1,-1,-1,-1,-1,-1,-1,-1,-1,-1,-1},
    {130,194,39,63,55,95,103,97,4096,-1,-1,-1,-1,-1,-1,-1,-1,-1,-1,-1,-1,-1,-1,-1},
    {130,194,39,63,55,95,103,97,4096,-1,-1,-1,-1,-1,-1,-1,-1,-1,-1,-1,-1,-1,-1,-1},
    {135,199,454,494,67,83,365,413,191,255,4096,-1,-1,-1,-1,-1,-1,-1,-1,-1,-1,-1,-1,-1},
    {135,199,454,494,67,83,365,413,191,255,4096,-1,-1,-1,-1,-1,-1,-1,-1,-1,-1,-1,-1,-1},
    {348,484,460,308,292,452,316,372,428,420,476,101,187,251,4096,-1,-1,-1,-1,-1,-1,-1,-1,-1},
    {348,484,460,308,292,452,316,372,428,420,476,101,187,251,4096,-1,-1,-1,-1,-1,-1,-1,-1,-1},
    {13,154,218,58,106,74,178,242,4096,-1,-1,-1,-1,-1,-1,-1,-1,-1,-1,-1,-1,-1,-1,-1},
    {13,154,218,58,106,74,178,242,4096,-1,-1,-1,-1,-1,-1,-1,-1,-1,-1,-1,-1,-1,-1,-1},
    {465,481,457,505,289,328,71,111,79,166,230,4096,-1,-1,-1,-1,-1,-1,-1,-1,-1,-1,-1,-1},
    {465,481,457,505,289,328,71,111,79,166,230,4096,-1,-1,-1,-1,-1,-1,-1,-1,-1,-1,-1,-1},
    {44,270,446,294,326,65,81,89,161,225,4096,-1,-1,-1,-1,-1,-1,-1,-1,-1,-1,-1,-1,-1},
    {44,270,446,294,326,65,81,89,161,225,4096,-1,-1,-1,-1,-1,-1,-1,-1,-1,-1,-1,-1,-1},
    {9,511,503,295,327,375,399,381,437,353,409,473,169,233,4096,-1,-1,-1,-1,-1,-1,-1,-1,-1},
    {9,511,503,295,327,375,399,381,437,353,409,473,169,233,4096,-1,-1,-1,-1,-1,-1,-1,-1,-1},
    {347,283,483,259,291,491,331,371,431,383,367,99,186,250,4096,-1,-1,-1,-1,-1,-1,-1,-1,-1},
    {347,283,483,259,291,491,331,371,431,383,367,99,186,250,4096,-1,-1,-1,-1,-1,-1,-1,-1,-1},
    {274,282,458,261,293,493,397,389,429,421,357,75,189,253,4096,-1,-1,-1,-1,-1,-1,-1,-1,-1},
    {274,282,458,261,293,493,397,389,429,421,357,75,189,253,4096,-1,-1,-1,-1,-1,-1,-1,-1,-1},
    {278,286,406,32,64,56,48,88,170,234,4096,-1,-1,-1,-1,-1,-1,-1,-1,-1,-1,-1,-1,-1},
    {278,286,406,32,64,56,48,88,170,234,4096,-1,-1,-1,-1,-1,-1,-1,-1,-1,-1,-1,-1,-1},
    {279,351,271,447,298,330,394,370,426,378,354,434,164,228,4096,-1,-1,-1,-1,-1,-1,-1,-1,-1},
    {279,351,271,447,298,330,394,370,426,378,354,434,164,228,4096,-1,-1,-1,-1,-1,-1,-1,-1,-1},
    {344,345,497,257,297,321,313,82,50,90,98,96,4096,-1,-1,-1,-1,-1,-1,-1,-1,-1,-1,-1},
    {344,345,497,257,297,321,313,82,50,90,98,96,4096,-1,-1,-1,-1,-1,-1,-1,-1,-1,-1,-1},
    {129,193,311,335,319,86,438,364,436,163,227,4096,-1,-1,-1,-1,-1,-1,-1,-1,-1,-1,-1,-1},
    {129,193,311,335,319,86,438,364,436,163,227,4096,-1,-1,-1,-1,-1,-1,-1,-1,-1,-1,-1,-1},
    {341,285,509,461,301,325,398,80,418,362,410,474,177,241,4096,-1,-1,-1,-1,-1,-1,-1,-1,-1},
    {341,285,509,461,301,325,398,80,418,362,410,474,177,241,4096,-1,-1,-1,-1,-1,-1,-1,-1,-1},
    {342,275,267,499,299,451,395,57,49,73,185,249,4096,-1,-1,-1,-1,-1,-1,-1,-1,-1,-1,-1},
    {342,275,267,499,299,451,395,57,49,73,185,249,4096,-1,-1,-1,-1,-1,-1,-1,-1,-1,-1,-1},
    {346,402,496,304,443,323,315,387,427,419,355,411,165,229,4096,-1,-1,-1,-1,-1,-1,-1,-1,-1},
    {346,402,496,304,443,323,315,387,427,419,355,411,165,229,4096,-1,-1,-1,-1,-1,-1,-1,-1,-1},
    {15,401,305,441,70,62,54,94,190,254,4096,-1,-1,-1,-1,-1,-1,-1,-1,-1,-1,-1,-1,-1},
    {15,401,305,441,70,62,54,94,190,254,4096,-1,-1,-1,-1,-1,-1,-1,-1,-1,-1,-1,-1,-1},
    {467,7,36,68,84,105,475,162,226,4096,-1,-1,-1,-1,-1,-1,-1,-1,-1,-1,-1,-1,-1,-1},
    {467,7,36,68,84,105,475,162,226,4096,-1,-1,-1,-1,-1,-1,-1,-1,-1,-1,-1,-1,-1,-1},
};

void build_rounds() {
    for (int c = 0; c < NUM_SMS / 2; c++) {
        const int16_t* jobs = h_params.jobs[2 * c];
        int nr = 0, prev_key = -1, last = 0;
        for (int j = 0; (jobs[j] >> 12) == T_P; j++) {
            const int n = jobs[j] >> 3, a = n >= 32, unit = n >= 16 && n < 32 ? (n >> 3) - 1 : 0, cnt = a ? 2 : 4;
            const int key = (jobs[j] & 7) | a << 3 | (unit > 0) << 4;
            const int wm = n < 16 ? 0 : (n < 32 ? 1 : n >> 4 & 1), col = n < 16 ? n : (n < 32 ? n & 7 : n & 15);
            const bool keep = key == prev_key, final_tile = (jobs[j + 1] >> 12) != T_P;
            const int k0 = keep ? last : 0;
            for (int r = 0; r < cnt; r++) {
                last = (k0 + r) % cnt;
                h_params.rounds[c][nr++] = (uint16_t)((key & 15) | wm << 4 | col << 6 | last << 10 | (keep && r == 0) << 12 | (final_tile && r == 0) << 13 | unit << 14);
            }
            prev_key = key;
        }
        while (nr < MAX_ROUNDS) h_params.rounds[c][nr++] = 0xFFFF;
        {
            const uint32_t rec = h_params.rounds[c][0], col = rec >> 6 & 15, unit = rec >> 14;
            for (uint32_t r = 0; r < 2; r++) {
                uint32_t wm[2], wb[2];
                for (uint32_t h = 0; h < 2; h++) {
                    wm[h] = 2 + ((rec & 8) ? 2 + h : ((rec >> 15) && h ? 0 : rec >> 4 & 1));
                    wb[h] = (rec & 8) ? (col + (rec & 16)) * 2
                                      : (unit == 0 ? col * 4 + h * 2 : (unit == 1 ? 16 + h * 16 + col * 2 : (h ? unit_head(col) : col) * 2));
                }
                const uint32_t am = unit ? 6 : (rec >> 3 & 1), arow = unit ? (rec & 7) * 128 + r * 64 : (rec & 7) * 256 + r * 128;
                h_params.first[2 * c + r] = make_uint2((unit ? 1 : 0) | am << 7 | wm[0] << 11 | wm[1] << 15 | arow << 20, wb[0] | wb[1] << 16);
            }
        }
    }
}

void build_schedule() {
    for (int c = 0; c < NUM_SMS; c++) {
        for (int j = 0; j < MAX_JOBS; j++) h_params.jobs[c][j] = k_jobs[c][j];
    }
    build_rounds();
}

}

extern "C" void kernel_launch(void* const* d_in, const int* in_sizes, int n_in, void* d_out, int out_size) {
    (void)in_sizes; (void)n_in; (void)out_size;
    static EncodeFn enc = nullptr;
    if (!enc) {
        cudaDriverEntryPointQueryResult qr;
        void* fn = nullptr;
        cudaGetDriverEntryPoint("cuTensorMapEncodeTiled", &fn, cudaEnableDefault, &qr);
        enc = (EncodeFn)fn;
        cudaFuncSetAttribute(fused_kernel, cudaFuncAttributeMaxDynamicSharedMemorySize, SMEM_BYTES);
        build_schedule();
    }
    void* qkv;
    cudaGetSymbolAddress(&qkv, g_qkv);
    Params& p = h_params;
    make_map3(enc, &p.amap[0], d_in[0], SEQ, DM, 128, 1);
    make_map3(enc, &p.amap[1], d_in[1], SEQ, DC, 128, 1);
    make_map3(enc, &p.wmap[0], d_in[2], DM, 4096, 64, 2);
    make_map3(enc, &p.wmap[2], d_in[3], DC, 4096, 64, 2);
    make_map3(enc, &p.wmap[3], d_in[4], DC, 4096, 64, 2);
    make_map3(enc, &p.wmap[1], d_in[7], DM, 3072, 64, 2);
    make_map3(enc, &p.wo_a, d_in[5], 4096, DM, 64, 2);
    make_map3(enc, &p.wo_b, d_in[8], DM, DM, 64, 2);
    make_map3(enc, &p.qkv_st, qkv, SEQ, QKV_W, 64, 1, true);
    make_map3(enc, &p.qkv_ld, qkv, SEQ, QKV_W, 128, 2, true);
    make_map3(enc, &p.qkv_half, qkv, SEQ, QKV_W, 128, 1, true);
    {
        cuuint64_t dims[4] = {64, SEQ / 2, 2, QKV_W / 64}, strides[3] = {256, 128, (cuuint64_t)SEQ * 128};
        cuuint32_t box[4] = {64, 64, 1, 1}, es[4] = {1, 1, 1, 1};
        enc(&p.st_par, CU_TENSOR_MAP_DATA_TYPE_BFLOAT16, 4, qkv, dims, strides, box, es, CU_TENSOR_MAP_INTERLEAVE_NONE,
            CU_TENSOR_MAP_SWIZZLE_128B, CU_TENSOR_MAP_L2_PROMOTION_L2_256B, CU_TENSOR_MAP_FLOAT_OOB_FILL_NONE);
        dims[3] = DM / 64; strides[0] = DM * 4; strides[1] = DM * 2; strides[2] = 128; box[2] = 2;
        enc(&p.x_par, CU_TENSOR_MAP_DATA_TYPE_BFLOAT16, 4, d_in[0], dims, strides, box, es, CU_TENSOR_MAP_INTERLEAVE_NONE,
            CU_TENSOR_MAP_SWIZZLE_128B, CU_TENSOR_MAP_L2_PROMOTION_L2_256B, CU_TENSOR_MAP_FLOAT_OOB_FILL_NONE);
    }
    make_map3(enc, &p.out_st, d_out, SEQ, DM, 64, 1);
    p.xp = (const __nv_bfloat16*)d_in[0];
    p.gate_w = (const __nv_bfloat16*)d_in[9];
    p.out = (__nv_bfloat16*)d_out;
    fused_kernel<<<NUM_SMS, 384, SMEM_BYTES, cudaStreamPerThread>>>(p);
}
```

```cpp
#include <cuda_runtime.h>
#include <cuda_bf16.h>
#include <cuda.h>
#include <stdint.h>

#define INL __attribute__((always_inline))

namespace {

constexpr int SEQ = 2048;
constexpr int DM = 1024;
constexpr int DC = 512;
constexpr int QKV_W = 13312;
constexpr int NUM_SMS = 132;
constexpr int GATE_DELAY_SHORT_NS = 1000, GATE_DELAY_LONG_NS = 3000;
constexpr int CLEAR_KS = 44, CLEAR_GAP_NS = 100;
constexpr float K_SCALE = 0.08838834764831845f * 1.4426950408889634f;

__device__ __align__(1024) __nv_bfloat16 g_qkv[(size_t)SEQ * QKV_W];
__device__ float g_gate[SEQ];
__device__ uint4 g_halo[16 * 8 * 2 * 5 * 4 * 32];

constexpr int F_Q = 0;
constexpr int F_KV = 1792;
constexpr int F_H = 768;
constexpr int F_CTX = 960;
constexpr int F_GATE = 1600;
constexpr int F_DONE = 1632;
constexpr int F_SPLIT = 1664;
constexpr int F_TICKET = 1696;
constexpr int F_OUT = 1728;
constexpr int GATE_COUNT = NUM_SMS;
__device__ uint32_t g_flags[2304];

#define END_MARK(slot)
#define TRACE_MARK(k, w, i)
#define GTRACE(w)
#define KTRACE(w)
#define PTRACE(i)
#define TRACE_GATE 32
#define TRACE_TID 128

__device__ __forceinline__ uint32_t smem_u32(const void* p) { return (uint32_t)__cvta_generic_to_shared(p); }
__device__ __forceinline__ void mbar_init(uint32_t bar, uint32_t cnt) {
    asm volatile("mbarrier.init.shared::cta.b64 [%0], %1;" ::"r"(bar), "r"(cnt));
}
__device__ __forceinline__ void mbar_arrive(uint32_t bar) {
    asm volatile("mbarrier.arrive.shared::cta.b64 _, [%0];" ::"r"(bar) : "memory");
}
__device__ __forceinline__ bool elect_one() {
    uint32_t r;
    asm volatile("{\n.reg .pred p;\nelect.sync _|p, 0xffffffff;\nselp.b32 %0, 1, 0, p;\n}" : "=r"(r));
    return r != 0;
}
__device__ __forceinline__ uint32_t mapa(uint32_t addr, uint32_t cta) {
    uint32_t r;
    asm("mapa.shared::cluster.u32 %0, %1, %2;" : "=r"(r) : "r"(addr), "r"(cta));
    return r;
}
__device__ __forceinline__ void warp_arrive(uint32_t bar, bool pred = true) {
    asm volatile("{\n.reg .pred p, q;\nsetp.ne.u32 q, %1, 0;\nelect.sync _|p, 0xffffffff;\nand.pred p, p, q;\n"
                 "@p mbarrier.arrive.shared::cta.b64 _, [%0];\n}" ::"r"(bar), "r"((uint32_t)pred) : "memory");
}
__device__ __forceinline__ void warp_arrive2(uint32_t bar0, uint32_t bar1) {
    asm volatile("{\n.reg .pred p;\nelect.sync _|p, 0xffffffff;\n@p mbarrier.arrive.shared::cta.b64 _, [%0];\n"
                 "@p mbarrier.arrive.shared::cta.b64 _, [%1];\n}" ::"r"(bar0), "r"(bar1) : "memory");
}
__device__ __forceinline__ void warp_arrive_pair(uint32_t bar, uint32_t peer_bar, bool pred = true) {
    asm volatile("{\n.reg .pred p, q;\nsetp.ne.u32 q, %2, 0;\nelect.sync _|p, 0xffffffff;\nand.pred p, p, q;\n"
                 "@p mbarrier.arrive.shared::cluster.b64 _, [%1];\n@p mbarrier.arrive.shared::cta.b64 _, [%0];\n}"
                 ::"r"(bar), "r"(peer_bar), "r"((uint32_t)pred) : "memory");
}
__device__ __forceinline__ void mbar_expect_tx(uint32_t bar, uint32_t bytes) {
    asm volatile("mbarrier.arrive.expect_tx.shared::cta.b64 _, [%0], %1;" ::"r"(bar), "r"(bytes) : "memory");
}
constexpr int WAIT_HINT_NS = 20000, WAIT_TRIES = 200000;
__device__ __forceinline__ void mbar_wait(uint32_t bar, uint32_t parity) {
    asm volatile("{\n.reg .pred p;\n.reg .u32 c;\n"
                 "mbarrier.try_wait.parity.shared::cta.b64 p, [%0], %1;\n@p bra DONE;\nmov.u32 c, 0;\n"
                 "SPIN:\nmbarrier.try_wait.parity.shared::cta.b64 p, [%0], %1, %2;\n@p bra DONE;\n"
                 "add.u32 c, c, 1;\nsetp.lt.u32 p, c, %3;\n@p bra SPIN;\ntrap;\nDONE:\n}"
                 ::"r"(bar), "r"(parity), "n"(WAIT_HINT_NS), "n"(WAIT_TRIES) : "memory");
}
__device__ __forceinline__ void mbar_wait_hot(uint32_t bar, uint32_t parity) {
    asm volatile("{\n.reg .pred p, q;\n.reg .u32 c;\n.reg .u64 z;\nmov.u32 c, 0;\nmov.u64 z, 0;\n"
                 "SPIN:\nmbarrier.try_wait.parity.shared::cta.b64 p, [%0], %1;\n"
                 "add.u32 c, c, 1;\nsetp.lt.and.u32 q, c, 4194304, !p;\n@q bra SPIN;\n@!p st.global.u32 [z], c;\n}"
                 ::"r"(bar), "r"(parity) : "memory");
}
__device__ __forceinline__ void mbar_wait_lean(uint32_t bar, uint32_t parity) {
    asm volatile("{\n.reg .pred p;\n.reg .u32 c;\n"
                 "mbarrier.try_wait.parity.shared::cta.b64 p, [%0], %1;\n@p bra DONE;\nmov.u32 c, 0;\n"
                 "SPIN:\nmbarrier.try_wait.parity.shared::cta.b64 p, [%0], %1;\n@p bra DONE;\n"
                 "add.u32 c, c, 1;\nsetp.lt.u32 p, c, 4194304;\n@p bra SPIN;\ntrap;\nDONE:\n}"
                 ::"r"(bar), "r"(parity) : "memory");
}
constexpr uint64_t POL_STREAM = 0x12F0000000000000ull;
constexpr uint64_t POL_NORMAL = 0x1000000000000000ull;
__device__ __forceinline__ void tma_load_3d(uint32_t dst, const CUtensorMap* map, uint32_t bar, int c0, int c1, int c2, uint64_t pol = POL_NORMAL) {
    asm volatile("cp.async.bulk.tensor.3d.shared::cluster.global.mbarrier::complete_tx::bytes.L2::cache_hint [%0], [%1, {%3, %4, %5}], [%2], %6;"
                 ::"r"(dst), "l"(map), "r"(bar), "r"(c0), "r"(c1), "r"(c2), "l"(pol) : "memory");
}
__device__ __forceinline__ void load_kstep(uint32_t sa, uint32_t sw, uint32_t bar, uint32_t bytes, const CUtensorMap* wmap, int wk, int wblk,
                                           const CUtensorMap* amap, int arow, int kc, uint32_t amode) {
    asm volatile("{\n.reg .pred p, q, r;\n.reg .b32 k;\nelect.sync _|p, 0xffffffff;\nsetp.eq.and.u32 q, %9, 1, p;\nsetp.eq.and.u32 r, %9, 2, p;\nshl.b32 k, %12, 6;\n"
                 "@p mbarrier.arrive.expect_tx.shared::cta.b64 _, [%2], %3;\n"
                 "@p cp.async.bulk.tensor.3d.shared::cluster.global.mbarrier::complete_tx::bytes.multicast::cluster.L2::cache_hint [%1], [%4, {0, k, %5}], [%2], %10, %11;\n"
                 "@q cp.async.bulk.tensor.3d.shared::cluster.global.mbarrier::complete_tx::bytes.L2::cache_hint [%0], [%6, {0, %7, %8}], [%2], %11;\n"
                 "@r cp.async.bulk.tensor.4d.shared::cluster.global.mbarrier::complete_tx::bytes.L2::cache_hint [%0], [%6, {0, %7, 0, %8}], [%2], %11;\n}"
                 ::"r"(sa), "r"(sw), "r"(bar), "r"(bytes), "l"(wmap), "r"(wblk), "l"(amap), "r"(arow), "r"(kc), "r"(amode), "h"((uint16_t)3), "l"(POL_NORMAL), "r"(wk) : "memory");
}
__device__ __forceinline__ void load_operand(uint32_t dst, uint32_t bar, const CUtensorMap* full, const CUtensorMap* half, int row, int blk,
                                             uint32_t rank, bool solo, uint64_t pol) {
    asm volatile("{\n.reg .pred p, q, r;\n.reg .b32 d, b;\nelect.sync _|p, 0xffffffff;\nsetp.ne.and.u32 q, %7, 0, p;\nsetp.eq.and.u32 r, %7, 0, p;\n"
                 "mad.lo.u32 d, %6, 16384, %0;\nadd.u32 b, %5, %6;\n"
                 "@p mbarrier.arrive.expect_tx.shared::cta.b64 _, [%1], 32768;\n"
                 "@q cp.async.bulk.tensor.3d.shared::cluster.global.mbarrier::complete_tx::bytes.L2::cache_hint [%0], [%2, {0, %4, %5}], [%1], %9;\n"
                 "@r cp.async.bulk.tensor.3d.shared::cluster.global.mbarrier::complete_tx::bytes.multicast::cluster.L2::cache_hint [d], [%3, {0, %4, b}], [%1], %8, %9;\n}"
                 ::"r"(dst), "r"(bar), "l"(full), "l"(half), "r"(row), "r"(blk), "r"(rank), "r"((uint32_t)solo), "h"((uint16_t)3), "l"(pol) : "memory");
}
__device__ __forceinline__ void tma_store_par(const CUtensorMap* map, uint32_t src, int pair, int parity, int blk) {
    asm volatile("cp.async.bulk.tensor.4d.global.shared::cta.bulk_group.L2::cache_hint [%0, {0, %2, %3, %4}], [%1], %5;"
                 ::"l"(map), "r"(src), "r"(pair), "r"(parity), "r"(blk), "l"(POL_STREAM) : "memory");
}
__device__ __forceinline__ void tma_store_3d(const CUtensorMap* map, uint32_t src, int c0, int c1, int c2, uint64_t pol) {
    asm volatile("cp.async.bulk.tensor.3d.global.shared::cta.bulk_group.L2::cache_hint [%0, {%2, %3, %4}], [%1], %5;"
                 ::"l"(map), "r"(src), "r"(c0), "r"(c1), "r"(c2), "l"(pol) : "memory");
}
__device__ __forceinline__ void tma_reduce_add_3d(const CUtensorMap* map, uint32_t src, int c0, int c1, int c2) {
    asm volatile("cp.reduce.async.bulk.tensor.3d.global.shared::cta.add.tile.bulk_group [%0, {%2, %3, %4}], [%1];"
                 ::"l"(map), "r"(src), "r"(c0), "r"(c1), "r"(c2) : "memory");
}
__device__ __forceinline__ void bulk_commit() { asm volatile("cp.async.bulk.commit_group;" ::: "memory"); }
template <int N> __device__ __forceinline__ void bulk_wait_read() { asm volatile("cp.async.bulk.wait_group.read %0;" ::"n"(N) : "memory"); }
template <int N> __device__ __forceinline__ void bulk_wait() { asm volatile("cp.async.bulk.wait_group %0;" ::"n"(N) : "memory"); }
__device__ __forceinline__ void fence_async_smem() { asm volatile("fence.proxy.async.shared::cta;" ::: "memory"); }
__device__ __forceinline__ void fence_async_global() { asm volatile("fence.proxy.async.global;" ::: "memory"); }
__device__ __forceinline__ uint32_t ld_acquire(const uint32_t* p) {
    uint32_t v;
    asm volatile("ld.acquire.gpu.global.u32 %0, [%1];" : "=r"(v) : "l"(p) : "memory");
    return v;
}
__device__ __forceinline__ uint32_t ld_relaxed(const uint32_t* p) {
    uint32_t v;
    asm volatile("ld.relaxed.gpu.global.u32 %0, [%1];" : "=r"(v) : "l"(p) : "memory");
    return v;
}
__device__ __forceinline__ void fence_acquire() { asm volatile("fence.acquire.gpu;\nfence.proxy.async.global;" ::: "memory"); }
__device__ __forceinline__ void red_release(uint32_t* p) {
    asm volatile("red.release.gpu.global.add.u32 [%0], 1;" ::"l"(p) : "memory");
}
__device__ __forceinline__ void red_relaxed(uint32_t* p) {
    asm volatile("red.relaxed.gpu.global.add.u32 [%0], 1;" ::"l"(p) : "memory");
}
__device__ __forceinline__ void prefetch_map(const CUtensorMap* map) { asm volatile("prefetch.tensormap [%0];" ::"l"(map) : "memory"); }
__device__ __forceinline__ void trap_if(bool c) { asm volatile("{\n.reg .pred p;\nsetp.ne.u32 p, %0, 0;\n@p trap;\n}" ::"r"((uint32_t)c)); }
__device__ __forceinline__ void setup_arrive() { asm volatile("barrier.cluster.arrive.relaxed.aligned;" ::: "memory"); }
__device__ __forceinline__ void setup_wait() { asm volatile("barrier.cluster.wait.aligned;" ::: "memory"); }
__device__ __forceinline__ uint32_t cluster_rank() { uint32_t r; asm("mov.u32 %0, %%cluster_ctarank;" : "=r"(r)); return r; }
__device__ __forceinline__ void named_sync(int id, int n) { asm volatile("bar.sync %0, %1;" ::"r"(id), "r"(n) : "memory"); }
__device__ __forceinline__ void named_arrive(int id, int n) { asm volatile("bar.arrive %0, %1;" ::"r"(id), "r"(n) : "memory"); }
__device__ __forceinline__ void named_sync_if(bool c, int id, int n) {
    asm volatile("{\n.reg .pred p;\nsetp.ne.u32 p, %0, 0;\n@p bar.sync %1, %2;\n}" ::"r"((uint32_t)c), "r"(id), "r"(n) : "memory");
}
__device__ __forceinline__ void named_arrive_if(bool c, int id, int n) {
    asm volatile("{\n.reg .pred p;\nsetp.ne.u32 p, %0, 0;\n@p bar.arrive %1, %2;\n}" ::"r"((uint32_t)c), "r"(id), "r"(n) : "memory");
}
template <int V> struct IC { static constexpr int v = V; };
template <int N> __device__ __forceinline__ void reg_dec() { asm volatile("setmaxnreg.dec.sync.aligned.u32 %0;" ::"n"(N)); }
template <int N> __device__ __forceinline__ void reg_inc() { asm volatile("setmaxnreg.inc.sync.aligned.u32 %0;" ::"n"(N)); }

__device__ __forceinline__ void wg_fence() { asm volatile("wgmma.fence.sync.aligned;" ::: "memory"); }
__device__ __forceinline__ void wg_commit() { asm volatile("wgmma.commit_group.sync.aligned;" ::: "memory"); }
template <int N> __device__ __forceinline__ void wg_wait() { asm volatile("wgmma.wait_group.sync.aligned %0;" ::"n"(N) : "memory"); }
template <int N> __device__ __forceinline__ void fence_regs(float (&r)[N]) {
#pragma unroll
    for (int i = 0; i < N; i++) asm volatile("" : "+f"(r[i])::"memory");
}
template <int N> __device__ __forceinline__ void fence_regs(uint32_t (&r)[N]) {
#pragma unroll
    for (int i = 0; i < N; i++) asm volatile("" : "+r"(r[i])::"memory");
}
__device__ __forceinline__ uint32_t desc_lo(uint32_t addr, uint32_t lbo) { return ((addr & 0x3FFFF) >> 4) | ((lbo >> 4) << 16); }
__device__ __forceinline__ int uniform(int v) { return __shfl_sync(0xffffffffu, v, 0); }
__device__ __forceinline__ uint32_t pack_bf16(float lo, float hi) {
    uint32_t r;
    asm("cvt.rn.bf16x2.f32 %0, %1, %2;" : "=r"(r) : "f"(hi), "f"(lo));
    return r;
}
__device__ __forceinline__ uint32_t mul_bf16x2(uint32_t x, uint32_t y) {
    uint32_t r;
    asm("mul.rn.bf16x2 %0, %1, %2;" : "=r"(r) : "r"(x), "r"(y));
    return r;
}
__device__ __forceinline__ void stmatrix_x4(uint32_t addr, uint32_t r0, uint32_t r1, uint32_t r2, uint32_t r3) {
    asm volatile("stmatrix.sync.aligned.m8n8.x4.shared.b16 [%0], {%1, %2, %3, %4};"
                 ::"r"(addr), "r"(r0), "r"(r1), "r"(r2), "r"(r3) : "memory");
}
__device__ __forceinline__ void stmatrix_x4(uint32_t addr, uint32_t r0, uint32_t r1, uint32_t r2, uint32_t r3, bool trans) {
    asm volatile("{\n.reg .pred p;\nsetp.ne.u32 p, %5, 0;\n@p stmatrix.sync.aligned.m8n8.x4.trans.shared.b16 [%0], {%1, %2, %3, %4};\n"
                 "@!p stmatrix.sync.aligned.m8n8.x4.shared.b16 [%0], {%1, %2, %3, %4};\n}"
                 ::"r"(addr), "r"(r0), "r"(r1), "r"(r2), "r"(r3), "r"((uint32_t)trans) : "memory");
}
__device__ __forceinline__ void ldmatrix_x4_t(uint32_t addr, uint32_t (&r)[4]) {
    asm volatile("ldmatrix.sync.aligned.m8n8.x4.trans.shared.b16 {%0, %1, %2, %3}, [%4];"
                 : "=r"(r[0]), "=r"(r[1]), "=r"(r[2]), "=r"(r[3]) : "r"(addr) : "memory");
}
__device__ __forceinline__ void mma_16816(float (&d)[4], uint32_t a0, uint32_t a1, uint32_t a2, uint32_t a3, uint32_t b0, uint32_t b1) {
    asm("mma.sync.aligned.m16n8k16.row.col.f32.bf16.bf16.f32 {%0, %1, %2, %3}, {%4, %5, %6, %7}, {%8, %9}, {%0, %1, %2, %3};"
        : "+f"(d[0]), "+f"(d[1]), "+f"(d[2]), "+f"(d[3]) : "r"(a0), "r"(a1), "r"(a2), "r"(a3), "r"(b0), "r"(b1));
}
__device__ __forceinline__ void order_after(float v, uint32_t scratch) {
    asm volatile("{\n.reg .pred p;\nsetp.gt.f32 p, %0, 0f70000000;\n@p st.shared.u32 [%1], 0;\n}" ::"f"(v), "r"(scratch) : "memory");
}
__device__ __forceinline__ float rcp(float x) { float y; asm("rcp.approx.ftz.f32 %0, %1;" : "=f"(y) : "f"(x)); return y; }
__device__ __forceinline__ float ex2(float x) { float y; asm("ex2.approx.ftz.f32 %0, %1;" : "=f"(y) : "f"(x)); return y; }

template <int OA, int OB>
__device__ __forceinline__ void wgmma_ss_n256(float (&d0)[64], float (&d1)[64], uint32_t da, uint32_t db, uint32_t ha, uint32_t hb) {
    asm volatile("{\n.reg .b32 ta, tb;\n.reg .b64 da, db;\nadd.u32 ta, %128, %130;\nadd.u32 tb, %129, %131;\n"
        "mov.b64 da, {ta, %132};\nmov.b64 db, {tb, %133};\n"
        "wgmma.mma_async.sync.aligned.m64n256k16.f32.bf16.bf16 {%0, %1, %2, %3, %4, %5, %6, %7, %8, %9, %10, %11, %12, %13, %14, %15, %16, %17, %18, %19, %20, %21, %22, %23, %24, %25, %26, %27, %28, %29, %30, %31, %32, %33, %34, %35, %36, %37, %38, %39, %40, %41, %42, %43, %44, %45, %46, %47, %48, %49, %50, %51, %52, %53, %54, %55, %56, %57, %58, %59, %60, %61, %62, %63, %64, %65, %66, %67, %68, %69, %70, %71, %72, %73, %74, %75, %76, %77, %78, %79, %80, %81, %82, %83, %84, %85, %86, %87, %88, %89, %90, %91, %92, %93, %94, %95, %96, %97, %98, %99, %100, %101, %102, %103, %104, %105, %106, %107, %108, %109, %110, %111, %112, %113, %114, %115, %116, %117, %118, %119, %120, %121, %122, %123, %124, %125, %126, %127}, da, db, 1, 1, 1, 0, 1;\n}\n"
        : "+f"(d0[0]), "+f"(d0[1]), "+f"(d0[2]), "+f"(d0[3]), "+f"(d0[4]), "+f"(d0[5]), "+f"(d0[6]), "+f"(d0[7]), "+f"(d0[8]), "+f"(d0[9]), "+f"(d0[10]), "+f"(d0[11]), "+f"(d0[12]), "+f"(d0[13]), "+f"(d0[14]), "+f"(d0[15]), "+f"(d0[16]), "+f"(d0[17]), "+f"(d0[18]), "+f"(d0[19]), "+f"(d0[20]), "+f"(d0[21]), "+f"(d0[22]), "+f"(d0[23]), "+f"(d0[24]), "+f"(d0[25]), "+f"(d0[26]), "+f"(d0[27]), "+f"(d0[28]), "+f"(d0[29]), "+f"(d0[30]), "+f"(d0[31]), "+f"(d0[32]), "+f"(d0[33]), "+f"(d0[34]), "+f"(d0[35]), "+f"(d0[36]), "+f"(d0[37]), "+f"(d0[38]), "+f"(d0[39]), "+f"(d0[40]), "+f"(d0[41]), "+f"(d0[42]), "+f"(d0[43]), "+f"(d0[44]), "+f"(d0[45]), "+f"(d0[46]), "+f"(d0[47]), "+f"(d0[48]), "+f"(d0[49]), "+f"(d0[50]), "+f"(d0[51]), "+f"(d0[52]), "+f"(d0[53]), "+f"(d0[54]), "+f"(d0[55]), "+f"(d0[56]), "+f"(d0[57]), "+f"(d0[58]), "+f"(d0[59]), "+f"(d0[60]), "+f"(d0[61]), "+f"(d0[62]), "+f"(d0[63]), "+f"(d1[0]), "+f"(d1[1]), "+f"(d1[2]), "+f"(d1[3]), "+f"(d1[4]), "+f"(d1[5]), "+f"(d1[6]), "+f"(d1[7]), "+f"(d1[8]), "+f"(d1[9]), "+f"(d1[10]), "+f"(d1[11]), "+f"(d1[12]), "+f"(d1[13]), "+f"(d1[14]), "+f"(d1[15]), "+f"(d1[16]), "+f"(d1[17]), "+f"(d1[18]), "+f"(d1[19]), "+f"(d1[20]), "+f"(d1[21]), "+f"(d1[22]), "+f"(d1[23]), "+f"(d1[24]), "+f"(d1[25]), "+f"(d1[26]), "+f"(d1[27]), "+f"(d1[28]), "+f"(d1[29]), "+f"(d1[30]), "+f"(d1[31]), "+f"(d1[32]), "+f"(d1[33]), "+f"(d1[34]), "+f"(d1[35]), "+f"(d1[36]), "+f"(d1[37]), "+f"(d1[38]), "+f"(d1[39]), "+f"(d1[40]), "+f"(d1[41]), "+f"(d1[42]), "+f"(d1[43]), "+f"(d1[44]), "+f"(d1[45]), "+f"(d1[46]), "+f"(d1[47]), "+f"(d1[48]), "+f"(d1[49]), "+f"(d1[50]), "+f"(d1[51]), "+f"(d1[52]), "+f"(d1[53]), "+f"(d1[54]), "+f"(d1[55]), "+f"(d1[56]), "+f"(d1[57]), "+f"(d1[58]), "+f"(d1[59]), "+f"(d1[60]), "+f"(d1[61]), "+f"(d1[62]), "+f"(d1[63])
        : "r"(da), "r"(db), "n"(OA), "n"(OB), "r"(ha), "r"(hb));
}

__device__ __forceinline__ void wgmma_ss_n256_init(float (&d0)[64], float (&d1)[64], uint32_t da, uint32_t db, uint32_t ha, uint32_t hb) {
    asm volatile("{\n.reg .b64 da, db;\n"
        "mov.b64 da, {%128, %130};\nmov.b64 db, {%129, %131};\n"
        "wgmma.mma_async.sync.aligned.m64n256k16.f32.bf16.bf16 {%0, %1, %2, %3, %4, %5, %6, %7, %8, %9, %10, %11, %12, %13, %14, %15, %16, %17, %18, %19, %20, %21, %22, %23, %24, %25, %26, %27, %28, %29, %30, %31, %32, %33, %34, %35, %36, %37, %38, %39, %40, %41, %42, %43, %44, %45, %46, %47, %48, %49, %50, %51, %52, %53, %54, %55, %56, %57, %58, %59, %60, %61, %62, %63, %64, %65, %66, %67, %68, %69, %70, %71, %72, %73, %74, %75, %76, %77, %78, %79, %80, %81, %82, %83, %84, %85, %86, %87, %88, %89, %90, %91, %92, %93, %94, %95, %96, %97, %98, %99, %100, %101, %102, %103, %104, %105, %106, %107, %108, %109, %110, %111, %112, %113, %114, %115, %116, %117, %118, %119, %120, %121, %122, %123, %124, %125, %126, %127}, da, db, 0, 1, 1, 0, 1;\n}\n"
        : "=f"(d0[0]), "=f"(d0[1]), "=f"(d0[2]), "=f"(d0[3]), "=f"(d0[4]), "=f"(d0[5]), "=f"(d0[6]), "=f"(d0[7]), "=f"(d0[8]), "=f"(d0[9]), "=f"(d0[10]), "=f"(d0[11]), "=f"(d0[12]), "=f"(d0[13]), "=f"(d0[14]), "=f"(d0[15]), "=f"(d0[16]), "=f"(d0[17]), "=f"(d0[18]), "=f"(d0[19]), "=f"(d0[20]), "=f"(d0[21]), "=f"(d0[22]), "=f"(d0[23]), "=f"(d0[24]), "=f"(d0[25]), "=f"(d0[26]), "=f"(d0[27]), "=f"(d0[28]), "=f"(d0[29]), "=f"(d0[30]), "=f"(d0[31]), "=f"(d0[32]), "=f"(d0[33]), "=f"(d0[34]), "=f"(d0[35]), "=f"(d0[36]), "=f"(d0[37]), "=f"(d0[38]), "=f"(d0[39]), "=f"(d0[40]), "=f"(d0[41]), "=f"(d0[42]), "=f"(d0[43]), "=f"(d0[44]), "=f"(d0[45]), "=f"(d0[46]), "=f"(d0[47]), "=f"(d0[48]), "=f"(d0[49]), "=f"(d0[50]), "=f"(d0[51]), "=f"(d0[52]), "=f"(d0[53]), "=f"(d0[54]), "=f"(d0[55]), "=f"(d0[56]), "=f"(d0[57]), "=f"(d0[58]), "=f"(d0[59]), "=f"(d0[60]), "=f"(d0[61]), "=f"(d0[62]), "=f"(d0[63]), "=f"(d1[0]), "=f"(d1[1]), "=f"(d1[2]), "=f"(d1[3]), "=f"(d1[4]), "=f"(d1[5]), "=f"(d1[6]), "=f"(d1[7]), "=f"(d1[8]), "=f"(d1[9]), "=f"(d1[10]), "=f"(d1[11]), "=f"(d1[12]), "=f"(d1[13]), "=f"(d1[14]), "=f"(d1[15]), "=f"(d1[16]), "=f"(d1[17]), "=f"(d1[18]), "=f"(d1[19]), "=f"(d1[20]), "=f"(d1[21]), "=f"(d1[22]), "=f"(d1[23]), "=f"(d1[24]), "=f"(d1[25]), "=f"(d1[26]), "=f"(d1[27]), "=f"(d1[28]), "=f"(d1[29]), "=f"(d1[30]), "=f"(d1[31]), "=f"(d1[32]), "=f"(d1[33]), "=f"(d1[34]), "=f"(d1[35]), "=f"(d1[36]), "=f"(d1[37]), "=f"(d1[38]), "=f"(d1[39]), "=f"(d1[40]), "=f"(d1[41]), "=f"(d1[42]), "=f"(d1[43]), "=f"(d1[44]), "=f"(d1[45]), "=f"(d1[46]), "=f"(d1[47]), "=f"(d1[48]), "=f"(d1[49]), "=f"(d1[50]), "=f"(d1[51]), "=f"(d1[52]), "=f"(d1[53]), "=f"(d1[54]), "=f"(d1[55]), "=f"(d1[56]), "=f"(d1[57]), "=f"(d1[58]), "=f"(d1[59]), "=f"(d1[60]), "=f"(d1[61]), "=f"(d1[62]), "=f"(d1[63])
        : "r"(da), "r"(db), "r"(ha), "r"(hb));
}

template <int TB, int OA, int OB>
__device__ __forceinline__ void wgmma_ss_n128_init(float (&d)[64], uint32_t da, uint32_t db, uint32_t ha, uint32_t hb) {
    asm volatile("{\n.reg .b32 ta, tb;\n.reg .b64 da, db;\nadd.u32 ta, %64, %66;\nadd.u32 tb, %65, %67;\n"
        "mov.b64 da, {ta, %69};\nmov.b64 db, {tb, %70};\n"
        "wgmma.mma_async.sync.aligned.m64n128k16.f32.bf16.bf16 {%0, %1, %2, %3, %4, %5, %6, %7, %8, %9, %10, %11, %12, %13, %14, %15, %16, %17, %18, %19, %20, %21, %22, %23, %24, %25, %26, %27, %28, %29, %30, %31, %32, %33, %34, %35, %36, %37, %38, %39, %40, %41, %42, %43, %44, %45, %46, %47, %48, %49, %50, %51, %52, %53, %54, %55, %56, %57, %58, %59, %60, %61, %62, %63}, da, db, 0, 1, 1, 0, %68;\n}\n"
        : "=f"(d[0]), "=f"(d[1]), "=f"(d[2]), "=f"(d[3]), "=f"(d[4]), "=f"(d[5]), "=f"(d[6]), "=f"(d[7]), "=f"(d[8]), "=f"(d[9]), "=f"(d[10]), "=f"(d[11]), "=f"(d[12]), "=f"(d[13]), "=f"(d[14]), "=f"(d[15]), "=f"(d[16]), "=f"(d[17]), "=f"(d[18]), "=f"(d[19]), "=f"(d[20]), "=f"(d[21]), "=f"(d[22]), "=f"(d[23]), "=f"(d[24]), "=f"(d[25]), "=f"(d[26]), "=f"(d[27]), "=f"(d[28]), "=f"(d[29]), "=f"(d[30]), "=f"(d[31]), "=f"(d[32]), "=f"(d[33]), "=f"(d[34]), "=f"(d[35]), "=f"(d[36]), "=f"(d[37]), "=f"(d[38]), "=f"(d[39]), "=f"(d[40]), "=f"(d[41]), "=f"(d[42]), "=f"(d[43]), "=f"(d[44]), "=f"(d[45]), "=f"(d[46]), "=f"(d[47]), "=f"(d[48]), "=f"(d[49]), "=f"(d[50]), "=f"(d[51]), "=f"(d[52]), "=f"(d[53]), "=f"(d[54]), "=f"(d[55]), "=f"(d[56]), "=f"(d[57]), "=f"(d[58]), "=f"(d[59]), "=f"(d[60]), "=f"(d[61]), "=f"(d[62]), "=f"(d[63])
        : "r"(da), "r"(db), "n"(OA), "n"(OB), "n"(TB), "r"(ha), "r"(hb));
}

template <int OA, int OB>
__device__ __forceinline__ void wgmma_ss_n128_tb0(float (&d)[64], uint32_t da, uint32_t db, int scale_d, uint32_t ha, uint32_t hb) {
    asm volatile("{\n.reg .pred p;\n.reg .b32 ta, tb;\n.reg .b64 da, db;\nsetp.ne.b32 p, %66, 0;\nadd.u32 ta, %64, %67;\nadd.u32 tb, %65, %68;\n"
        "mov.b64 da, {ta, %69};\nmov.b64 db, {tb, %70};\n"
        "wgmma.mma_async.sync.aligned.m64n128k16.f32.bf16.bf16 "
        "{%0, %1, %2, %3, %4, %5, %6, %7, %8, %9, %10, %11, %12, %13, %14, %15, %16, %17, %18, %19, %20, %21, %22, %23, %24, %25, %26, %27, %28, %29, %30, %31, %32, %33, %34, %35, %36, %37, %38, %39, %40, %41, %42, %43, %44, %45, %46, %47, %48, %49, %50, %51, %52, %53, %54, %55, %56, %57, %58, %59, %60, %61, %62, %63}, da, db, p, 1, 1, 0, 0;\n}\n"
        : "+f"(d[0]), "+f"(d[1]), "+f"(d[2]), "+f"(d[3]), "+f"(d[4]), "+f"(d[5]), "+f"(d[6]), "+f"(d[7]), "+f"(d[8]), "+f"(d[9]), "+f"(d[10]), "+f"(d[11]), "+f"(d[12]), "+f"(d[13]), "+f"(d[14]), "+f"(d[15]), "+f"(d[16]), "+f"(d[17]), "+f"(d[18]), "+f"(d[19]), "+f"(d[20]), "+f"(d[21]), "+f"(d[22]), "+f"(d[23]), "+f"(d[24]), "+f"(d[25]), "+f"(d[26]), "+f"(d[27]), "+f"(d[28]), "+f"(d[29]), "+f"(d[30]), "+f"(d[31]), "+f"(d[32]), "+f"(d[33]), "+f"(d[34]), "+f"(d[35]), "+f"(d[36]), "+f"(d[37]), "+f"(d[38]), "+f"(d[39]), "+f"(d[40]), "+f"(d[41]), "+f"(d[42]), "+f"(d[43]), "+f"(d[44]), "+f"(d[45]), "+f"(d[46]), "+f"(d[47]), "+f"(d[48]), "+f"(d[49]), "+f"(d[50]), "+f"(d[51]), "+f"(d[52]), "+f"(d[53]), "+f"(d[54]), "+f"(d[55]), "+f"(d[56]), "+f"(d[57]), "+f"(d[58]), "+f"(d[59]), "+f"(d[60]), "+f"(d[61]), "+f"(d[62]), "+f"(d[63])
        : "r"(da), "r"(db), "r"(scale_d), "n"(OA), "n"(OB), "r"(ha), "r"(hb));
}

template <int OB>
__device__ __forceinline__ void wgmma_rs_n128_tb1(float (&d)[64], uint32_t a0, uint32_t a1, uint32_t a2, uint32_t a3, uint32_t db, int scale_d, uint32_t hb) {
    asm volatile("{\n.reg .pred p;\n.reg .b32 tb;\n.reg .b64 db;\nsetp.ne.b32 p, %69, 0;\nadd.u32 tb, %68, %70;\n"
        "mov.b64 db, {tb, %71};\n"
        "wgmma.mma_async.sync.aligned.m64n128k16.f32.bf16.bf16 "
        "{%0, %1, %2, %3, %4, %5, %6, %7, %8, %9, %10, %11, %12, %13, %14, %15, %16, %17, %18, %19, %20, %21, %22, %23, %24, %25, %26, %27, %28, %29, %30, %31, %32, %33, %34, %35, %36, %37, %38, %39, %40, %41, %42, %43, %44, %45, %46, %47, %48, %49, %50, %51, %52, %53, %54, %55, %56, %57, %58, %59, %60, %61, %62, %63}, {%64, %65, %66, %67}, db, p, 1, 1, 1;\n}\n"
        : "+f"(d[0]), "+f"(d[1]), "+f"(d[2]), "+f"(d[3]), "+f"(d[4]), "+f"(d[5]), "+f"(d[6]), "+f"(d[7]), "+f"(d[8]), "+f"(d[9]), "+f"(d[10]), "+f"(d[11]), "+f"(d[12]), "+f"(d[13]), "+f"(d[14]), "+f"(d[15]), "+f"(d[16]), "+f"(d[17]), "+f"(d[18]), "+f"(d[19]), "+f"(d[20]), "+f"(d[21]), "+f"(d[22]), "+f"(d[23]), "+f"(d[24]), "+f"(d[25]), "+f"(d[26]), "+f"(d[27]), "+f"(d[28]), "+f"(d[29]), "+f"(d[30]), "+f"(d[31]), "+f"(d[32]), "+f"(d[33]), "+f"(d[34]), "+f"(d[35]), "+f"(d[36]), "+f"(d[37]), "+f"(d[38]), "+f"(d[39]), "+f"(d[40]), "+f"(d[41]), "+f"(d[42]), "+f"(d[43]), "+f"(d[44]), "+f"(d[45]), "+f"(d[46]), "+f"(d[47]), "+f"(d[48]), "+f"(d[49]), "+f"(d[50]), "+f"(d[51]), "+f"(d[52]), "+f"(d[53]), "+f"(d[54]), "+f"(d[55]), "+f"(d[56]), "+f"(d[57]), "+f"(d[58]), "+f"(d[59]), "+f"(d[60]), "+f"(d[61]), "+f"(d[62]), "+f"(d[63])
        : "r"(a0), "r"(a1), "r"(a2), "r"(a3), "r"(db), "r"(scale_d), "n"(OB), "r"(hb));
}

__device__ __forceinline__ uint32_t stage_addr(uint32_t block, int warp, int lane) {
    return block + (warp * 16 + (lane & 7) + ((lane >> 3) & 1) * 8) * 128 + (((lane >> 4) ^ (lane & 7)) << 4);
}
template <int OFF, int N>
__device__ __forceinline__ void stage_packed_64x64(uint32_t a0, int off, const uint32_t (&v)[N]) {
#pragma unroll
    for (int j = 0; j < 8; j += 2) {
        uint32_t a = a0;
        if (j) asm volatile("xor.b32 %0, %1, %2;" : "=r"(a) : "r"(a0), "r"(j << 4));
        stmatrix_x4(a + off, v[OFF + j * 2], v[OFF + j * 2 + 1], v[OFF + j * 2 + 2], v[OFF + j * 2 + 3]);
    }
}

template <int OFF, int N>
__device__ __forceinline__ void stage_packed_64x64(const uint32_t (&a)[4], int off, const uint32_t (&v)[N]) {
#pragma unroll
    for (int j = 0; j < 4; j++) stmatrix_x4(a[j] + off, v[OFF + j * 4], v[OFF + j * 4 + 1], v[OFF + j * 4 + 2], v[OFF + j * 4 + 3]);
}

template <int OFF, int N>
__device__ __forceinline__ void stage_packed_64x64(const uint32_t (&a)[4], int off, const uint32_t (&v)[N], bool trans) {
#pragma unroll
    for (int j = 0; j < 4; j++) stmatrix_x4(a[j] + off, v[OFF + j * 4], v[OFF + j * 4 + 1], v[OFF + j * 4 + 2], v[OFF + j * 4 + 3], trans);
}

constexpr int MAX_JOBS = 24;
constexpr int MAX_ROUNDS = 44;
constexpr int T_P = 0, T_O = 1, T_A = 2;
constexpr int HQ_A = 4, HQ_B = 28;
__host__ __device__ constexpr int unit_head(int g) { return g + (g < 4 ? HQ_A : HQ_B - 4); }
constexpr int G_STAGE = 49152;
constexpr int OFF_Q0 = 0, OFF_K0 = 32768, OFF_Q1 = 65536, OFF_K1 = 98304, OFF_V0 = 131072, OFF_V1 = 163840;
constexpr int OFF_STG = 196608;
constexpr int OFF_BAR = 229376;
constexpr int SMEM_BYTES = OFF_BAR + 640;
constexpr int TURN_THREADS = 288;

struct Params {
    CUtensorMap amap[2];
    CUtensorMap wmap[4];
    CUtensorMap x_par, wo_a, wo_b, qkv_st, qkv_ld, qkv_half, st_par, out_st;
    const __nv_bfloat16* xp;
    const __nv_bfloat16* gate_w;
    __nv_bfloat16* out;
    uint2 first[NUM_SMS];
    int16_t jobs[NUM_SMS][MAX_JOBS];
    uint16_t rounds[NUM_SMS / 2][MAX_ROUNDS];
};

constexpr int O_STAGGER = 4;
constexpr int O_F0 = 35, O_H1 = 5;
constexpr int O_FLEX = 16, O_H0 = O_F0 + 8, O_T0 = 8, O_T1 = 64 - O_F0 - O_FLEX - O_H1;
__device__ __forceinline__ int o_head(int job) { return (job & 32) ? O_H1 : O_H0; }
__device__ __forceinline__ int o_tail(int job) { return (job & 32) ? O_T1 : O_T0; }
__device__ __forceinline__ uint32_t o_state(uint32_t word, int have) {
    uint32_t v;
    asm volatile("{\n.reg .pred p, q;\n.reg .u32 c, t;\nmov.u32 c, 0;\n"
                 "SPIN:\nld.volatile.shared.u32 %0, [%1];\nand.b32 t, %0, 1;\nsetp.ne.u32 q, t, 0;\nsetp.gt.or.u32 p, %0, %2, q;\n@p bra DONE;\n"
                 "add.u32 c, c, 1;\nsetp.lt.u32 q, c, 16777216;\n@q bra SPIN;\ntrap;\nDONE:\n}"
                 : "=r"(v) : "r"(word), "r"(2 * have + 1) : "memory");
    return v;
}

template <class T> __device__ __forceinline__ T* page_ptr(int off) {
    extern __shared__ __align__(1024) uint8_t smem_raw[];
    return *reinterpret_cast<T* volatile*>(smem_raw + OFF_BAR + off);
}
template <int SLEEP_NS = 0>
__device__ __forceinline__ bool wait_flags(bool active, int idx, uint32_t target, bool block = true) {
    for (uint32_t tries = 0;; tries++) {
        const bool ok = !active | ((int32_t)(ld_acquire(g_flags + idx) - target) >= 0);
        if (__all_sync(0xffffffffu, ok)) break;
        if (!block) return false;
        if (SLEEP_NS) __nanosleep(SLEEP_NS);
        trap_if(tries > (1u << 22));
    }
    fence_async_global();
    return true;
}

__global__ void __cluster_dims__(2, 1, 1) __launch_bounds__(384, 1)
fused_kernel(const __grid_constant__ Params p) {
    extern __shared__ __align__(1024) uint8_t smem_raw[];
    const uint32_t base = smem_u32(smem_raw);
    const uint32_t bars = base + OFF_BAR;
    const uint32_t gfull = bars, gempty = bars + 32, sfull = bars + 64, sempty = bars + 96;
    const uint32_t qfull = bars + 128, qempty = bars + 144, kfull = bars + 160, kempty = bars + 176;
    const uint32_t vfull = bars + 192, vempty = bars + 208, lready = bars + 224, hout = bars + 240;
    const uint32_t tfull = bars + 256, aready = bars + 272, gatefull = bars + 280;
    const uint32_t otile = bars + 528;
    const uint32_t olim = bars + 504;
    const uint32_t stg = base + OFF_STG;
    uint32_t* rounds = reinterpret_cast<uint32_t*>(smem_raw + OFF_BAR + 416);
    const uint32_t rank = cluster_rank();
    int* jobs = reinterpret_cast<int*>(smem_raw + OFF_BAR + 312);
    auto w_map = [&](uint32_t rec, uint32_t half) INL { return &p.wmap[(rec & 8) ? 2 + half : ((rec >> 15) && half ? 0 : rec >> 4 & 1)]; };
    auto w_blk = [&](uint32_t rec, uint32_t half) INL -> int {
        const int col = rec >> 6 & 15;
        if (rec & 8) return (col + (rec & 16)) * 2;
        return rec >> 14 == 0 ? col * 4 + half * 2 : (rec >> 14 == 1 ? 16 + half * 16 + col * 2 : (half ? unit_head(col) : col) * 2);
    };
    auto load_round = [&](uint32_t rec, int st0, uint32_t parity) INL {
        const CUtensorMap* wm = w_map(rec, rank);
        const CUtensorMap* am = rec >> 14 ? &p.x_par : &p.amap[rec >> 3 & 1];
        const int wb = w_blk(rec, rank), kc0 = (rec >> 10 & 3) * 4, arow = ((rec & 7) * 256 + rank * 128) >> (rec >> 14 ? 1 : 0);
        const uint32_t bytes = (rec & 4096) ? G_STAGE - 16384 : G_STAGE, amode = (rec & 4096) ? 0 : (rec >> 14 ? 2 : 1);
#pragma unroll 1
        for (int st = st0; st < 4; st++) {
            const uint32_t sa = base + st * G_STAGE;
            mbar_wait(gempty + st * 8, parity);
            load_kstep(sa, sa + 16384 + rank * 16384, gfull + st * 8, bytes, wm, kc0 + st, wb, am, arow, kc0 + st, amode);
        }
    };
    if (threadIdx.x < 32) {
        if (elect_one()) {
            const uint2 r = p.first[blockIdx.x];
            mbar_init(gfull, 1);
            fence_async_smem();
            const char* maps;
            asm("mov.b64 %0, %1;" : "=l"(maps) : "l"(&p.amap[0]));
            asm volatile("{\n.reg .pred q;\nsetp.eq.u32 q, %8, 0;\n"
                         "mbarrier.arrive.expect_tx.shared::cta.b64 _, [%1], 49152;\n"
                         "cp.async.bulk.tensor.3d.shared::cluster.global.mbarrier::complete_tx::bytes.L2::cache_hint [%9], [%3, {0, 0, %6}], [%1], %11;\n"
                         "cp.async.bulk.tensor.3d.shared::cluster.global.mbarrier::complete_tx::bytes.L2::cache_hint [%10], [%4, {0, 0, %7}], [%1], %11;\n"
                         "@q cp.async.bulk.tensor.3d.shared::cluster.global.mbarrier::complete_tx::bytes.L2::cache_hint [%0], [%2, {0, %5, 0}], [%1], %11;\n"
                         "@!q cp.async.bulk.tensor.4d.shared::cluster.global.mbarrier::complete_tx::bytes.L2::cache_hint [%0], [%2, {0, %5, 0, 0}], [%1], %11;\n}"
                         ::"r"(base), "r"(gfull), "l"(maps + (r.x & 0x780)), "l"(maps + (r.x >> 4 & 0x780)), "l"(maps + (r.x >> 8 & 0x780)),
                           "r"(r.x >> 20), "r"(r.y & 0xffff), "r"(r.y >> 16), "r"(r.x & 1), "r"(base + 16384), "r"(base + 32768), "l"(POL_NORMAL) : "memory");
            asm volatile("fence.mbarrier_init.release.cluster;" ::: "memory");
        }
        __syncwarp();
    }
    const int tid = threadIdx.x, warp = uniform(tid >> 5), lane = tid & 31, wg = warp >> 2;
    if (warp == 1) {
        if (elect_one()) {
#pragma unroll
            for (int i = 1; i < 39; i++)
                mbar_init(bars + i * 8, (0x0CC000F0ull >> i & 1) ? 16 : ((0x300000F00ull >> i & 1) ? 4 : ((0xC0000ull >> i & 1) ? 8 : 1)));
            asm volatile("fence.mbarrier_init.release.cluster;" ::: "memory");
            fence_async_smem();
        }
        __syncwarp();
    }
    setup_arrive();
    if (warp > 3) {
        reg_inc<232>();
        named_sync(0, 352);
        const int w = wg - 1, wwarp = warp & 3;
        const uint32_t slot_a = stage_addr(stg + w * 16384, wwarp, lane);
        const uint32_t bars_peer = uniform(mapa(bars, rank ^ 1));
        auto arrive_pair = [&](uint32_t bar, bool pred = true) INL { warp_arrive_pair(bar, bars_peer + (bar - bars), pred); };
        uint32_t gph = 0;
        uint32_t sph = 1;
        int jb = 0;
        int job = uniform(jobs[0]);
        auto next_job = [&]() INL { jb++; job = uniform(jobs[jb]); };
        auto desc_hi = [&]() INL {
            uint32_t v;
            asm volatile("ld.volatile.shared.b32 %0, [%1];\nadd.u32 %0, %0, 0x40000041;" : "=r"(v) : "r"(bars + 312 + MAX_JOBS * 4));
            return (uint32_t)uniform(v);
        };
        auto slot_wait = [&](int q) INL { mbar_wait(sempty + (w * 2 + (q & 1)) * 8, (q >> 1) ^ sph ^ 1); };
        auto signal = [&](int q) INL {
            __syncwarp();
            warp_arrive(sfull + (w * 2 + (q & 1)) * 8);
        };
        uint32_t pk[64];
        float O[64];
        uint32_t slot4[4];
        bool ptrans = false;
        auto stage_quarter = [&](const int Q) INL {
            slot_wait(Q);
            if (Q == 0) stage_packed_64x64<0>(slot4, 0, pk, ptrans);
            if (Q == 1) stage_packed_64x64<16>(slot4, 8192, pk, ptrans);
            if (Q == 2) stage_packed_64x64<32>(slot4, 0, pk);
            if (Q == 3) stage_packed_64x64<48>(slot4, 8192, pk);
        };
        auto stage_pair = [&]() INL {
            slot_wait(1);
            stage_packed_64x64<0>(slot4, 0, pk, ptrans);
            stage_packed_64x64<16>(slot4, 8192, pk, ptrans);
        };
        auto signal_both = [&]() INL {
            __syncwarp();
            warp_arrive2(sfull + w * 16, sfull + w * 16 + 8);
        };
        uint32_t un = 0;
        auto lane_id = [&]() INL { uint32_t ln; asm volatile("mov.u32 %0, %%laneid;" : "=r"(ln)); return ln; };
        auto v_addr = [&](uint32_t ln) INL { return stg + w * 16384 + (wwarp * 16 + (ln & 7)) * 128 + (((ln >> 3) ^ (ln & 7)) << 4); };
        auto v_off = [&](uint32_t a, const int h) INL { return (a ^ ((h & 1) * 64)) + (h >> 1) * 8192; };
        auto halo_ptr = [&](int mt, int g, int slot, uint32_t ln) INL { return page_ptr<uint4>(512) + (((mt * 8 + g) * 2 + w) * 5 + slot) * 128 + ln; };
        auto pack_k = [&](const float (&acc)[64]) INL {
#pragma unroll
            for (int j = 0; j < 16; j++) { pk[j] = pack_bf16(acc[4 * j], acc[4 * j + 1]); pk[16 + j] = pack_bf16(acc[4 * j + 2], acc[4 * j + 3]); }
        };
        auto unit_export = [&](int cur) INL {
            const uint32_t ln = lane_id();
            uint4* dst = halo_ptr((cur & 7) * 2 + rank, cur >> 3 & 7, wwarp, ln);
            slot_wait(1);
            stage_packed_64x64<32>(slot4, 0, pk);
            stage_packed_64x64<48>(slot4, 8192, pk);
#pragma unroll
            for (int h = 0; h < 4; h++) __stcg(dst + h * 32, make_uint4(pk[16 + h * 4], pk[17 + h * 4], pk[18 + h * 4], pk[19 + h * 4]));
            __syncwarp();
            if (wwarp == 3) {
                const uint32_t va = v_addr(ln) + 1024;
#pragma unroll
                for (int h = 0; h < 4; h++) {
                    uint32_t t[4];
                    ldmatrix_x4_t(v_off(va, h), t);
                    pk[32 + h * 4] = t[0]; pk[33 + h * 4] = t[1]; pk[34 + h * 4] = t[2]; pk[35 + h * 4] = t[3];
                }
#pragma unroll
                for (int h = 0; h < 4; h++) __stcg(dst + 128 + h * 32, make_uint4(pk[32 + h * 4], pk[33 + h * 4], pk[34 + h * 4], pk[35 + h * 4]));
                __syncwarp();
                warp_arrive(hout + w * 8);
            }
        };
        auto unit_import = [&](int cur) INL {
            const uint32_t ln = lane_id();
            const int mt = (cur & 7) * 2 + rank;
            mbar_wait(lready + un * 8, 0);
            un++;
            const uint4* src = halo_ptr(wwarp ? mt : max(mt - 1, 0), cur >> 3 & 7, (wwarp + 3) & 3, ln);
#pragma unroll
            for (int h = 0; h < 4; h++) {
                const uint4 t = __ldcg(src + h * 32);
                pk[32 + h * 4] = t.x; pk[33 + h * 4] = t.y; pk[34 + h * 4] = t.z; pk[35 + h * 4] = t.w;
            }
            if (wwarp) {
                const uint32_t va = v_addr(ln) - 1024;
#pragma unroll
                for (int h = 0; h < 4; h++) {
                    uint32_t t[4];
                    ldmatrix_x4_t(v_off(va, h), t);
                    pk[48 + h * 4] = t[0]; pk[49 + h * 4] = t[1]; pk[50 + h * 4] = t[2]; pk[51 + h * 4] = t[3];
                }
            } else {
#pragma unroll
                for (int h = 0; h < 4; h++) {
                    const uint4 t = __ldcg(src + 128 + h * 32);
                    pk[48 + h * 4] = t.x; pk[49 + h * 4] = t.y; pk[50 + h * 4] = t.z; pk[51 + h * 4] = t.w;
                }
            }
        };
        auto unit_attend = [&](const float (&q)[64], int cur) INL {
            const float cs = 0.17677669529663687f * 1.4426950408889634f;
            const uint32_t ln = lane_id();
            const int g = ln >> 2, c2 = (ln & 3) * 2, mt = (cur & 7) * 2 + rank;
            uint32_t qf[32], vo[8][4];
#pragma unroll
            for (int i = 0; i < 32; i++) qf[i] = pack_bf16(q[2 * i], q[2 * i + 1]);
            fence_regs(qf);
            const float* gp = page_ptr<float>(520) + mt * 128 + wwarp * 32 + g * 2 + w;
            const float lg0 = 1.f - __ldcg(gp), lg1 = 1.f - __ldcg(gp + 16);
            const uint32_t va = stg + w * 16384 + (wwarp * 16 + (ln & 7) + (ln >> 4) * 8) * 128 + ((((ln >> 3) & 1) ^ (ln & 7)) << 4);
#pragma unroll
            for (int i = 0; i < 8; i++) ldmatrix_x4_t((va ^ ((i & 3) * 32)) + (i >> 2) * 8192, vo[i]);
            const bool m0 = c2 > g, m1 = c2 + 1 > g, first = mt + wwarp == 0;
            const uint32_t mk = (m0 ? 0xffffu : 0u) | (m1 ? 0xffff0000u : 0u);
#pragma unroll
            for (int h = 0; h < 4; h++) {
                float s[3][4] = {};
#pragma unroll
                for (int k = 0; k < 2; k++) {
                    const int i = h * 8 + k * 4, j = h * 4 + k * 2;
                    mma_16816(s[0], qf[i], qf[i + 1], qf[i + 2], qf[i + 3], pk[32 + j], pk[33 + j]);
                    mma_16816(s[1], qf[i], qf[i + 1], qf[i + 2], qf[i + 3], pk[j], pk[j + 1]);
                    mma_16816(s[2], qf[i], qf[i + 1], qf[i + 2], qf[i + 3], pk[16 + j], pk[17 + j]);
                }
                if (first) s[0][0] = s[0][1] = -INFINITY;
                float u0 = m0 ? s[0][0] : s[1][0], u1 = m1 ? s[0][1] : s[1][1], v0 = m0 ? s[1][2] : s[2][2], v1 = m1 ? s[1][3] : s[2][3];
                float mu = fmaxf(u0, u1), mv = fmaxf(v0, v1);
                mu = fmaxf(mu, __shfl_xor_sync(0xffffffffu, mu, 1)); mv = fmaxf(mv, __shfl_xor_sync(0xffffffffu, mv, 1));
                mu = fmaxf(mu, __shfl_xor_sync(0xffffffffu, mu, 2)); mv = fmaxf(mv, __shfl_xor_sync(0xffffffffu, mv, 2));
                mu *= -cs; mv *= -cs;
                u0 = ex2(fmaf(u0, cs, mu)); u1 = ex2(fmaf(u1, cs, mu)); v0 = ex2(fmaf(v0, cs, mv)); v1 = ex2(fmaf(v1, cs, mv));
                float lu = u0 + u1, lv = v0 + v1;
                lu += __shfl_xor_sync(0xffffffffu, lu, 1); lv += __shfl_xor_sync(0xffffffffu, lv, 1);
                lu += __shfl_xor_sync(0xffffffffu, lu, 2); lv += __shfl_xor_sync(0xffffffffu, lv, 2);
                const float su = lg0 * rcp(lu), sv = lg1 * rcp(lv);
                const uint32_t pu = pack_bf16(u0 * su, u1 * su), pv = pack_bf16(v0 * sv, v1 * sv);
#pragma unroll
                for (int d = 0; d < 2; d++) {
                    const uint32_t (&vv)[4] = vo[h * 2 + d];
                    float oa[4] = {}, ob[4] = {};
                    mma_16816(oa, pk[48 + h * 4 + d * 2], pk[49 + h * 4 + d * 2], vv[0], vv[1], pu & mk, pu & ~mk);
                    mma_16816(ob, vv[0], vv[1], vv[2], vv[3], pv & mk, pv & ~mk);
                    qf[h * 8 + d * 4] = pack_bf16(oa[0], oa[1]); qf[h * 8 + d * 4 + 1] = pack_bf16(ob[0], ob[1]);
                    qf[h * 8 + d * 4 + 2] = pack_bf16(oa[2], oa[3]); qf[h * 8 + d * 4 + 3] = pack_bf16(ob[2], ob[3]);
                }
            }
#pragma unroll
            for (int i = 0; i < 32; i++) pk[i] = qf[i];
            named_sync(3 + w, 128);
        };
        auto pack_half = [&](const float (&acc)[64], const int OFF, float scale) INL {
#pragma unroll
            for (int i = 0; i < 32; i++) pk[OFF + i] = pack_bf16(acc[2 * i] * scale, acc[2 * i + 1] * scale);
        };
        auto gemm_run = [&]() INL {
                float acc0[64], acc1[64];
#pragma unroll
                for (int i = 0; i < 64; i++) pk[i] = 0;
#pragma unroll
                for (int j = 0; j < 4; j++) asm volatile("xor.b32 %0, %1, %2;" : "=r"(slot4[j]) : "r"(slot_a), "r"(j << 5));
                const uint32_t dA = desc_lo(base + w * 8192, 0), dB = desc_lo(base + 16384, 8192);
                const uint32_t gh_a = desc_hi(), gh_b = desc_hi();
                auto wait_full = [&](int st) INL { mbar_wait_hot(gfull + st * 8, gph); };
                auto release = [&](int st) INL { arrive_pair(gempty + st * 8); };
                bool pend = false;
                auto kstep = [&](auto st_, const int Q, bool ending = false) INL {
                    constexpr int st = decltype(st_)::v, OA = st * (G_STAGE >> 4);
                    const bool held = st == 2 && ending && w;
                    if (st == 2 && __builtin_expect(held, 0)) {
                        wg_wait<0>();
                        release(1);
                        named_sync(6, 256);
                    }
                    wait_full(st);
                    wg_fence();
                    wgmma_ss_n256<OA, OA>(acc0, acc1, dA, dB, gh_a, gh_b);
                    wg_commit();
                    wg_wait<1>();
                    arrive_pair(gempty + ((st + 3) & 3) * 8, !held);
                    wg_fence();
                    wgmma_ss_n256<OA + 2, OA + 128>(acc0, acc1, dA, dB, gh_a, gh_b);
                    wgmma_ss_n256<OA + 4, OA + 256>(acc0, acc1, dA, dB, gh_a, gh_b);
                    if (st == 3) named_arrive_if(ending && !w, 6, 256);
                    wgmma_ss_n256<OA + 6, OA + 384>(acc0, acc1, dA, dB, gh_a, gh_b);
                    wg_commit();
                    if (Q >= 0) { stage_quarter(Q); signal(Q); }
                    KTRACE(w);
                };
                wait_full(0);
                GTRACE(w);
                while (true) {
                    wg_fence();
                    wgmma_ss_n256_init(acc0, acc1, dA, dB, gh_a, gh_b);
                    wgmma_ss_n256<2, 128>(acc0, acc1, dA, dB, gh_a, gh_b);
                    wgmma_ss_n256<4, 256>(acc0, acc1, dA, dB, gh_a, gh_b);
                    wgmma_ss_n256<6, 384>(acc0, acc1, dA, dB, gh_a, gh_b);
                    wg_commit();
                    KTRACE(w);
                    const int cur = job;
                    const bool is_o = cur >= (T_O << 12), unit2 = (cur >> 6) == 3;
                    const int tail = o_tail(cur);
                    int lim = is_o ? o_head(cur) + tail : (cur < 256 ? 16 : 8);
                    int left = unit2 ? 11 : lim - (is_o ? O_STAGGER + 1 : 1);
                    bool imp = unit2;
                    next_job();
                    if (__builtin_expect(unit2, 0)) { if (tid == TRACE_TID) PTRACE(4); unit_export(cur); if (tid == TRACE_TID) PTRACE(5); }
                    if (pend) {
                        kstep(IC<1>{}, 0);
                        kstep(IC<2>{}, -1);
                        kstep(IC<3>{}, 1);
                        GTRACE(w);
                        gph ^= 1;
                        kstep(IC<0>{}, -1);
                        kstep(IC<1>{}, 2);
                        kstep(IC<2>{}, 3, left == 7);
                        kstep(IC<3>{}, -1, left == 7);
                        GTRACE(w);
                        gph ^= 1;
                        left -= 7;
                        if (left > 0) { kstep(IC<0>{}, -1); left--; }
                    }
                    int last_st = 3;
#pragma unroll 1
                    while (left > 0) {
                        auto ends = [&]() INL -> bool {
                            if (__builtin_expect(--left > 0, 1)) return false;
                            if (is_o) {
                                const uint32_t v = uniform(o_state(olim, lim - tail));
                                const int n = (v >> 1) + ((v & 1) ? 0 : tail);
                                left = n - lim; lim = n;
                            }
                            return left == 0;
                        };
                        kstep(IC<1>{}, -1);
                        if (ends()) { last_st = 1; break; }
                        kstep(IC<2>{}, -1, left == 2 && !is_o && !imp);
                        if (ends()) { last_st = 2; break; }
                        kstep(IC<3>{}, -1, left == 1 && !is_o && !imp);
                        GTRACE(w);
                        gph ^= 1;
                        if (ends()) {
                            if (!imp) break;
                            if (tid == TRACE_TID) PTRACE(6);
                            unit_import(cur);
                            if (tid == TRACE_TID) PTRACE(7);
                            imp = false; left = 4;
                        }
                        kstep(IC<0>{}, -1);
                        if (ends()) { last_st = 0; break; }
                    }
                    if (is_o) {
                        if (w) {
                            wg_wait<0>();
                            release(last_st);
                            named_sync(6, 256);
                        }
#pragma unroll 1
                        for (int i = 1; i <= O_STAGGER; i++) {
                            const int st = (last_st + i) & 3;
                            if (i > 1 && st == 0) gph ^= 1;
                            wait_full(st);
                            const uint32_t a = dA + st * (G_STAGE >> 4), b = dB + st * (G_STAGE >> 4);
                            wg_fence();
                            wgmma_ss_n256<0, 0>(acc0, acc1, a, b, gh_a, gh_b);
                            wgmma_ss_n256<2, 128>(acc0, acc1, a, b, gh_a, gh_b);
                            wgmma_ss_n256<4, 256>(acc0, acc1, a, b, gh_a, gh_b);
                            wgmma_ss_n256<6, 384>(acc0, acc1, a, b, gh_a, gh_b);
                            wg_commit();
                            named_arrive_if(!w && i == O_STAGGER, 6, 256);
                            wg_wait<1>();
                            arrive_pair(gempty + last_st * 8, i == 1 && !w);
                        }
                        slot_wait(1);
                        wg_wait<0>();
                        fence_regs(acc0);
                        fence_regs(acc1);
                        auto put = [&](const float (&acc)[64], const int Q, int off) INL {
#pragma unroll
                            for (int j = 0; j < 4; j++) {
                                const float* o = acc + Q * 32 + j * 8;
                                stmatrix_x4(slot4[j] + off, pack_bf16(o[0], o[1]), pack_bf16(o[2], o[3]), pack_bf16(o[4], o[5]), pack_bf16(o[6], o[7]));
                            }
                        };
                        put(acc0, 0, 0);
                        signal(0);
                        put(acc0, 1, 8192);
                        signal(1);
                        put(acc1, 0, -OFF_STG - w * 8192);
                        put(acc1, 1, G_STAGE - OFF_STG - w * 8192);
                        __syncwarp();
                        warp_arrive(tfull + w * 8);
#pragma unroll
                        for (int i = 1; i <= O_STAGGER; i++) release((last_st + i) & 3);
                        GTRACE(w);
#pragma unroll
                        for (int i = 0; i < 64; i++) O[i] = 0.f;
                        break;
                    }
                    if (tid == 128 && !is_o) PTRACE(12);
                    ptrans = unit2;
                    if (tid == TRACE_TID && unit2) PTRACE(1);
                    named_arrive_if(w && job >= (T_A << 12), 1, TURN_THREADS);
                    wg_wait<0>();
                    fence_regs(acc0);
                    fence_regs(acc1);
                    release(3);
                    if (tid == TRACE_TID && unit2) PTRACE(2);
                    if (__builtin_expect(unit2, 0)) { unit_attend(acc0, cur); if (tid == TRACE_TID) PTRACE(3); }
                    else if (__builtin_expect((cur >> 6) == 2, 0)) pack_k(acc0);
                    else if (cur < 128) pack_half(acc0, 0, 1.f);
                    else pack_half(acc0, 0, K_SCALE);
                    if (job >= (T_A << 12)) {
                        stage_pair();
                        signal_both();
#pragma unroll
                        for (int i = 0; i < 64; i++) asm volatile("mov.b32 %0, %1;" : "=f"(O[i]) : "f"(acc1[i]));
                        break;
                    }
                    pack_half(acc1, 32, 1.f);
                    fence_regs(pk);
                    wait_full(0);
                    pend = (cur >> 6) != 2;
                }
        };
        setup_wait();
#pragma unroll 1
        while (true) {
        gemm_run();
        if (job < 0) break;
        if (tid == 128) PTRACE(11);
        GTRACE(w);
        {
            {
                sph ^= 1;
                uint32_t step = ~0u, ajob = ~0u;
                const uint32_t dh_a = desc_hi(), dh_b = desc_hi(), dh_v = desc_hi();
                const int r0 = w * 64 + wwarp * 16 + (lane >> 2);
                float S[64];
                uint32_t P[32] = {};
                fence_regs(P);
                float m0 = 0.f, m1 = 0.f, l0 = 0.25f, l1 = 0.25f, g0 = 1.f, g1 = 1.f, e0 = 0.f, e1 = 0.f;
                constexpr float SUM_MAX = 1.1529215e18f;
                float sum_max = SUM_MAX;
                float sum_min = (lane & 3) == 0 ? 8.6736174e-19f : -1.f;
                asm volatile("" : "+f"(sum_min));
                int rem = 0;
                int maskrem = 0;
                uint32_t starts = 1;
                auto issue_S = [&]() INL {
                    const uint32_t da = desc_lo(base + OFF_Q0 + w * 8192, 0) + (ajob & 1) * ((OFF_Q1 - OFF_Q0) >> 4);
                    const uint32_t db = desc_lo(base + OFF_K0, 0) + (step & 1) * ((OFF_K1 - OFF_K0) >> 4);
                    wg_fence();
                    wgmma_ss_n128_init<0, 0, 0>(S, da, db, dh_a, dh_b);
                    wgmma_ss_n128_tb0<2, 2>(S, da, db, 1, dh_a, dh_b);
                    wgmma_ss_n128_tb0<4, 4>(S, da, db, 1, dh_a, dh_b);
                    wgmma_ss_n128_tb0<6, 6>(S, da, db, 1, dh_a, dh_b);
                    wgmma_ss_n128_tb0<1024, 1024>(S, da, db, 1, dh_a, dh_b);
                    wgmma_ss_n128_tb0<1026, 1026>(S, da, db, 1, dh_a, dh_b);
                    wgmma_ss_n128_tb0<1028, 1028>(S, da, db, 1, dh_a, dh_b);
                    wgmma_ss_n128_tb0<1030, 1030>(S, da, db, 1, dh_a, dh_b);
                    wg_commit();
                };
                auto issue_PV = [&](uint32_t t, int pass) INL {
                    const uint32_t db = desc_lo(base + OFF_V0, 16384) + (t & 1) * ((OFF_V1 - OFF_V0) >> 4);
                    mbar_wait_lean(vfull + (t & 1) * 8, (t >> 1) & 1);
                    wg_fence();
                    wgmma_rs_n128_tb1<0>(O, P[0], P[1], P[2], P[3], db, !(starts & 2), dh_v);
                    wgmma_rs_n128_tb1<128>(O, P[4], P[5], P[6], P[7], db, 1, dh_v);
                    wgmma_rs_n128_tb1<256>(O, P[8], P[9], P[10], P[11], db, 1, dh_v);
                    wgmma_rs_n128_tb1<384>(O, P[12], P[13], P[14], P[15], db, 1, dh_v);
                    if (pass) named_arrive(pass, TURN_THREADS);
                    wgmma_rs_n128_tb1<512>(O, P[16], P[17], P[18], P[19], db, 1, dh_v);
                    wgmma_rs_n128_tb1<640>(O, P[20], P[21], P[22], P[23], db, 1, dh_v);
                    wgmma_rs_n128_tb1<768>(O, P[24], P[25], P[26], P[27], db, 1, dh_v);
                    wgmma_rs_n128_tb1<896>(O, P[28], P[29], P[30], P[31], db, 1, dh_v);
                    wg_commit();
                };
                auto pv_done = [&](uint32_t t) INL {
                    wg_wait<0>();
                    fence_regs(O);
                    arrive_pair(vempty + (t & 1) * 8, t != ~0u);
                };
                auto row_max = [&](float& a0, float& a1) INL {
                    a0 = fmaxf(S[0], S[1]); a1 = fmaxf(S[2], S[3]);
#pragma unroll
                    for (int j = 1; j < 16; j++) {
                        a0 = fmaxf(a0, fmaxf(S[j * 4], S[j * 4 + 1]));
                        a1 = fmaxf(a1, fmaxf(S[j * 4 + 2], S[j * 4 + 3]));
                    }
                    a0 = fmaxf(a0, __shfl_xor_sync(0xffffffffu, a0, 1));
                    a1 = fmaxf(a1, __shfl_xor_sync(0xffffffffu, a1, 1));
                    a0 = fmaxf(a0, __shfl_xor_sync(0xffffffffu, a0, 2));
                    a1 = fmaxf(a1, __shfl_xor_sync(0xffffffffu, a1, 2));
                };
                auto mask_diag = [&]() INL {
                    const int d = (r0 & 63) - (lane & 3) * 2;
                    auto mask_block = [&](const int J0) INL {
                        bool up0 = false, up1 = false;
#pragma unroll
                        for (int j = 0; j < 8; j++) {
                            const bool c0 = j * 8 > d, c1 = j * 8 + 1 > d;
                            if (c0) S[(J0 + j) * 4] = -INFINITY;
                            if (c1) S[(J0 + j) * 4 + 1] = -INFINITY;
                            if (up0) S[(J0 + j) * 4 + 2] = -INFINITY;
                            if (up1) S[(J0 + j) * 4 + 3] = -INFINITY;
                            up0 = c0; up1 = c1;
                        }
                    };
                    if (w) {
                        mask_block(8);
                    } else {
                        mask_block(0);
#pragma unroll
                        for (int i = 32; i < 64; i++) S[i] = -INFINITY;
                    }
                };
                auto exp_part = [&](float& t0, float& t1, const int J0, const int J1, const bool SUB) INL {
#pragma unroll
                    for (int j = J0; j < J1; j++) {
                        const float e0 = ex2(SUB ? S[j * 4] - m0 : S[j * 4]), e1 = ex2(SUB ? S[j * 4 + 1] - m0 : S[j * 4 + 1]);
                        const float e2 = ex2(SUB ? S[j * 4 + 2] - m1 : S[j * 4 + 2]), e3 = ex2(SUB ? S[j * 4 + 3] - m1 : S[j * 4 + 3]);
                        t0 = (j ? t0 : l0) + (e0 + e1);
                        t1 = (j ? t1 : l1) + (e2 + e3);
                        P[j * 2] = pack_bf16(e0, e1);
                        P[j * 2 + 1] = pack_bf16(e2, e3);
                    }
                };
                auto exp_head = [&](float& t0, float& t1, auto j1_) INL {
                    constexpr int J1 = decltype(j1_)::v;
                    float E[J1 * 4];
#pragma unroll
                    for (int j = 0; j < J1; j++) {
#pragma unroll
                        for (int e = 0; e < 4; e++) E[j * 4 + e] = ex2(S[j * 4 + e]);
                        t0 = (j ? t0 : l0) + (E[j * 4] + E[j * 4 + 1]);
                        t1 = (j ? t1 : l1) + (E[j * 4 + 2] + E[j * 4 + 3]);
                    }
                    order_after(t0 + t1, bars + 508);
                    pv_done(step - 1);
                    fence_regs(P);
                    fence_regs(S);
                    fence_regs(E);
#pragma unroll
                    for (int i = 0; i < J1 * 2; i++) P[i] = pack_bf16(E[i * 2], E[i * 2 + 1]);
                };
                auto close_job = [&]() INL {
                    l0 += __shfl_xor_sync(0xffffffffu, l0, 1); l1 += __shfl_xor_sync(0xffffffffu, l1, 1);
                    l0 += __shfl_xor_sync(0xffffffffu, l0, 2); l1 += __shfl_xor_sync(0xffffffffu, l1, 2);
                    e0 = g0 * rcp(l0); e1 = g1 * rcp(l1);
                };
                auto put_O = [&]() INL {
                    mbar_wait_hot(sempty + (w * 2 + 1) * 8, sph ^ 1);
                    uint32_t a[4];
#pragma unroll
                    for (int j = 0; j < 4; j++) asm volatile("xor.b32 %0, %1, %2;" : "=r"(a[j]) : "r"(slot_a), "r"(j << 5));
                    const uint32_t h0 = pack_bf16(e0, e0), h1 = pack_bf16(e1, e1);
#pragma unroll
                    for (int q = 0; q < 8; q++) {
                        const float* o = O + q * 8;
                        stmatrix_x4(a[q & 3] + (q >> 2) * 8192, mul_bf16x2(pack_bf16(o[0], o[1]), h0), mul_bf16x2(pack_bf16(o[2], o[3]), h1),
                                    mul_bf16x2(pack_bf16(o[4], o[5]), h0), mul_bf16x2(pack_bf16(o[6], o[7]), h1));
                    }
                    sph ^= 1;
                    signal_both();
                };
                auto exp_plain = [&](float& t0, float& t1) INL {
                    exp_head(t0, t1, IC<6>{});
                    exp_part(t0, t1, 6, 16, false);
                    fence_regs(P);
                };
                auto exp_diag = [&](float& t0, float& t1) INL {
                    const int d = warp - 4, dd = (r0 & 7) - (int)(slot_a >> 6 & 6);
                    auto tri = [&](const int B) INL {
                        if (0 > dd) S[8 * B] = S[8 * B + 6] = -INFINITY;
                        if (1 > dd) S[8 * B + 1] = S[8 * B + 7] = -INFINITY;
                        S[8 * B + 4] = S[8 * B + 5] = -INFINITY;
                        asm volatile("" ::: "memory");
                    };
                    auto blocks = [&](const int B) INL {
                        auto zero = [&](const int B0) INL {
#pragma unroll
                            for (int i = 4 * B0; i < 4 * B + 12; i++) P[i] = 0;
                            asm volatile("" ::: "memory");
                        };
                        auto block = [&](const int B0) INL { exp_part(t0, t1, 2 * B0, 2 * B0 + 2, false); asm volatile("" ::: "memory"); };
                        if (d < B) zero(B);
                        else {
                            block(B);
                            if (d < B + 1) zero(B + 1);
                            else {
                                block(B + 1);
                                if (d < B + 2) zero(B + 2); else block(B + 2);
                            }
                        }
                    };
                    if (d > 3) {
                        if (d < 6) { if (d == 4) tri(4); else tri(5); } else { if (d == 6) tri(6); else tri(7); }
                        exp_head(t0, t1, IC<5>{});
                        exp_part(t0, t1, 5, 10, false);
                        blocks(5);
                    } else {
                        if (d < 2) { if (d == 0) tri(0); else tri(1); } else { if (d == 2) tri(2); else tri(3); }
                        exp_head(t0, t1, IC<2>{});
#pragma unroll
                        for (int i = 16; i < 32; i++) P[i] = 0;
                        blocks(1);
                    }
                    fence_regs(P);
                };
                auto unsafe_tile = [&](float t0, float t1) INL -> bool {
                    const bool unsafe = !(t0 + t1 <= sum_max) | !(fminf(t0, t1) >= sum_min);
                    return __any_sync(0xffffffffu, unsafe);
                };
                auto redo_tile = [&](float& t0, float& t1, bool fresh) INL {
                    wg_wait<0>();
                    fence_regs(O);
                    if (rem == maskrem) mask_diag();
                    float a0, a1;
                    row_max(a0, a1);
                    if (!fresh) { a0 = fmaxf(a0, m0); a1 = fmaxf(a1, m1); }
                    const float c0 = fresh ? 1.f : ex2(m0 - a0), c1 = fresh ? 1.f : ex2(m1 - a1);
                    m0 = a0; m1 = a1; sum_max = -1.f;
                    l0 *= c0; l1 *= c1;
#pragma unroll
                    for (int j = 0; j < 16; j++) { O[j * 4] *= c0; O[j * 4 + 1] *= c0; O[j * 4 + 2] *= c1; O[j * 4 + 3] *= c1; }
                    exp_part(t0, t1, 0, 16, true);
                };
                auto finish = [&]() INL {
                    if (starts & 2) put_O();
                    named_sync(1 + w, TURN_THREADS);
                    TRACE_MARK(0, w, step + 1);
                    issue_PV(step, w == 0 ? 2 : 0);
                    close_job();
                    pv_done(step);
                    put_O();
                };
                int njob;
                auto open_job = [&]() INL {
                    ajob++; rem = (job & 15) + 1; maskrem = (job & 512) ? 0 : job & 15;
                    njob = jobs[jb + 1];
                };
                auto do_step = [&]() INL -> bool {
                    float t0, t1;
                    const bool fresh = starts & 1, pending = starts & 2;
                    rem--; step++;
                    named_sync(1 + w, TURN_THREADS);
                    TRACE_MARK(0, w, step);
                    issue_S();
                    uint32_t ob[18];
#pragma unroll
                    for (int i = 0; i < 18; i++) asm volatile("" : "=r"(ob[i]));
                    if (__builtin_expect(pending || fresh, 0)) {
                        if (pending) {
                            const uint32_t h0 = pack_bf16(e0, e0), h1 = pack_bf16(e1, e1);
                            mbar_wait_hot(sempty + (w * 2 + 1) * 8, sph ^ 1);
#pragma unroll
                            for (int q = 0; q < 4; q++) {
                                const float* o = O + q * 8;
                                uint32_t a;
                                asm volatile("xor.b32 %0, %1, %2;" : "=r"(a) : "r"(slot_a), "r"(q << 5));
                                stmatrix_x4(a, mul_bf16x2(pack_bf16(o[0], o[1]), h0), mul_bf16x2(pack_bf16(o[2], o[3]), h1),
                                            mul_bf16x2(pack_bf16(o[4], o[5]), h0), mul_bf16x2(pack_bf16(o[6], o[7]), h1));
                            }
#pragma unroll
                            for (int i = 0; i < 16; i++) ob[i] = pack_bf16(O[32 + 2 * i], O[33 + 2 * i]);
                            ob[16] = h0; ob[17] = h1;
                            fence_regs(ob);
                        }
                        if (fresh) {
                            close_job();
                            g0 = __ldcg(g_gate + (job & 15) * 128 + r0); g1 = __ldcg(g_gate + (job & 15) * 128 + r0 + 8);
                            l0 = 0.f; l1 = 0.f; m0 = 0.f; m1 = 0.f; sum_max = SUM_MAX;
                            if (step == 0) {
                                wg_fence();
                                wg_commit();
                                named_arrive(2 - w, TURN_THREADS);
                                goto issued;
                            }
                        }
                    }
                    issue_PV(step - 1, 2 - w);
                    if (__builtin_expect(pending, 0)) {
#pragma unroll
                        for (int q = 0; q < 4; q++) {
                            uint32_t a;
                            asm volatile("xor.b32 %0, %1, %2;" : "=r"(a) : "r"(slot_a), "r"(q << 5));
                            stmatrix_x4(a + 8192, mul_bf16x2(ob[q * 4], ob[16]), mul_bf16x2(ob[q * 4 + 1], ob[17]),
                                        mul_bf16x2(ob[q * 4 + 2], ob[16]), mul_bf16x2(ob[q * 4 + 3], ob[17]));
                        }
                        sph ^= 1;
                        signal_both();
                    }
                issued:
                    starts = (starts << 1 & 2) | (rem == 0);
                    TRACE_MARK(1, w, step);
                    wg_wait<1>();
                    fence_regs(S);
                    arrive_pair(kempty + (step & 1) * 8);
                    TRACE_MARK(2, w, step);
                    warp_arrive(qempty + (ajob & 1) * 8, rem == 0);
                    bool bad;
                    if (__builtin_expect(rem != maskrem, 1)) {
                        exp_plain(t0, t1);
                        bad = unsafe_tile(t0, t1);
                        if (__builtin_expect(!bad && rem != 0, 1)) {
                            l0 = t0; l1 = t1;
                            TRACE_MARK(3, w, step);
                            return true;
                        }
                    } else {
                        exp_diag(t0, t1);
                        bad = unsafe_tile(t0, t1);
                    }
                    if (bad) redo_tile(t0, t1, fresh);
                    l0 = t0; l1 = t1;
                    TRACE_MARK(3, w, step);
                    if (rem == 0) {
                        jb++;
                        job = uniform(njob);
                        if ((job >> 12) != T_A) return false;
                        open_job();
                    }
                    return true;
                };
                open_job();
#pragma unroll 1
                while (do_step()) {}
                finish();
            }
        }
        GTRACE(w);
        jb = uniform(jb); job = uniform(job); sph = uniform(sph); gph = uniform(gph);
        if (job < 0) break;
        }
    } else {
        reg_dec<40>();
        if (base & 1023) __trap();
        if (warp == 0) {
            const uint2 r = p.first[blockIdx.x];
            const char* maps = reinterpret_cast<const char*>(&p.amap[0]);
            const CUtensorMap* wm = reinterpret_cast<const CUtensorMap*>(maps + (r.x >> (rank ? 8 : 4) & 0x780));
            const CUtensorMap* am = reinterpret_cast<const CUtensorMap*>(maps + (r.x & 0x780));
            const int wb = rank ? r.y >> 16 : r.y & 0xffff;
            setup_wait();
#pragma unroll 1
            for (int st = 1; st < 4; st++) {
                const uint32_t sa = base + st * G_STAGE;
                load_kstep(sa, sa + 16384 + rank * 16384, gfull + st * 8, G_STAGE, wm, st, wb, am, r.x >> 20, st, 1 + (r.x & 1));
            }
            named_sync(7, 96);
        } else {
            if (warp == 2) {
                const int jl = lane < MAX_JOBS ? p.jobs[blockIdx.x][lane] : -1;
                if (lane <= MAX_JOBS) jobs[lane] = jl;
                if ((jl >> 12) == T_O) *reinterpret_cast<volatile uint32_t*>(smem_raw + OFF_BAR + 504) = 2 * o_head(jl);
                if (lane == 31) *reinterpret_cast<volatile uint32_t*>(smem_raw + OFF_BAR + 528) = 0;
            } else if (warp == 3) {
                if (lane == 31) *reinterpret_cast<ulonglong2*>(smem_raw + OFF_BAR + 512) = make_ulonglong2((uint64_t)g_halo, (uint64_t)g_gate);
                if (lane < MAX_ROUNDS / 2) rounds[lane] = reinterpret_cast<const uint32_t*>(p.rounds[blockIdx.x >> 1])[lane];
            }
            named_arrive_if(warp > 1, 7, 96);
            named_sync(0, 352);
            setup_wait();
        }
        volatile uint32_t* epoch_word = reinterpret_cast<volatile uint32_t*>(smem_raw + OFF_BAR + 532);
        uint32_t epoch1 = 0;
        if (warp > 0) {
        if (warp == 3) { epoch1 = uniform(ld_acquire(g_flags + F_DONE)) / NUM_SMS + 1; if (lane == 0) *epoch_word = epoch1; }
        {
            if (warp == 1 && elect_one()) {
#pragma unroll
                for (int i = 0; i < 7; i++) prefetch_map(&p.amap[0] + i);
            }
            __syncwarp();
            if (warp < 3) __nanosleep(jobs[0] < 256 ? GATE_DELAY_LONG_NS : GATE_DELAY_SHORT_NS);
            if (tid == TRACE_GATE) PTRACE(10);
            float* gate_vals = reinterpret_cast<float*>(smem_raw + OFF_BAR + 576);
            if (warp == 3) {
                if (blockIdx.x == 0) g_flags[F_SPLIT + lane] = g_flags[F_TICKET + lane] = 0;
                named_sync(5, 96);
                if (lane < 16 && blockIdx.x + lane * NUM_SMS < SEQ) g_gate[blockIdx.x + lane * NUM_SMS] = 1.f / (1.f + __expf(-gate_vals[lane]));
                if (tid == TRACE_GATE) PTRACE(9);
                __threadfence();
                __syncwarp();
                if (lane == 0) red_release(g_flags + F_GATE);
            } else {
                const uint32_t bar = gatefull + (warp - 1) * 16;
                auto fetch = [&](int r) INL {
                    if (lane == 0) mbar_expect_tx(bar + (r & 2) * 4, 4096);
                    __syncwarp();
                    if (lane < 2) asm volatile("cp.async.bulk.shared::cluster.global.mbarrier::complete_tx::bytes [%0], [%1], 2048, [%2];"
                                               ::"r"(stg + ((warp - 1) * 8 + r + lane) * 2048), "l"(p.xp + (size_t)min((int)blockIdx.x + ((warp - 1) * 8 + r + lane) * NUM_SMS, SEQ - 1) * DM), "r"(bar + (r & 2) * 4) : "memory");
                };
                fetch(0); fetch(2);
                uint32_t gw[16];
#pragma unroll
                for (int i = 0; i < 4; i++) {
                    const uint4 t = __ldg(reinterpret_cast<const uint4*>(p.gate_w) + i * 32 + lane);
                    gw[i * 4] = t.x; gw[i * 4 + 1] = t.y; gw[i * 4 + 2] = t.z; gw[i * 4 + 3] = t.w;
                }
#pragma unroll 1
                for (int r = 0; r < 8; r += 2) {
                    mbar_wait(bar + (r & 2) * 4, r >> 2);
                    if (r < 4) fetch(r + 4);
                    fence_regs(gw);
                    float acc0 = 0.f, acc1 = 0.f;
                    uint32_t ln;
                    asm volatile("mov.u32 %0, %%laneid;" : "=r"(ln));
#pragma unroll
                    for (int i = 0; i < 4; i++) {
                        const uint4* xr = reinterpret_cast<const uint4*>(smem_raw + OFF_STG + ((warp - 1) * 8 + r) * 2048) + i * 32 + ln;
                        const uint4 a = xr[0], c = xr[128];
                        const uint32_t av[4] = {a.x, a.y, a.z, a.w}, cv[4] = {c.x, c.y, c.z, c.w};
#pragma unroll
                        for (int e = 0; e < 4; e++) {
                            const float lo = __uint_as_float(gw[i * 4 + e] << 16), hi = __uint_as_float(gw[i * 4 + e] & 0xffff0000u);
                            acc0 = fmaf(__uint_as_float(av[e] << 16), lo, acc0);
                            acc1 = fmaf(__uint_as_float(cv[e] << 16), lo, acc1);
                            acc0 = fmaf(__uint_as_float(av[e] & 0xffff0000u), hi, acc0);
                            acc1 = fmaf(__uint_as_float(cv[e] & 0xffff0000u), hi, acc1);
                        }
                    }
                    float t = (lane < 16 ? acc0 : acc1) + __shfl_xor_sync(0xffffffffu, lane < 16 ? acc1 : acc0, 16);
#pragma unroll
                    for (int o = 8; o > 0; o >>= 1) t += __shfl_xor_sync(0xffffffffu, t, o);
                    if ((lane & 15) == 0) gate_vals[(warp - 1) * 8 + r + (lane >> 4)] = t;
                }
                uint32_t t2;
                asm volatile("mov.u32 %0, %%tid.x;" : "=r"(t2));
                warp_arrive2(sempty - 16 + (t2 >> 5) * 16, sempty - 8 + (t2 >> 5) * 16);
                named_arrive(5, 96);
                if (tid == TRACE_GATE) PTRACE(9);
            }
            if (tid == TRACE_GATE) PTRACE(8);
        }
        if (warp < 3) {
            if (elect_one()) {
                const int w = warp - 1;
                uint32_t qn = 0, un = 0;
                prefetch_map(&p.qkv_st); prefetch_map(&p.st_par);
                for (int jb = 0; jb < MAX_JOBS; jb++) {
                    const int job = jobs[jb];
                    if (job < 0) break;
                    const int type = job >> 12, pl = type == T_O ? o_state(otile, 0) >> 1 : job & 0xFFF;
                    const CUtensorMap* map = &p.qkv_st;
                    int nq = 4, mt, ob0, ob1, flag, flag2 = -1;
                    bool par = false;
                    if (type <= T_O) {
                        const int n = pl >> 3;
                        mt = (pl & 7) * 2 + rank;
                        if (type == T_O)  {
                            map = &p.out_st; ob0 = (n & 3) * 4; ob1 = ob0 + 2; flag = -1;
                            for (uint32_t tries = 0; (int32_t)(ld_acquire(g_flags + F_OUT + pl * 2 + rank) - *epoch_word) < 0; tries++) {
                                __nanosleep(300);
                                if (tries > (1u << 22)) __trap();
                            }
                            fence_async_global();
                        }
                        else if (n < 16)  { ob0 = n * 4; ob1 = ob0 + 2; flag = F_Q + n * 32 + mt; flag2 = flag + 16; }
                        else if (n < 24)  {
                            mbar_wait(hout + w * 8, un++ & 1);
                            nq = ob0 = ob1 = 0; flag = F_H + mt * 8 + (n & 7);
                        } else if (n < 32) {
                            par = true; ob0 = 192 + (n & 7) * 2; ob1 = unit_head(n & 7) * 2;
                            flag = F_CTX + mt * 40 + 32 + (n & 7); flag2 = F_Q + ob1 * 8 + mt;
                        } else            { ob0 = n * 2; ob1 = ob0 + 64; flag = F_KV + (n - 32) * 16 + mt; }
                    } else {
                        nq = 2; mt = pl & 15; ob0 = ob1 = ((pl >> 4) & 31) * 2; flag = F_CTX + mt * 40 + ((pl >> 4) & 31);
                    }
                    for (int q = 0; q < nq; q++, qn++) {
                        const uint32_t slot = w * 2 + (qn & 1);
                        const int blk = (q < 2 ? ob0 : ob1) + (q & 1);
                        if (type == T_O && q == 2) {
                            mbar_wait(tfull + w * 8, 0);
                            fence_async_smem();
                            tma_reduce_add_3d(map, base + w * 8192, 0, mt * 128 + w * 64, ob1);
                            tma_reduce_add_3d(map, base + G_STAGE + w * 8192, 0, mt * 128 + w * 64, ob1 + 1);
                            bulk_commit();
                            break;
                        }
                        mbar_wait(sfull + slot * 8, (qn >> 1) & 1);
                        fence_async_smem();
                        if (type == T_O) {
                            tma_reduce_add_3d(map, stg + slot * 8192, 0, mt * 128 + w * 64, blk);
                        } else if (par) {
                            tma_store_par(&p.st_par, stg + slot * 8192, mt * 64, w, blk);
                        } else {
                            tma_store_3d(map, stg + slot * 8192, 0, mt * 128 + w * 64, blk, POL_STREAM);
                        }
                        bulk_commit();
                        if (type == T_O) continue;
                        if (!(q & 1)) continue;
                        bulk_wait_read<1>();
                        mbar_arrive(sempty + (slot ^ 1) * 8);
                        bulk_wait_read<0>();
                        mbar_arrive(sempty + slot * 8);
                    }
                    bulk_wait<0>();
                    END_MARK(jb);
                    if (flag >= 0) {
                        asm volatile("fence.release.gpu;" ::: "memory");
                        red_relaxed(g_flags + flag);
                        if (flag2 >= 0) red_relaxed(g_flags + flag2);
                    }
                }
            }
        } else {
            int jb = 0;
            for (int un = 0; (jobs[jb] >> 12) == T_P; jb++) {
                const int n = jobs[jb] >> 3, mt = (jobs[jb] & 7) * 2 + rank;
                if ((n >> 3) != 3) continue;
                wait_flags<200>(lane == 31 || (lane == 0 && mt > 0), lane == 31 ? F_GATE : F_H + max(mt - 1, 0) * 8 + (n & 7),
                                epoch1 * (lane == 31 ? GATE_COUNT : 2));
                if (lane == 0) mbar_arrive(lready + un * 8);
                un++;
            }
            if ((jobs[jb] >> 12) != T_A) {
                wait_flags<200>(lane == 0, F_GATE, epoch1 * GATE_COUNT);
                if (lane == 0) { mbar_arrive(aready); red_relaxed(g_flags + F_DONE); }
            } else {
                const int jh = jobs[jb] >> 4 & 31, jq = jobs[jb] & 15;
                wait_flags<100>(lane <= jq || lane >= 30, lane == 31 ? F_GATE : (lane == 30 ? F_Q + jh * 16 + jq : F_KV + jh * 16 + (lane & 15)),
                                epoch1 * (lane == 31 ? GATE_COUNT : 2));
                if (lane == 0) { mbar_arrive(aready); red_relaxed(g_flags + F_DONE); }
            int left = 0, nxt = jobs[jb];
            uint32_t ajob = 0;
#pragma unroll 1
            for (uint32_t astep = 0;; astep++) {
                if (left == 0) {
                    if ((nxt >> 12) != T_A) break;
                    left = (nxt & 15) + 1;
                    nxt = jobs[++jb];
                    mbar_wait(qfull + (ajob & 1) * 8, (ajob >> 1) & 1);
                    ajob++;
                }
                left--;
                mbar_wait(kfull + (astep & 1) * 8, (astep >> 1) & 1);
                named_sync(1, TURN_THREADS);
                named_sync(2, TURN_THREADS);
            }
            named_sync(1, TURN_THREADS);
            named_sync(2, TURN_THREADS);
            }
            if (jobs[jb] == (T_O << 12)) {
                mbar_wait(gatefull, 0);
                const int tile = o_state(otile, 0) >> 1;
                uint4* dst = reinterpret_cast<uint4*>(p.out) + ((tile & 7) * 256 + rank * 128) * (DM / 8) + (tile >> 3) * 32 + lane;
#pragma unroll 4
                for (int r = 0; r < 128; r++) {
                    dst[r * (DM / 8)] = make_uint4(0, 0, 0, 0);
                    if ((r & 3) == 3) __nanosleep(CLEAR_GAP_NS);
                }
                __threadfence();
                fence_async_global();
                __syncwarp();
                if (lane == 0) red_release(g_flags + F_OUT + tile * 2 + rank);
            }
        }
        } else {
            uint32_t gph = 1;
            int vrow = 0, vblk = 0;
            bool vsolo = false;
            auto load_kv = [&](uint32_t dst, uint32_t bar, int row, int blk, bool solo) INL {
                load_operand(dst, bar, &p.qkv_ld, &p.qkv_half, row, blk, rank, solo, POL_NORMAL);
            };
            auto load_v = [&](uint32_t t) INL {
                if (t == 0) mbar_wait(gempty + 24, gph);
                mbar_wait(vempty + (t & 1) * 8, ((t >> 1) & 1) ^ 1);
                load_kv(base + ((t & 1) ? OFF_V1 : OFF_V0), vfull + (t & 1) * 8, vrow, vblk, vsolo);
            };
            int jb = __ffs(__ballot_sync(0xffffffffu, lane <= MAX_JOBS && (jobs[min(lane, MAX_JOBS)] >> 12) != T_P)) - 1;
            int cur = uniform(jobs[jb]);
            auto announce = [&](uint32_t word, uint32_t v) INL {
                asm volatile("{\n.reg .pred p;\nsetp.lt.u32 p, %2, 2;\n@p red.relaxed.cluster.shared::cluster.max.u32 [%0], %1;\n}"
                             ::"r"(mapa(word, lane & 1)), "r"(v), "r"(lane) : "memory");
                __syncwarp();
            };
            uint32_t ticket = 0;
            auto draw_ticket = [&](int ojob) INL {
                asm volatile("{\n.reg .pred p;\nsetp.ne.u32 p, %2, 0;\n@p atom.relaxed.gpu.global.inc.u32 %0, [%1], 0x7fffffff;\n}"
                             : "+r"(ticket) : "l"(g_flags + F_TICKET + (ojob >> 5 & 1)), "r"((uint32_t)(rank == 0 && lane == 0)) : "memory");
                __syncwarp();
            };
            int pl = 0;
            uint32_t seen_a = 0, seen_b = 0;
            auto ask_ctx = [&]() INL {
                const uint32_t* f = g_flags + F_CTX + ((pl & 7) * 2 + rank) * 40;
                seen_a = ld_relaxed(f + lane); seen_b = ld_relaxed(f + 32 + (lane & 7));
            };
            auto open_tile = [&](int ojob) INL {
                if (rank == 0) {
                    const uint32_t t = uniform(ticket);
                    announce(otile, 2 * ((ojob & 32) ? 31 - t : t) + 1);
                }
                pl = (ojob & 32) | uniform(o_state(otile, 0) >> 1);
                ask_ctx();
            };
            const uint16_t* recs = reinterpret_cast<const uint16_t*>(rounds);
            uint32_t rec = uniform(recs[0]), nrec = uniform(recs[1]);
            int st0 = 4;
#pragma unroll 1
            for (int r = 2; rec != 0xFFFF; r++) {
                const uint32_t nnrec = recs[r];
                load_round(rec, st0, gph);
                gph ^= 1;
                st0 = 0;
                rec = nrec; nrec = uniform(nnrec);
                if (nrec == 0xFFFF || (rec & 8192)) {
                    if (nrec != 0xFFFF) {
                        prefetch_map(&p.qkv_ld); prefetch_map(&p.qkv_half);
                        if ((cur >> 12) == T_O) { prefetch_map(&p.wo_a); prefetch_map(&p.wo_b); prefetch_map(&p.out_st); }
                    } else if ((cur >> 12) == T_O) {
                        if (rec != 0xFFFF) {
                            mbar_wait(aready, 0);
                            draw_ticket(cur);
                        } else {
                            open_tile(cur);
                        }
                    }
                }
            }
            int nxt = cur;
            uint32_t astep = 0;
            if ((cur >> 12) == T_A) {
            {
                const int jh = cur >> 4 & 31, jq = cur & 15, j0 = (cur & 512) ? 0 : jq;
                mbar_wait(aready, 0);
                fence_async_global();
                mbar_wait(gempty, gph);
                load_operand(base + OFF_Q0, qfull, &p.qkv_ld, &p.qkv_ld, jq * 128, jh * 2, 0, true, POL_STREAM);
                PTRACE(17);
                mbar_wait(gempty + 8, gph);
                load_kv(base + OFF_K0, kfull, j0 * 128, 64 + jh * 2, j0 == jq && (jq & 1));
                PTRACE(16);
            }
            epoch1 = *epoch_word;
            jb++;
            nxt = uniform(jobs[jb]);
            int i = 0;
            uint32_t ajob = 1;
            bool q_issued = false;
#pragma unroll 1
            while (true) {
                const int qt = cur & 15;
                const bool last = i == qt;
                const int j = (cur & 512) ? i : qt - i, blk = (cur >> 4 & 31) * 2;
                const bool solo = j == qt && (qt & 1);
                {
                    const uint32_t sl = astep & 1;
                    if (astep == 0) {
                        mbar_wait(gempty + 16, gph);
                    } else {
                        mbar_wait(kempty + sl * 8, ((astep >> 1) & 1) ^ 1);
                        load_kv(base + (sl ? OFF_K1 : OFF_K0), kfull + sl * 8, j * 128, 64 + blk, solo);
                        if (astep == 1) PTRACE(14);
                        load_v(astep - 1);
                        if (astep == 1) PTRACE(15);
                    }
                }
                vrow = j * 128; vblk = 128 + blk; vsolo = solo;
                astep++;
                if ((nxt >> 12) != T_A) {
                    if (last) break;
                } else if (!q_issued && (last || i == 2 || (i > 2 && i >= qt - 2))) {
                    const int jh = nxt >> 4 & 31, jq = nxt & 15;
                    q_issued = wait_flags(lane <= jq || lane >= 30, lane == 31 ? F_GATE : (lane == 30 ? F_Q + jh * 16 + jq : F_KV + jh * 16 + (lane & 15)),
                                          epoch1 * (lane == 31 ? GATE_COUNT : 2), last);
                    if (q_issued) {
                        mbar_wait(qempty + (ajob & 1) * 8, ((ajob >> 1) & 1) ^ 1);
                        load_operand(base + ((ajob & 1) ? OFF_Q1 : OFF_Q0), qfull + (ajob & 1) * 8, &p.qkv_ld, &p.qkv_ld, jq * 128, jh * 2, 0, true, POL_STREAM);
                    }
                }
                i++;
                if (last) {
                    cur = nxt; jb++; nxt = uniform(jobs[jb]); i = 0; ajob++; q_issued = false;
                    if ((nxt >> 12) == T_O) { prefetch_map(&p.wo_a); prefetch_map(&p.wo_b); prefetch_map(&p.out_st); }
                }
            }
            if (nxt >= 0) draw_ticket(nxt);
            load_v(astep - 1);
            if (nxt >= 0) open_tile(nxt);
            }
            int nks = 0;
            if (nxt >= 0) {
                epoch1 = *epoch_word;
                const int m0 = (pl & 7) * 256 + rank * 128, nb = (pl >> 3 & 3) * 4 + rank * 2, part = pl >> 5 & 1;
                uint32_t ready_a = 0, ready_b = 0;
                uint32_t claim_even = 0, claim_odd = 0;
                const int head = o_head(pl), tail = o_tail(pl);
                int lim = head;
                bool known = false;
#pragma unroll 1
                for (int ks = 0;; ks++) {
                    const int st = ks & 3;
                    if (rank == 0) {
                        auto exchange = [&](uint32_t& claim) INL {
                            if (ks + 1 >= head) {
                                known = (uint32_t)uniform(claim) >= O_FLEX;
                                if (!known) lim = ks + 2;
                                announce(olim, known ? 2 * (lim + tail) + 1 : 2 * lim);
                            }
                            asm volatile("{\n.reg .pred p;\nsetp.ne.u32 p, %2, 0;\n@p atom.relaxed.gpu.global.inc.u32 %0, [%1], 0x7fffffff;\n}"
                                         : "+r"(claim) : "l"(g_flags + F_SPLIT + (pl & 31)), "r"((uint32_t)(!known && lane == 0)) : "memory");
                            __syncwarp();
                        };
                        if (!known && ks + 3 >= head) { if (ks & 1) exchange(claim_odd); else exchange(claim_even); }
                    } else if (!known && ks >= lim) {
                        const uint32_t v = uniform(o_state(olim, ks));
                        known = v & 1;
                        lim = (v >> 1) - (known ? tail : 0);
                    }
                    if (ks >= lim + tail) { nks = ks; break; }
                    if (ks == CLEAR_KS && !part) warp_arrive(gatefull);
                    int acol;
                    if (ks >= lim) acol = (part ? 64 - O_T1 : 200) + ks - lim;
                    else if (part) acol = ks < O_H1 ? O_F0 + ks : O_F0 + 2 * O_H1 + O_FLEX - 1 - ks;
                    else acol = ks < 8 ? 192 + ks : (ks < O_H0 ? ks - 8 : ks - 8 + O_H1);
                    for (uint32_t tries = 0; !(((acol < 192 ? ready_a : ready_b) >> (acol >> 1 & 31)) & 1); tries++) {
                        if (ks | tries) ask_ctx();
                        ready_a = __ballot_sync(0xffffffffu, (int32_t)(seen_a - epoch1 * 2) >= 0);
                        ready_b = __ballot_sync(0xffffffffu, (int32_t)(seen_b - epoch1 * 2) >= 0);
                        fence_acquire();
                        trap_if(tries > (1u << 22));
                    }
                    {
                        const uint32_t sa = base + st * G_STAGE;
                        if (ks < 4 && astep) mbar_wait((ks < 2 ? kempty : vempty) + ((astep - 1) & 1) * 8, ((astep - 1) >> 1) & 1);
                        else mbar_wait(gempty + st * 8, gph);
                        load_kstep(sa, sa + 16384 + rank * 16384, gfull + st * 8, G_STAGE, acol >= 192 ? &p.wo_b : &p.wo_a, acol & 63, nb,
                                   &p.qkv_half, m0, acol, 1);
                    }
                    if (st == 3) gph ^= 1;
                }
            }
            if (lane == 0) {
                if (nxt >= 0) for (int s = 0; s < 4; s++) mbar_wait(gempty + s * 8, gph ^ (s < (nks & 3)));
                else for (uint32_t t = astep; t < astep + 2; t++) {
                    mbar_wait(kempty + (t & 1) * 8, ((t >> 1) & 1) ^ 1);
                    mbar_wait(vempty + (t & 1) * 8, ((t >> 1) & 1) ^ 1);
                }
            }
        }
    }
}

typedef CUresult (*EncodeFn)(CUtensorMap*, CUtensorMapDataType, cuuint32_t, void*, const cuuint64_t*, const cuuint64_t*,
                             const cuuint32_t*, const cuuint32_t*, CUtensorMapInterleave, CUtensorMapSwizzle,
                             CUtensorMapL2promotion, CUtensorMapFloatOOBfill);

void make_map3(EncodeFn enc, CUtensorMap* m, const void* ptr, int rows, int cols, int box_rows, int box_blks, bool blocked = false) {
    cuuint64_t dims[3] = {64, (cuuint64_t)rows, (cuuint64_t)(cols / 64)};
    cuuint64_t strides[2] = {blocked ? 128 : (cuuint64_t)cols * 2, blocked ? (cuuint64_t)rows * 128 : 128};
    cuuint32_t box[3] = {64, (cuuint32_t)box_rows, (cuuint32_t)box_blks};
    cuuint32_t es[3] = {1, 1, 1};
    enc(m, CU_TENSOR_MAP_DATA_TYPE_BFLOAT16, 3, const_cast<void*>(ptr), dims, strides, box, es, CU_TENSOR_MAP_INTERLEAVE_NONE,
        CU_TENSOR_MAP_SWIZZLE_128B, CU_TENSOR_MAP_L2_PROMOTION_L2_256B, CU_TENSOR_MAP_FLOAT_OOB_FILL_NONE);
}

Params h_params;

const int16_t k_jobs[NUM_SMS][MAX_JOBS] = {
    {339,153,217,8890,8339,8802,8311,9042,8405,9008,8551,9134,8677,4128,-1,-1,-1,-1,-1,-1,-1,-1,-1,-1},
    {339,153,217,8891,8338,8803,8310,9043,8404,9009,8550,9135,8676,4128,-1,-1,-1,-1,-1,-1,-1,-1,-1,-1},
    {40,0,307,8888,8289,8720,8259,8854,8539,8898,8627,8998,8655,4128,-1,-1,-1,-1,-1,-1,-1,-1,-1,-1},
    {40,0,307,8889,8288,8721,8258,8855,8538,8899,8626,8999,8654,4128,-1,-1,-1,-1,-1,-1,-1,-1,-1,-1},
    {10,157,221,8706,8269,8820,8457,9006,8687,4128,-1,-1,-1,-1,-1,-1,-1,-1,-1,-1,-1,-1,-1,-1},
    {10,157,221,8707,8268,8821,8456,9007,8686,4128,-1,-1,-1,-1,-1,-1,-1,-1,-1,-1,-1,-1,-1,-1},
    {132,196,296,8730,8333,8940,8503,9082,8697,4128,-1,-1,-1,-1,-1,-1,-1,-1,-1,-1,-1,-1,-1,-1},
    {132,196,296,8731,8332,8941,8502,9083,8696,4128,-1,-1,-1,-1,-1,-1,-1,-1,-1,-1,-1,-1,-1,-1},
    {128,192,8758,8199,8774,8313,9026,8415,9130,8663,4128,-1,-1,-1,-1,-1,-1,-1,-1,-1,-1,-1,-1,-1},
    {128,192,8759,8198,8775,8312,9027,8414,9131,8662,4128,-1,-1,-1,-1,-1,-1,-1,-1,-1,-1,-1,-1,-1},
    {133,197,8742,8369,8704,8285,8768,8543,9022,8601,4128,-1,-1,-1,-1,-1,-1,-1,-1,-1,-1,-1,-1,-1},
    {133,197,8743,8368,8705,8284,8769,8542,9023,8600,4128,-1,-1,-1,-1,-1,-1,-1,-1,-1,-1,-1,-1,-1},
    {131,195,38,8708,8265,8932,8461,8896,8631,9076,8585,4128,-1,-1,-1,-1,-1,-1,-1,-1,-1,-1,-1,-1},
    {131,195,38,8709,8264,8933,8460,8897,8630,9077,8584,4128,-1,-1,-1,-1,-1,-1,-1,-1,-1,-1,-1,-1},
    {137,201,8750,8331,8816,8533,8912,8411,9078,8671,4128,-1,-1,-1,-1,-1,-1,-1,-1,-1,-1,-1,-1,-1},
    {137,201,8751,8330,8817,8532,8913,8410,9079,8670,4128,-1,-1,-1,-1,-1,-1,-1,-1,-1,-1,-1,-1,-1},
    {43,264,440,8744,8201,8858,8417,8954,8483,9016,8649,9152,8691,4128,-1,-1,-1,-1,-1,-1,-1,-1,-1,-1},
    {43,264,440,8745,8200,8859,8416,8955,8482,9017,8648,9153,8690,4128,-1,-1,-1,-1,-1,-1,-1,-1,-1,-1},
    {151,215,8876,8299,8964,8445,9146,8703,4128,-1,-1,-1,-1,-1,-1,-1,-1,-1,-1,-1,-1,-1,-1,-1},
    {151,215,8877,8298,8965,8444,9147,8702,4128,-1,-1,-1,-1,-1,-1,-1,-1,-1,-1,-1,-1,-1,-1,-1},
    {470,5,159,223,8772,8281,8936,8407,9066,8651,4128,-1,-1,-1,-1,-1,-1,-1,-1,-1,-1,-1,-1,-1},
    {470,5,159,223,8773,8280,8937,8406,9067,8650,4128,-1,-1,-1,-1,-1,-1,-1,-1,-1,-1,-1,-1,-1},
    {136,200,444,8760,8275,8848,8477,9040,8525,9148,8681,4128,-1,-1,-1,-1,-1,-1,-1,-1,-1,-1,-1,-1},
    {136,200,444,8761,8274,8849,8476,9041,8524,9149,8680,4128,-1,-1,-1,-1,-1,-1,-1,-1,-1,-1,-1,-1},
    {46,510,462,310,8764,8293,8862,8439,9064,8653,4128,-1,-1,-1,-1,-1,-1,-1,-1,-1,-1,-1,-1,-1},
    {46,510,462,310,8765,8292,8863,8438,9065,8652,4128,-1,-1,-1,-1,-1,-1,-1,-1,-1,-1,-1,-1,-1},
    {145,209,8894,8335,8942,8485,9098,8695,4128,-1,-1,-1,-1,-1,-1,-1,-1,-1,-1,-1,-1,-1,-1,-1},
    {145,209,8895,8334,8943,8484,9099,8694,4128,-1,-1,-1,-1,-1,-1,-1,-1,-1,-1,-1,-1,-1,-1,-1},
    {140,204,8878,8329,8934,8441,9070,8685,4128,-1,-1,-1,-1,-1,-1,-1,-1,-1,-1,-1,-1,-1,-1,-1},
    {140,204,8879,8328,8935,8440,9071,8684,4128,-1,-1,-1,-1,-1,-1,-1,-1,-1,-1,-1,-1,-1,-1,-1},
    {146,210,504,8884,8301,8966,8527,9128,8603,4128,-1,-1,-1,-1,-1,-1,-1,-1,-1,-1,-1,-1,-1,-1},
    {146,210,504,8885,8300,8967,8526,9129,8602,4128,-1,-1,-1,-1,-1,-1,-1,-1,-1,-1,-1,-1,-1,-1},
    {14,6,8868,8245,8806,8267,8938,8547,9000,8611,9108,8643,4128,-1,-1,-1,-1,-1,-1,-1,-1,-1,-1,-1},
    {14,6,8869,8244,8807,8266,8939,8546,9001,8610,9109,8642,4128,-1,-1,-1,-1,-1,-1,-1,-1,-1,-1,-1},
    {144,208,8748,8211,8836,8463,9004,8591,4128,-1,-1,-1,-1,-1,-1,-1,-1,-1,-1,-1,-1,-1,-1,-1},
    {144,208,8749,8210,8837,8462,9005,8590,4128,-1,-1,-1,-1,-1,-1,-1,-1,-1,-1,-1,-1,-1,-1,-1},
    {12,4,8740,8243,8724,8287,8930,8435,8900,8517,9086,8659,4128,-1,-1,-1,-1,-1,-1,-1,-1,-1,-1,-1},
    {12,4,8741,8242,8725,8286,8931,8434,8901,8516,9087,8658,4128,-1,-1,-1,-1,-1,-1,-1,-1,-1,-1,-1},
    {143,207,8866,8353,8752,8205,8830,8409,9056,8561,9140,8581,9104,8679,4128,-1,-1,-1,-1,-1,-1,-1,-1,-1},
    {143,207,8867,8352,8753,8204,8831,8408,9057,8560,9141,8580,9105,8678,4128,-1,-1,-1,-1,-1,-1,-1,-1,-1},
    {147,211,8872,8297,8834,8459,9030,8437,9100,8665,4128,-1,-1,-1,-1,-1,-1,-1,-1,-1,-1,-1,-1,-1},
    {147,211,8873,8296,8835,8458,9031,8436,9101,8664,4128,-1,-1,-1,-1,-1,-1,-1,-1,-1,-1,-1,-1,-1},
    {41,1,8766,8327,8828,8399,9126,8667,4128,-1,-1,-1,-1,-1,-1,-1,-1,-1,-1,-1,-1,-1,-1,-1},
    {41,1,8767,8326,8829,8398,9127,8666,4128,-1,-1,-1,-1,-1,-1,-1,-1,-1,-1,-1,-1,-1,-1,-1},
    {150,214,8882,8223,8832,8473,8980,8413,9094,8669,4128,-1,-1,-1,-1,-1,-1,-1,-1,-1,-1,-1,-1,-1},
    {150,214,8883,8222,8833,8472,8981,8412,9095,8668,4128,-1,-1,-1,-1,-1,-1,-1,-1,-1,-1,-1,-1,-1},
    {141,205,33,8726,8341,8976,8479,9024,8449,9136,8501,9144,8683,4128,-1,-1,-1,-1,-1,-1,-1,-1,-1,-1},
    {141,205,33,8727,8340,8977,8478,9025,8448,9137,8500,9145,8682,4128,-1,-1,-1,-1,-1,-1,-1,-1,-1,-1},
    {277,405,152,216,8718,8475,8902,8403,9150,8661,4128,-1,-1,-1,-1,-1,-1,-1,-1,-1,-1,-1,-1,-1},
    {277,405,152,216,8719,8474,8903,8402,9151,8660,4128,-1,-1,-1,-1,-1,-1,-1,-1,-1,-1,-1,-1,-1},
    {139,203,8886,8203,8856,8433,9032,8393,9080,8599,4128,-1,-1,-1,-1,-1,-1,-1,-1,-1,-1,-1,-1,-1},
    {139,203,8887,8202,8857,8432,9033,8392,9081,8598,4128,-1,-1,-1,-1,-1,-1,-1,-1,-1,-1,-1,-1,-1},
    {149,213,8746,8303,8982,8397,9084,8645,4128,-1,-1,-1,-1,-1,-1,-1,-1,-1,-1,-1,-1,-1,-1,-1},
    {149,213,8747,8302,8983,8396,9085,8644,4128,-1,-1,-1,-1,-1,-1,-1,-1,-1,-1,-1,-1,-1,-1,-1},
    {138,202,8870,8221,8860,8395,9060,8607,4128,-1,-1,-1,-1,-1,-1,-1,-1,-1,-1,-1,-1,-1,-1,-1},
    {138,202,8871,8220,8861,8394,9061,8606,4128,-1,-1,-1,-1,-1,-1,-1,-1,-1,-1,-1,-1,-1,-1,-1},
    {134,198,8738,8225,8728,8283,8962,8541,8992,8499,9074,8609,9124,8595,9184,8693,4128,-1,-1,-1,-1,-1,-1,-1},
    {134,198,8739,8224,8729,8282,8963,8540,8993,8498,9075,8608,9125,8594,9185,8692,4128,-1,-1,-1,-1,-1,-1,-1},
    {142,206,8874,8271,8818,8447,9068,8647,4128,-1,-1,-1,-1,-1,-1,-1,-1,-1,-1,-1,-1,-1,-1,-1},
    {142,206,8875,8270,8819,8446,9069,8646,4128,-1,-1,-1,-1,-1,-1,-1,-1,-1,-1,-1,-1,-1,-1,-1},
    {47,498,506,306,8892,8277,8784,8467,9048,8535,9020,8579,9088,8657,9186,8689,4128,-1,-1,-1,-1,-1,-1,-1},
    {47,498,506,306,8893,8276,8785,8466,9049,8534,9021,8578,9089,8656,9187,8688,4128,-1,-1,-1,-1,-1,-1,-1},
    {148,212,8762,8279,8826,8523,9002,8605,4128,-1,-1,-1,-1,-1,-1,-1,-1,-1,-1,-1,-1,-1,-1,-1},
    {148,212,8763,8278,8827,8522,9003,8604,4128,-1,-1,-1,-1,-1,-1,-1,-1,-1,-1,-1,-1,-1,-1,-1},
    {276,404,268,500,450,490,374,390,430,380,356,412,168,232,9018,8701,-1,-1,-1,-1,-1,-1,-1,-1},
    {276,404,268,500,450,490,374,390,430,380,356,412,168,232,9019,8700,-1,-1,-1,-1,-1,-1,-1,-1},
    {11,403,459,507,329,393,369,377,417,361,433,167,231,9132,8699,-1,-1,-1,-1,-1,-1,-1,-1,-1},
    {11,403,459,507,329,393,369,377,417,361,433,167,231,9133,8698,-1,-1,-1,-1,-1,-1,-1,-1,-1},
    {350,486,502,262,302,334,318,87,52,100,179,243,4096,-1,-1,-1,-1,-1,-1,-1,-1,-1,-1,-1},
    {350,486,502,262,302,334,318,87,52,100,179,243,4096,-1,-1,-1,-1,-1,-1,-1,-1,-1,-1,-1},
    {340,158,222,492,60,108,76,172,236,4096,-1,-1,-1,-1,-1,-1,-1,-1,-1,-1,-1,-1,-1,-1},
    {340,158,222,492,60,108,76,172,236,4096,-1,-1,-1,-1,-1,-1,-1,-1,-1,-1,-1,-1,-1,-1},
    {42,3,35,59,107,360,408,181,245,4096,-1,-1,-1,-1,-1,-1,-1,-1,-1,-1,-1,-1,-1,-1},
    {42,3,35,59,107,360,408,181,245,4096,-1,-1,-1,-1,-1,-1,-1,-1,-1,-1,-1,-1,-1,-1},
    {45,156,220,396,85,109,93,180,244,4096,-1,-1,-1,-1,-1,-1,-1,-1,-1,-1,-1,-1,-1,-1},
    {45,156,220,396,85,109,93,180,244,4096,-1,-1,-1,-1,-1,-1,-1,-1,-1,-1,-1,-1,-1,-1},
    {466,482,266,258,37,69,53,77,183,247,4096,-1,-1,-1,-1,-1,-1,-1,-1,-1,-1,-1,-1,-1},
    {466,482,266,258,37,69,53,77,183,247,4096,-1,-1,-1,-1,-1,-1,-1,-1,-1,-1,-1,-1,-1},
    {471,407,463,442,290,322,314,386,478,382,366,414,182,246,4096,-1,-1,-1,-1,-1,-1,-1,-1,-1},
    {471,407,463,442,290,322,314,386,478,382,366,414,182,246,4096,-1,-1,-1,-1,-1,-1,-1,-1,-1},
    {469,349,485,501,445,333,317,373,477,423,439,415,173,237,4096,-1,-1,-1,-1,-1,-1,-1,-1,-1},
    {469,349,485,501,445,333,317,373,477,423,439,415,173,237,4096,-1,-1,-1,-1,-1,-1,-1,-1,-1},
    {8,269,309,453,449,489,385,425,422,358,92,188,252,4096,-1,-1,-1,-1,-1,-1,-1,-1,-1,-1},
    {8,269,309,453,449,489,385,425,422,358,92,188,252,4096,-1,-1,-1,-1,-1,-1,-1,-1,-1,-1},
    {343,287,487,263,303,455,495,391,51,91,160,224,4096,-1,-1,-1,-1,-1,-1,-1,-1,-1,-1,-1},
    {343,287,487,263,303,455,495,391,51,91,160,224,4096,-1,-1,-1,-1,-1,-1,-1,-1,-1,-1,-1},
    {464,272,480,456,288,488,392,61,379,363,435,176,240,4096,-1,-1,-1,-1,-1,-1,-1,-1,-1,-1},
    {464,272,480,456,288,488,392,61,379,363,435,176,240,4096,-1,-1,-1,-1,-1,-1,-1,-1,-1,-1},
    {336,280,400,256,448,320,312,384,424,416,352,432,472,171,235,4096,-1,-1,-1,-1,-1,-1,-1,-1},
    {336,280,400,256,448,320,312,384,424,416,352,432,472,171,235,4096,-1,-1,-1,-1,-1,-1,-1,-1},
    {337,273,265,155,219,368,376,479,359,102,184,248,4096,-1,-1,-1,-1,-1,-1,-1,-1,-1,-1,-1},
    {337,273,265,155,219,368,376,479,359,102,184,248,4096,-1,-1,-1,-1,-1,-1,-1,-1,-1,-1,-1},
    {468,284,508,260,300,324,332,388,104,72,174,238,4096,-1,-1,-1,-1,-1,-1,-1,-1,-1,-1,-1},
    {468,284,508,260,300,324,332,388,104,72,174,238,4096,-1,-1,-1,-1,-1,-1,-1,-1,-1,-1,-1},
    {338,281,2,34,66,110,78,175,239,4096,-1,-1,-1,-1,-1,-1,-1,-1,-1,-1,-1,-1,-1,-1},
    {338,281,2,34,66,110,78,175,239,4096,-1,-1,-1,-1,-1,-1,-1,-1,-1,-1,-1,-1,-1,-1},
    {130,194,39,63,55,95,103,97,4096,-1,-1,-1,-1,-1,-1,-1,-1,-1,-1,-1,-1,-1,-1,-1},
    {130,194,39,63,55,95,103,97,4096,-1,-1,-1,-1,-1,-1,-1,-1,-1,-1,-1,-1,-1,-1,-1},
    {135,199,454,494,67,83,365,413,191,255,4096,-1,-1,-1,-1,-1,-1,-1,-1,-1,-1,-1,-1,-1},
    {135,199,454,494,67,83,365,413,191,255,4096,-1,-1,-1,-1,-1,-1,-1,-1,-1,-1,-1,-1,-1},
    {348,484,460,308,292,452,316,372,428,420,476,101,187,251,4096,-1,-1,-1,-1,-1,-1,-1,-1,-1},
    {348,484,460,308,292,452,316,372,428,420,476,101,187,251,4096,-1,-1,-1,-1,-1,-1,-1,-1,-1},
    {13,154,218,58,106,74,178,242,4096,-1,-1,-1,-1,-1,-1,-1,-1,-1,-1,-1,-1,-1,-1,-1},
    {13,154,218,58,106,74,178,242,4096,-1,-1,-1,-1,-1,-1,-1,-1,-1,-1,-1,-1,-1,-1,-1},
    {465,481,457,505,289,328,71,111,79,166,230,4096,-1,-1,-1,-1,-1,-1,-1,-1,-1,-1,-1,-1},
    {465,481,457,505,289,328,71,111,79,166,230,4096,-1,-1,-1,-1,-1,-1,-1,-1,-1,-1,-1,-1},
    {44,270,446,294,326,65,81,89,161,225,4096,-1,-1,-1,-1,-1,-1,-1,-1,-1,-1,-1,-1,-1},
    {44,270,446,294,326,65,81,89,161,225,4096,-1,-1,-1,-1,-1,-1,-1,-1,-1,-1,-1,-1,-1},
    {9,511,503,295,327,375,399,381,437,353,409,473,169,233,4096,-1,-1,-1,-1,-1,-1,-1,-1,-1},
    {9,511,503,295,327,375,399,381,437,353,409,473,169,233,4096,-1,-1,-1,-1,-1,-1,-1,-1,-1},
    {347,283,483,259,291,491,331,371,431,383,367,99,186,250,4096,-1,-1,-1,-1,-1,-1,-1,-1,-1},
    {347,283,483,259,291,491,331,371,431,383,367,99,186,250,4096,-1,-1,-1,-1,-1,-1,-1,-1,-1},
    {274,282,458,261,293,493,397,389,429,421,357,75,189,253,4096,-1,-1,-1,-1,-1,-1,-1,-1,-1},
    {274,282,458,261,293,493,397,389,429,421,357,75,189,253,4096,-1,-1,-1,-1,-1,-1,-1,-1,-1},
    {278,286,406,32,64,56,48,88,170,234,4096,-1,-1,-1,-1,-1,-1,-1,-1,-1,-1,-1,-1,-1},
    {278,286,406,32,64,56,48,88,170,234,4096,-1,-1,-1,-1,-1,-1,-1,-1,-1,-1,-1,-1,-1},
    {279,351,271,447,298,330,394,370,426,378,354,434,164,228,4096,-1,-1,-1,-1,-1,-1,-1,-1,-1},
    {279,351,271,447,298,330,394,370,426,378,354,434,164,228,4096,-1,-1,-1,-1,-1,-1,-1,-1,-1},
    {344,345,497,257,297,321,313,82,50,90,98,96,4096,-1,-1,-1,-1,-1,-1,-1,-1,-1,-1,-1},
    {344,345,497,257,297,321,313,82,50,90,98,96,4096,-1,-1,-1,-1,-1,-1,-1,-1,-1,-1,-1},
    {129,193,311,335,319,86,438,364,436,163,227,4096,-1,-1,-1,-1,-1,-1,-1,-1,-1,-1,-1,-1},
    {129,193,311,335,319,86,438,364,436,163,227,4096,-1,-1,-1,-1,-1,-1,-1,-1,-1,-1,-1,-1},
    {341,285,509,461,301,325,398,80,418,362,410,474,177,241,4096,-1,-1,-1,-1,-1,-1,-1,-1,-1},
    {341,285,509,461,301,325,398,80,418,362,410,474,177,241,4096,-1,-1,-1,-1,-1,-1,-1,-1,-1},
    {342,275,267,499,299,451,395,57,49,73,185,249,4096,-1,-1,-1,-1,-1,-1,-1,-1,-1,-1,-1},
    {342,275,267,499,299,451,395,57,49,73,185,249,4096,-1,-1,-1,-1,-1,-1,-1,-1,-1,-1,-1},
    {346,402,496,304,443,323,315,387,427,419,355,411,165,229,4096,-1,-1,-1,-1,-1,-1,-1,-1,-1},
    {346,402,496,304,443,323,315,387,427,419,355,411,165,229,4096,-1,-1,-1,-1,-1,-1,-1,-1,-1},
    {15,401,305,441,70,62,54,94,190,254,4096,-1,-1,-1,-1,-1,-1,-1,-1,-1,-1,-1,-1,-1},
    {15,401,305,441,70,62,54,94,190,254,4096,-1,-1,-1,-1,-1,-1,-1,-1,-1,-1,-1,-1,-1},
    {467,7,36,68,84,105,475,162,226,4096,-1,-1,-1,-1,-1,-1,-1,-1,-1,-1,-1,-1,-1,-1},
    {467,7,36,68,84,105,475,162,226,4096,-1,-1,-1,-1,-1,-1,-1,-1,-1,-1,-1,-1,-1,-1},
};

void build_rounds() {
    for (int c = 0; c < NUM_SMS / 2; c++) {
        const int16_t* jobs = h_params.jobs[2 * c];
        int nr = 0, prev_key = -1, last = 0;
        for (int j = 0; (jobs[j] >> 12) == T_P; j++) {
            const int n = jobs[j] >> 3, a = n >= 32, unit = n >= 16 && n < 32 ? (n >> 3) - 1 : 0, cnt = a ? 2 : 4;
            const int key = (jobs[j] & 7) | a << 3 | (unit > 0) << 4;
            const int wm = n < 16 ? 0 : (n < 32 ? 1 : n >> 4 & 1), col = n < 16 ? n : (n < 32 ? n & 7 : n & 15);
            const bool keep = key == prev_key, final_tile = (jobs[j + 1] >> 12) != T_P;
            const int k0 = keep ? last : 0;
            for (int r = 0; r < cnt; r++) {
                last = (k0 + r) % cnt;
                h_params.rounds[c][nr++] = (uint16_t)((key & 15) | wm << 4 | col << 6 | last << 10 | (keep && r == 0) << 12 | (final_tile && r == 0) << 13 | unit << 14);
            }
            prev_key = key;
        }
        while (nr < MAX_ROUNDS) h_params.rounds[c][nr++] = 0xFFFF;
        {
            const uint32_t rec = h_params.rounds[c][0], col = rec >> 6 & 15, unit = rec >> 14;
            for (uint32_t r = 0; r < 2; r++) {
                uint32_t wm[2], wb[2];
                for (uint32_t h = 0; h < 2; h++) {
                    wm[h] = 2 + ((rec & 8) ? 2 + h : ((rec >> 15) && h ? 0 : rec >> 4 & 1));
                    wb[h] = (rec & 8) ? (col + (rec & 16)) * 2
                                      : (unit == 0 ? col * 4 + h * 2 : (unit == 1 ? 16 + h * 16 + col * 2 : (h ? unit_head(col) : col) * 2));
                }
                const uint32_t am = unit ? 6 : (rec >> 3 & 1), arow = unit ? (rec & 7) * 128 + r * 64 : (rec & 7) * 256 + r * 128;
                h_params.first[2 * c + r] = make_uint2((unit ? 1 : 0) | am << 7 | wm[0] << 11 | wm[1] << 15 | arow << 20, wb[0] | wb[1] << 16);
            }
        }
    }
}

void build_schedule() {
    for (int c = 0; c < NUM_SMS; c++) {
        for (int j = 0; j < MAX_JOBS; j++) h_params.jobs[c][j] = k_jobs[c][j];
    }
    build_rounds();
}

}

extern "C" void kernel_launch(void* const* d_in, const int* in_sizes, int n_in, void* d_out, int out_size) {
    (void)in_sizes; (void)n_in; (void)out_size;
    static EncodeFn enc = nullptr;
    if (!enc) {
        cudaDriverEntryPointQueryResult qr;
        void* fn = nullptr;
        cudaGetDriverEntryPoint("cuTensorMapEncodeTiled", &fn, cudaEnableDefault, &qr);
        enc = (EncodeFn)fn;
        cudaFuncSetAttribute(fused_kernel, cudaFuncAttributeMaxDynamicSharedMemorySize, SMEM_BYTES);
        build_schedule();
    }
    void* qkv;
    cudaGetSymbolAddress(&qkv, g_qkv);
    Params& p = h_params;
    make_map3(enc, &p.amap[0], d_in[0], SEQ, DM, 128, 1);
    make_map3(enc, &p.amap[1], d_in[1], SEQ, DC, 128, 1);
    make_map3(enc, &p.wmap[0], d_in[2], DM, 4096, 64, 2);
    make_map3(enc, &p.wmap[2], d_in[3], DC, 4096, 64, 2);
    make_map3(enc, &p.wmap[3], d_in[4], DC, 4096, 64, 2);
    make_map3(enc, &p.wmap[1], d_in[7], DM, 3072, 64, 2);
    make_map3(enc, &p.wo_a, d_in[5], 4096, DM, 64, 2);
    make_map3(enc, &p.wo_b, d_in[8], DM, DM, 64, 2);
    make_map3(enc, &p.qkv_st, qkv, SEQ, QKV_W, 64, 1, true);
    make_map3(enc, &p.qkv_ld, qkv, SEQ, QKV_W, 128, 2, true);
    make_map3(enc, &p.qkv_half, qkv, SEQ, QKV_W, 128, 1, true);
    {
        cuuint64_t dims[4] = {64, SEQ / 2, 2, QKV_W / 64}, strides[3] = {256, 128, (cuuint64_t)SEQ * 128};
        cuuint32_t box[4] = {64, 64, 1, 1}, es[4] = {1, 1, 1, 1};
        enc(&p.st_par, CU_TENSOR_MAP_DATA_TYPE_BFLOAT16, 4, qkv, dims, strides, box, es, CU_TENSOR_MAP_INTERLEAVE_NONE,
            CU_TENSOR_MAP_SWIZZLE_128B, CU_TENSOR_MAP_L2_PROMOTION_L2_256B, CU_TENSOR_MAP_FLOAT_OOB_FILL_NONE);
        dims[3] = DM / 64; strides[0] = DM * 4; strides[1] = DM * 2; strides[2] = 128; box[2] = 2;
        enc(&p.x_par, CU_TENSOR_MAP_DATA_TYPE_BFLOAT16, 4, d_in[0], dims, strides, box, es, CU_TENSOR_MAP_INTERLEAVE_NONE,
            CU_TENSOR_MAP_SWIZZLE_128B, CU_TENSOR_MAP_L2_PROMOTION_L2_256B, CU_TENSOR_MAP_FLOAT_OOB_FILL_NONE);
    }
    make_map3(enc, &p.out_st, d_out, SEQ, DM, 64, 1);
    p.xp = (const __nv_bfloat16*)d_in[0];
    p.gate_w = (const __nv_bfloat16*)d_in[9];
    p.out = (__nv_bfloat16*)d_out;
    fused_kernel<<<NUM_SMS, 384, SMEM_BYTES, cudaStreamPerThread>>>(p);
}
```
